```python
import torch

def _softmax(x, axis=-1):
    return torch.softmax(x, dim=axis)
def _gelu(x):
    return torch.nn.functional.gelu(x, approximate="tanh")
def _silu(x):
    return torch.nn.functional.silu(x)
def _sigmoid(x):
    return torch.sigmoid(x)
def _layernorm(x, axis=-1, eps=1e-5):
    m = x.mean(dim=axis, keepdim=True)
    v = x.var(dim=axis, keepdim=True, unbiased=False)
    return (x - m) / torch.sqrt(v + eps)
def _scatter_add(tgt, idx, src, axis=0):
    return tgt.clone().index_add_(axis, idx, src)
def _segment_sum(src, seg, n):
    out = torch.zeros((n,) + src.shape[1:], dtype=src.dtype)
    return out.index_add_(0, seg, src)
def _pad(x, pw):
    flat = tuple(v for pair in reversed(pw) for v in pair)
    return torch.nn.functional.pad(x, flat)

kernel_name = 'interleave_layers__sliding_block_cached__dense_activation_gelu__decode'

def setup_inputs():

    _w = (lambda a: (lambda t: t.to(torch.bfloat16) if t.is_floating_point() else t)(torch.as_tensor(a)))
    def _A_setup():
        B, Sq, D = 1, 1, 640
        Hq, Hkv, Sk, Dh = 32, 32, 32768, 192
        assert Hq % Hkv == 0, (Hq, Hkv)
        return {
            "x": _w((lambda *s: torch.randn(*s, dtype=torch.bfloat16) * 0.1)(B, Sq, D)),
            "k_cache": _w((lambda *s: torch.randn(*s, dtype=torch.bfloat16) * 0.8)(B, Hkv, Sk, Dh)),
            "v_cache": _w((lambda *s: torch.randn(*s, dtype=torch.bfloat16) * 1.6)(B, Hkv, Sk, Dh)),
            "wq": _w((lambda *s: torch.randn(*s, dtype=torch.bfloat16) * 0.8)(D, Hq * Dh) * (D ** -0.5)),
            "wo": _w((lambda *s: torch.randn(*s, dtype=torch.bfloat16) * 1.6)(Hq * Dh, D) * ((Hq * Dh) ** -0.5)),
        }
    _A_in = _A_setup()

    def _B_setup():
        B, S, D, F = 1, 1, 640, 1536
        return {
            "x": _w((lambda *s: torch.randn(*s, dtype=torch.bfloat16) * 0.1)(B, S, D)),
            "w1": _w((lambda *s: torch.randn(*s, dtype=torch.bfloat16) * 0.4)(D, F) * (D ** -0.5)),
            "b1": _w((lambda *s: torch.randn(*s, dtype=torch.bfloat16) * 0.4)(F) * 0.01),
            "w2": _w((lambda *s: torch.randn(*s, dtype=torch.bfloat16) * 0.4)(F, D) * (F ** -0.5)),
            "b2": _w((lambda *s: torch.randn(*s, dtype=torch.bfloat16) * 0.4)(D) * 0.01),
        }
    _B_in = _B_setup()

    return {
        "A_x": _A_in["x"],
        "A_k_cache": _A_in["k_cache"],
        "A_v_cache": _A_in["v_cache"],
        "A_wq": _A_in["wq"],
        "A_wo": _A_in["wo"],
        "B_x": _B_in["x"],
        "B_w1": _B_in["w1"],
        "B_b1": _B_in["b1"],
        "B_w2": _B_in["w2"],
        "B_b2": _B_in["b2"],
    }

def reference(A_x, A_k_cache, A_v_cache, A_wq, A_wo, B_x, B_w1, B_b1, B_w2, B_b2):
    def _A_ref(x, k_cache, v_cache, wq, wo):
        B, Sq, D = x.shape
        Hq, Dh = 32, 192
        Hkv, Sk = k_cache.shape[1], k_cache.shape[2]
        W = min(4096, max(256, Sk // 4))
        rep = Hq // Hkv
        q = (lambda x, *d: x.permute(*d))((x @ wq).reshape(B, Sq, Hq, Dh), 0, 2, 1, 3)
        k = (lambda x, n, axis: torch.repeat_interleave(x, n, dim=axis))(k_cache[:, :, Sk - W:, :], rep, axis=1)
        v = (lambda x, n, axis: torch.repeat_interleave(x, n, dim=axis))(v_cache[:, :, Sk - W:, :], rep, axis=1)
        scores = torch.einsum("bhqd,bhkd->bhqk", q, k) * (Dh ** -0.5)
        p = _softmax(scores, axis=-1)
        o = torch.einsum("bhqk,bhkd->bhqd", p, v)
        return (lambda x, *d: x.permute(*d))(o, 0, 2, 1, 3).reshape(B, Sq, Hq * Dh) @ wo

    def _B_ref(x, w1, b1, w2, b2):
        h = torch.einsum("bsd,df->bsf", x, w1) + b1
        h = _gelu(h)
        return torch.einsum("bsf,fd->bsd", h, w2) + b2

    x = A_x
    x = x + _A_ref(_layernorm(x, axis=-1), A_k_cache, A_v_cache, A_wq, A_wo)
    x = x + _B_ref(_layernorm(x, axis=-1), B_w1, B_b1, B_w2, B_b2)
    x = x + _A_ref(_layernorm(x, axis=-1), A_k_cache, A_v_cache, A_wq, A_wo)
    x = x + _B_ref(_layernorm(x, axis=-1), B_w1, B_b1, B_w2, B_b2)
    return x
```

```cpp
#include <cuda_runtime.h>
#include <cuda_bf16.h>
#include <cuda.h>
#include <stdint.h>

namespace {

constexpr int D_MODEL = 640, NHEAD = 32, SK = 32768, DH = 192, WIN = 4096, DFF = 1536;
constexpr int NCTA = 128, NTHR = 256;
constexpr int SUB = 8 * DH * 2;
constexpr int HT = 4 * SUB;
constexpr int WOU = 8 * 320;
constexpr int XCAP = 48;
constexpr int SM_RING = 1024;
constexpr int SM_W2 = SM_RING + 8 * WOU;
constexpr int SM_PK = SM_W2 + 15360;
constexpr int SM_WQ = SM_RING + 5 * HT;
constexpr int SM_KS = SM_WQ + 5 * HT;
constexpr int SM_PART = SM_KS + 8 * HT;
constexpr int SM_BAR = SM_PART + 6144;
constexpr int SM_VEC = SM_BAR + 512;
constexpr int SM_QU = SM_VEC + 384;
constexpr int SM_ZQ = SM_QU + 384;
constexpr int SM_CS = SM_ZQ + 64;
constexpr int SM_XR = SM_CS + 768;
constexpr int SM_XM = SM_XR + XCAP * 16;
constexpr int SM_SH = SM_XM + XCAP * 4;
constexpr int SM_C1 = SM_SH + 1024;
constexpr int SM_ML = SM_C1 + 320;
constexpr int SM_B1 = SM_ML + 64;
constexpr int SM_STAT = SM_B1 + 128;
constexpr int SM_QBAR = SM_STAT + 40;
constexpr int SM_CBAR = SM_QBAR + 8;
constexpr int SM_CNT = SM_CBAR + 128;
constexpr int SM_XN = SM_CNT + 56;
constexpr int SM_BIG = SM_XN + 4;
constexpr int SM_EPOCH = SM_BIG + 4;
constexpr int SM_FXS = SM_EPOCH + 4;
constexpr int SM_T0 = SM_FXS + 4;
constexpr int SM_TS = SM_T0 + 4;
constexpr int SM_TOTAL = 232448;
static_assert(SM_TS + 160 <= SM_RING + SM_TOTAL, "smem");

constexpr int SPIN = 1 << 20;
enum { TM_WQ = 0, TM_K = 1, TM_V = 2, TM_VP = 3, TM_V8 = 4, TM_WO = 5, TM_W1 = 6, TM_WO4 = 7, TM_W2 = 8, TM_WOP = 9 };
constexpr uint32_t POL_NORMAL = 0x16F00000u, POL_FIRST = 0x12F00000u;

#define PACE 484
#define PACE0 1900
#define KEEP0 32
#define NP 3
#define VORD 0x456789a321b0cdefull
#define CORD 0x2fedcba987654310ull
#define ISS 0x0010111010111111ull
#define X2AT 9
#define R56 6
#define PRE 6
#define KSL 0
#define PK0 32
#define PKD 12
#define NPK 6
#define XAT 94
#define LEAD 4
#define ARDELAY 600
#define QDELAY 220
#define PUBAT 7
#define ZCHK 12
#define S6D 900
#define S6G 200
#define XD 600
#define XG 200
#define TB 2
#define WOPACE 403
#define WOD 0
#define NPF0 2
#define HWAT 11
#define HWC 13
#define ODELAY1 600
#define ODELAY2 200
#define W1P 9999
#define W2P 600
#define W2LATE 0
#define NOW12 0
#define W1PROMO 2
#define W1FIRST 1
#define WOPROMO 2
#define NPFC 8
#define PFD 1200
#define PFG 250
#define PFPOL POL_NORMAL
#define E3 0
#define NI0 3
#define W1ST 0
#define W1D 0
#define W1POL POL_FIRST
#define WOKEEP 2
#define WPF2 8
#define WOPF 99
#define QLATE 0
#define W2POL POL_NORMAL
#define FX2LIM 524288.f

struct Plan { int slot[18], par[18], nld[16], ld[16][3]; bool ok; };
__host__ __device__ constexpr int cord(int s) { return (int)(CORD >> (4 * s) & 15); }
constexpr Plan make_plan() {
    Plan s{};
    int phase[7] = {}, state[18] = {}, freeat[7] = {}, k = 0;
    for (int p = 0; p < 7; p++) { s.slot[p] = p; s.par[p] = phase[p]++ & 1; state[p] = 1; freeat[p] = -1; }
    s.ok = true;
    for (int st = 0; st < 16; st++) {
        const int p = cord(st);
        if (state[p] != 1 || (p == 2 && !state[16])) s.ok = false;
        state[p] = 2;
        freeat[p == 2 ? s.slot[16] : s.slot[p]] = st;
        for (int n = (int)(ISS >> (4 * st) & 15); n > 0; n--, k++) {
            const int it = k < X2AT ? 7 + k : k == X2AT ? 16 : k < 10 ? 6 + k : 17;
            int best = -1;
            for (int c = 0; c < 7; c++) if (c != 2 && freeat[c] >= 0 && (c < 5 || k < R56) && (best < 0 || freeat[c] < freeat[best])) best = c;
            if (it == 17) best = freeat[5] >= 0 && freeat[6] >= 0 ? 5 : -1;
            if (best < 0 || k > 10 || s.nld[st] == 3) { s.ok = false; return s; }
            s.slot[it] = best; freeat[best] = -1; state[it] = 1;
            if (it != 16) s.par[it] = phase[best]++ & 1;
            s.ld[st][s.nld[st]++] = it;
        }
    }
    if (k != 11) s.ok = false;
    return s;
}
constexpr Plan PL = make_plan();
static_assert(PL.ok, "bad pass-2 plan");
__host__ __device__ constexpr int vunit(int p) { return (int)(VORD >> (4 * p) & 15); }

template <int I> struct IC { static constexpr int value = I; };
template <int A, int B, class F> __device__ __forceinline__ void static_for(F&& f) {
    if constexpr (A < B) { f(IC<A>{}); static_for<A + 1, B>(f); }
}

struct Params {
    CUtensorMap tm[10];
    const __nv_bfloat16 *x, *b1, *b2, *k;
    __nv_bfloat16* out;
};

typedef unsigned long long u64;
constexpr int ACC_PITCH = 256;
constexpr int ACC_BYTES = 80 * ACC_PITCH;
__device__ __align__(1024) unsigned char g_acc[4 * ACC_BYTES];
__device__ __align__(1024) u64 g_ll[3][NCTA][256];
__device__ unsigned g_epoch;
__device__ __align__(128) unsigned g_zflag;
#define DBG(i, v)
#define TS(i)
#define TSB(i)
#define TSA(i)
#define TR(k, i)

__device__ __forceinline__ void mbar_wait(uint32_t bar, uint32_t parity) {
    asm volatile("{\n.reg .pred p, q;\n.reg .u32 n;\nmov.u32 n, 0;\n"
                 "LOOP:\nmbarrier.try_wait.parity.shared::cta.b64 p, [%0], %1;\n"
                 "add.u32 n, n, 1;\nsetp.lt.and.u32 q, n, 0x100000, !p;\n@q bra.uni LOOP;\n}"
                 :: "r"(bar), "r"(parity) : "memory");
}
__device__ __forceinline__ bool elect() {
    uint32_t r;
    asm volatile("{\n.reg .pred p;\nelect.sync _|p, 0xffffffff;\nselp.u32 %0, 1, 0, p;\n}" : "=r"(r));
    return r != 0;
}
__device__ __forceinline__ void mbar_init(uint32_t bar, uint32_t n) { asm volatile("mbarrier.init.shared::cta.b64 [%0], %1;" :: "r"(bar), "r"(n) : "memory"); }
__device__ __forceinline__ void mbar_arrive(uint32_t bar) { asm volatile("mbarrier.arrive.shared::cta.b64 _, [%0];" :: "r"(bar) : "memory"); }
__device__ __forceinline__ void mbar_expect(uint32_t bar, uint32_t bytes) {
    asm volatile("mbarrier.arrive.expect_tx.shared::cta.b64 _, [%0], %1;" :: "r"(bar), "r"(bytes) : "memory");
}
__device__ __forceinline__ void fence_async() { asm volatile("fence.proxy.async.shared::cta;" ::: "memory"); }
#define DI __device__ __forceinline__
DI uint32_t ad(uint32_t a, uint32_t o) { uint32_t r; asm("add.u32 %0, %1, %2;" : "=r"(r) : "r"(a), "r"(o)); return r; }
DI uint4 lds128(uint32_t a, int o) {
    uint4 v; asm volatile("ld.shared.v4.u32 {%0,%1,%2,%3}, [%4];" : "=r"(v.x), "=r"(v.y), "=r"(v.z), "=r"(v.w) : "r"(ad(a, o)) : "memory"); return v;
}
DI void lds128(uint32_t* v, uint32_t a, int o) {
    asm volatile("ld.shared.v4.u32 {%0,%1,%2,%3}, [%4];" : "=r"(v[0]), "=r"(v[1]), "=r"(v[2]), "=r"(v[3]) : "r"(ad(a, o)) : "memory");
}
DI void lds64(uint32_t* v, uint32_t a, int o) { asm volatile("ld.shared.v2.u32 {%0,%1}, [%2];" : "=r"(v[0]), "=r"(v[1]) : "r"(ad(a, o)) : "memory"); }
DI uint4 ldsm_t(uint32_t a, int o) {
    uint4 v; asm volatile("ldmatrix.sync.aligned.m8n8.x4.trans.shared.b16 {%0,%1,%2,%3}, [%4];" : "=r"(v.x), "=r"(v.y), "=r"(v.z), "=r"(v.w) : "r"(ad(a, o)) : "memory"); return v;
}
DI uint2 lds64(uint32_t a, int o) { uint2 v; asm volatile("ld.shared.v2.u32 {%0,%1}, [%2];" : "=r"(v.x), "=r"(v.y) : "r"(ad(a, o)) : "memory"); return v; }
DI float2 lds64f(uint32_t a, int o) { const uint2 v = lds64(a, o); return make_float2(__uint_as_float(v.x), __uint_as_float(v.y)); }
DI uint32_t lds32(uint32_t a, int o) { uint32_t v; asm volatile("ld.shared.u32 %0, [%1];" : "=r"(v) : "r"(ad(a, o)) : "memory"); return v; }
DI float ldsf(uint32_t a, int o) { return __uint_as_float(lds32(a, o)); }
DI void sts32(uint32_t a, int o, uint32_t v) { asm volatile("st.shared.u32 [%0], %1;" :: "r"(ad(a, o)), "r"(v) : "memory"); }
DI void stsf(uint32_t a, int o, float v) { sts32(a, o, __float_as_uint(v)); }
DI void sts16(uint32_t a, int o, uint32_t v) { asm volatile("st.shared.u16 [%0], %1;" :: "r"(ad(a, o)), "h"((uint16_t)v) : "memory"); }
DI void sts64(uint32_t a, int o, uint32_t x, uint32_t y) { asm volatile("st.shared.v2.u32 [%0], {%1,%2};" :: "r"(ad(a, o)), "r"(x), "r"(y) : "memory"); }
DI void sts64f(uint32_t a, int o, float x, float y) { sts64(a, o, __float_as_uint(x), __float_as_uint(y)); }
DI void sts128(uint32_t a, int o, uint32_t x, uint32_t y, uint32_t z, uint32_t w) {
    asm volatile("st.shared.v4.u32 [%0], {%1,%2,%3,%4};" :: "r"(ad(a, o)), "r"(x), "r"(y), "r"(z), "r"(w) : "memory");
}
DI void sts128f(uint32_t a, int o, const float (&v)[4]) {
    asm volatile("st.shared.v4.f32 [%0], {%1,%2,%3,%4};" :: "r"(ad(a, o)), "f"(v[0]), "f"(v[1]), "f"(v[2]), "f"(v[3]) : "memory");
}
__device__ __forceinline__ uint32_t atoms_inc(uint32_t a, uint32_t lim) {
    uint32_t old; asm volatile("atom.relaxed.cta.shared.inc.u32 %0, [%1], %2;" : "=r"(old) : "r"(a), "r"(lim) : "memory"); return old;
}
__device__ __forceinline__ void mma(float (&c)[4], uint32_t a0, uint32_t a1, uint32_t a2, uint32_t a3, uint32_t b0, uint32_t b1) {
    asm volatile("mma.sync.aligned.m16n8k16.row.col.f32.bf16.bf16.f32 {%0,%1,%2,%3}, {%4,%5,%6,%7}, {%8,%9}, {%0,%1,%2,%3};"
                 : "+f"(c[0]), "+f"(c[1]), "+f"(c[2]), "+f"(c[3]) : "r"(a0), "r"(a1), "r"(a2), "r"(a3), "r"(b0), "r"(b1));
}
__device__ __forceinline__ void mma(float (&c)[4], const uint4& a, uint32_t b0, uint32_t b1) { mma(c, a.x, a.y, a.z, a.w, b0, b1); }
__device__ __forceinline__ void zero4(float (&c)[4]) { c[0] = c[1] = c[2] = c[3] = 0.f; }
__device__ __forceinline__ u64 ld_rlx(const void* p) {
    u64 a; asm volatile("ld.relaxed.gpu.global.u64 %0, [%1];" : "=l"(a) : "l"(p) : "memory"); return a;
}
__device__ __forceinline__ void ld_rlx2(const void* p, u64& a, u64& b) {
    asm volatile("ld.relaxed.gpu.global.v2.u64 {%0,%1}, [%2];" : "=l"(a), "=l"(b) : "l"(p) : "memory");
}
__device__ __forceinline__ void st_rlx(void* p, u64 a) { asm volatile("st.relaxed.gpu.global.u64 [%0], %1;" :: "l"(p), "l"(a) : "memory"); }
__device__ __forceinline__ uint4 ldg128(const void* p) {
    uint4 v; asm volatile("ld.global.nc.L1::no_allocate.L2::cache_hint.v4.u32 {%0,%1,%2,%3}, [%4], %5;" : "=r"(v.x), "=r"(v.y), "=r"(v.z), "=r"(v.w) : "l"(p), "l"((u64)POL_FIRST << 32)); return v;
}
__device__ __forceinline__ u64 ll_pack(float v, uint32_t tag) { return ((u64)tag << 32) | __float_as_uint(v); }
__device__ __forceinline__ float ll_val(u64 w) { return __uint_as_float((uint32_t)w); }
__device__ __forceinline__ uint32_t ll_tag(u64 w) { return (uint32_t)(w >> 32); }
__device__ __forceinline__ float bf_lo(uint32_t u) { return __uint_as_float(u << 16); }
__device__ __forceinline__ float bf_hi(uint32_t u) { return __uint_as_float(u & 0xffff0000u); }
__device__ __forceinline__ uint32_t pack_bf(float lo, float hi) {
    uint32_t r; asm("cvt.rn.bf16x2.f32 %0, %1, %2;" : "=r"(r) : "f"(hi), "f"(lo)); return r;
}
__device__ __forceinline__ uint32_t bf2_amax(uint32_t a, uint32_t b) { uint32_t r; asm("max.NaN.xorsign.abs.bf16x2 %0, %1, %2;" : "=r"(r) : "r"(a), "r"(b)); return r; }
__device__ __forceinline__ uint32_t bf2_amin(uint32_t a, uint32_t b) { uint32_t r; asm("min.xorsign.abs.bf16x2 %0, %1, %2;" : "=r"(r) : "r"(a), "r"(b)); return r; }
__device__ __forceinline__ uint32_t bf2_mulv(uint32_t a, uint32_t b) { uint32_t r; asm volatile("mul.rn.bf16x2 %0, %2, %1;" : "=r"(r) : "r"(a), "r"(b)); return r; }
__device__ __forceinline__ uint32_t bf2_mul(uint32_t a, uint32_t b) { uint32_t r; asm("mul.rn.bf16x2 %0, %1, %2;" : "=r"(r) : "r"(a), "r"(b)); return r; }
__device__ __forceinline__ uint32_t bf2_fma(uint32_t a, uint32_t b, uint32_t c) { uint32_t r; asm("fma.rn.bf16x2 %0, %1, %2, %3;" : "=r"(r) : "r"(a), "r"(b), "r"(c)); return r; }
__device__ __forceinline__ float ex2(float v) { float r; asm("ex2.approx.ftz.f32 %0, %1;" : "=f"(r) : "f"(v)); return r; }
__device__ __forceinline__ float rcp(float v) { float r; asm("rcp.approx.ftz.f32 %0, %1;" : "=f"(r) : "f"(v)); return r; }
__device__ __forceinline__ float rsq(float v) { float r; asm("rsqrt.approx.ftz.f32 %0, %1;" : "=f"(r) : "f"(v)); return r; }
__device__ __forceinline__ void bar_sync(int id, int n) { asm volatile("bar.sync %0, %1;" :: "r"(id), "r"(n) : "memory"); }
__device__ __forceinline__ uint32_t clk() { uint32_t c; asm volatile("mov.u32 %0, %clock;" : "=r"(c)); return c; }
__device__ __forceinline__ uint32_t gtime() { uint32_t c; asm volatile("mov.u32 %0, %globaltimer_lo;" : "=r"(c)); return c; }
__device__ __forceinline__ void spin(uint32_t cycles) { const uint32_t c0 = clk(); while (clk() - c0 < cycles); }
__device__ __forceinline__ uint32_t pin(uint32_t v) { return __shfl_xor_sync(~0u, v, 0); }
__device__ __forceinline__ uint32_t pin(uint32_t v, uint32_t dep) {
    uint32_t r; asm volatile("{\n.reg .u32 b;\nshl.b32 b, %2, 5;\nshfl.sync.bfly.b32 %0, %1, b, 31, 0xffffffff;\n}" : "=r"(r) : "r"(v), "r"(dep)); return r;
}
__device__ __forceinline__ float uni(float v) { return __shfl_sync(~0u, v, 0); }
__device__ __forceinline__ float shx(float v, int o) { return __shfl_xor_sync(~0u, v, o); }

__device__ __forceinline__ u64 fx_pack(float v, float scale) { return ((u64)__float2ll_rn(v * scale) & ~255ull) | 1ull; }
__device__ __forceinline__ float fx_scale(float meansq) {
    const int e = max(((int)(__float_as_uint(meansq) >> 23) - 127) >> 1, -6);
    return __uint_as_float((uint32_t)(127 + 32 - e) << 23);
}
__device__ __forceinline__ float fx_inv(float scale) { return __uint_as_float((254u << 23) - __float_as_uint(scale)); }
__device__ __forceinline__ uint32_t lo32(u64 w) { uint32_t l; asm("mov.b64 {%0, _}, %1;" : "=r"(l) : "l"(w)); return l; }
__device__ __forceinline__ int hi32(u64 w) { int h; asm("mov.b64 {_, %0}, %1;" : "=r"(h) : "l"(w)); return h; }
__device__ __forceinline__ float fx_val(u64 w) { return (float)hi32(w) * 4294967296.f + (float)lo32(w); }
__device__ __forceinline__ void fx_poll(const unsigned char* ap, u64 (&w)[4]) {
    asm volatile("{\n.reg .pred p, q;\n.reg .u32 n, a, b, c, d;\nmov.u32 n, 0;\nLOOP:\n"
                 "ld.relaxed.gpu.global.u64 %0, [%4];\nld.relaxed.gpu.global.u64 %1, [%4+5120];\n"
                 "ld.relaxed.gpu.global.u64 %2, [%4+10240];\nld.relaxed.gpu.global.u64 %3, [%4+15360];\n"
                 "add.u32 n, n, 1;\nsetp.ge.u32 q, n, 0x100000;\n@q bra.uni DONE;\n"
                 "mov.b64 {a, _}, %0;\nmov.b64 {b, _}, %1;\nmov.b64 {c, _}, %2;\nmov.b64 {d, _}, %3;\n"
                 "lop3.b32 a, a, b, c, 0x80;\nlop3.b32 a, a, d, 32, 0x80;\nsetp.eq.u32 p, a, 0;\n"
                 "vote.sync.any.pred p, p, 0xffffffff;\n@p bra.uni LOOP;\nDONE:\n}"
                 : "=l"(w[0]), "=l"(w[1]), "=l"(w[2]), "=l"(w[3]) : "l"(ap) : "memory");
}
__device__ __forceinline__ void fx_poll(const unsigned char* ap, u64 (&w)[2]) {
    asm volatile("{\n.reg .pred p, q;\n.reg .u32 n, a, b;\nmov.u32 n, 0;\nLOOP:\n"
                 "ld.relaxed.gpu.global.u64 %0, [%2];\nld.relaxed.gpu.global.u64 %1, [%2+10240];\n"
                 "add.u32 n, n, 1;\nsetp.ge.u32 q, n, 0x100000;\n@q bra.uni DONE;\n"
                 "mov.b64 {a, _}, %0;\nmov.b64 {b, _}, %1;\n"
                 "lop3.b32 a, a, b, 128, 0x80;\nsetp.eq.u32 p, a, 0;\n"
                 "vote.sync.any.pred p, p, 0xffffffff;\n@p bra.uni LOOP;\nDONE:\n}"
                 : "=l"(w[0]), "=l"(w[1]) : "l"(ap) : "memory");
}
__device__ __forceinline__ u64 fx2_pack(float a, float b) {
    const int ia = __float_as_int(a + 12582912.f) - 0x4b400000, ib = __float_as_int(b + 12582912.f) - 0x4b400000;
    return (u64)(uint32_t)(ia * 512 + 1) | (u64)(uint32_t)(ib * 16 + (ia >> 23)) << 32;
}
__device__ __forceinline__ float fx2_lo(u64 w) { return (float)((int)(__funnelshift_r(lo32(w), hi32(w), 9) << 5) >> 5); }
__device__ __forceinline__ float fx2_hi(u64 w) { return (float)((hi32(w) + 8) >> 4); }

__device__ __forceinline__ void tma3(uint32_t dst, const CUtensorMap* tm, int c1, int c2, uint32_t bar, uint32_t pol) {
    asm volatile("cp.async.bulk.tensor.3d.shared::cluster.global.mbarrier::complete_tx::bytes.L2::cache_hint [%0], [%1, {%2, %3, %4}], [%5], %6;"
                 :: "r"(dst), "l"(tm), "r"(0), "r"(c1), "r"(c2), "r"(bar), "l"((u64)pol << 32) : "memory");
}
__device__ __forceinline__ void tma3_pf(const CUtensorMap* tm, int c1, int c2, uint32_t pol) {
    asm volatile("cp.async.bulk.prefetch.tensor.3d.L2.global.tile.L2::cache_hint [%0, {%1, %2, %3}], %4;"
                 :: "l"(tm), "r"(0), "r"(c1), "r"(c2), "l"((u64)pol << 32) : "memory");
}
__device__ __forceinline__ void bulk_pf(const void* p, uint32_t bytes, uint32_t pol) {
    asm volatile("cp.async.bulk.prefetch.L2.global.L2::cache_hint [%0], %1, %2;" :: "l"(p), "r"(bytes), "l"((u64)pol << 32) : "memory");
}
__device__ __forceinline__ float warp_max(float v) {
#pragma unroll
    for (int o = 16; o; o >>= 1) v = fmaxf(v, shx(v, o));
    return v;
}
__device__ __forceinline__ float warp_sum(float v) {
#pragma unroll
    for (int o = 16; o; o >>= 1) v += shx(v, o);
    return v;
}
__device__ __forceinline__ float ll_gather4(const u64* buf, uint32_t tag, u64 w0, u64 w1, u64 w2, u64 w3) {
#pragma unroll 1
    for (int it = 0; it < SPIN; it++) {
        if (__all_sync(~0u, ll_tag(w0) == tag && ll_tag(w1) == tag && ll_tag(w2) == tag && ll_tag(w3) == tag)) break;
        w0 = ld_rlx(buf); w1 = ld_rlx(buf + 256); w2 = ld_rlx(buf + 512); w3 = ld_rlx(buf + 768);
    }
    return (ll_val(w0) + ll_val(w1)) + (ll_val(w2) + ll_val(w3));
}
__device__ __forceinline__ u64 lds_u64(uint32_t a, int o) { const uint2 v = lds64(a, o); return v.x | (u64)v.y << 32; }
__device__ __forceinline__ float sum8(uint32_t a, int o, int pitch) {
    float s[8];
#pragma unroll
    for (int w = 0; w < 8; w++) s[w] = ldsf(a, o + w * pitch);
    return ((s[0] + s[1]) + (s[2] + s[3])) + ((s[4] + s[5]) + (s[6] + s[7]));
}
__device__ __forceinline__ void ln_final(float& mean, float& rstd, float& msq) {
    float2 v[5];
#pragma unroll
    for (int w = 0; w < 5; w++) v[w] = lds64f(0, SM_STAT + w * 8);
    mean = (((v[0].x + v[1].x) + (v[2].x + v[3].x)) + v[4].x) * (1.f / D_MODEL);
    msq = (((v[0].y + v[1].y) + (v[2].y + v[3].y)) + v[4].y) * (1.f / D_MODEL);
    rstd = rsq(fmaxf(msq - mean * mean, 0.f) + 1e-5f);
}
constexpr float CS = 0.07216878364870322f * 1.4426950408889634f;
constexpr uint32_t ONES = 0x3f803f80u;

__global__ void __launch_bounds__(NTHR, 1) fused_kernel(const __grid_constant__ Params P) {
    extern __shared__ __align__(1024) unsigned char smem[];
    const int warp = __shfl_sync(~0u, threadIdx.x >> 5, 0), bx = blockIdx.x;
    const int cta = (((bx >> 1) & 15) + (bx >> 6) * 16) * 4 + ((bx >> 5) & 1) * 2 + (bx & 1);

    if (bx == NCTA) {
        if ((uint32_t)__cvta_generic_to_shared(smem) != SM_RING) __trap();
        const uint32_t ep = *(volatile unsigned*)&g_epoch;
        if (threadIdx.x == 0) {
#pragma unroll 1
            for (int it = 0; it < SPIN; it++) { if (ll_tag(ld_rlx(&g_ll[1][0][192])) == ep * 4 + 2) break; __nanosleep(200); }
        }
        __syncthreads();
#pragma unroll 1
        for (int i = threadIdx.x; i < 4 * 80 * 8; i += NTHR)
            *reinterpret_cast<uint4*>(g_acc + (i >> 3) * ACC_PITCH + (i & 7) * 16) = make_uint4(0, 0, 0, 0);
        __threadfence();
        __syncthreads();
        if (threadIdx.x == 0) asm volatile("st.relaxed.gpu.global.u32 [%0], %1;" :: "l"(&g_zflag), "r"(ep + 1) : "memory");
        return;
    }
    const uint32_t barw = SM_BAR + warp * 64;
    if (elect()) {
        if (warp < NI0) sts32(0, SM_T0, gtime());
        if (warp >= 3) {
            mbar_init(barw + 56, 1);
            asm volatile("fence.mbarrier_init.release.cluster;" ::: "memory");
            mbar_expect(barw + 56, HT);
            tma3(SM_WQ - 3 * HT + warp * HT, &P.tm[TM_WQ], (cta >> 2) * 3, (cta & 3) * 160 - 96 + warp * 32, barw + 56, POL_FIRST);
        }
        TS(31);
    }
    int tid = threadIdx.x, lane, g, t, c4;
    uint32_t maskA, maskB, offV0, offV2;
    auto derive = [&]() {
        lane = tid & 31; g = lane >> 2; t = lane & 3;
        c4 = (tid & 0xe1) + 16 * (t >> 1) + 2 * g;
        maskA = (g & 2) ? 0u : (g & 1) ? 0xffff0000u : 0x0000ffffu;
        maskB = (g & 2) ? ((g & 1) ? 0xffff0000u : 0x0000ffffu) : 0u;
        offV0 = (6 * t) * 128 + ((g ^ ((6 * t) & 7)) << 4);
        offV2 = (6 * t) * 128 + ((g ^ ((6 * t + 2) & 7)) << 4);
    };
    auto refresh = [&]() { tid = pin(tid); derive(); };
    auto refresh_after = [&](uint32_t dep) { tid = pin(tid, dep); derive(); };
    derive();
    const int j40 = (cta & 3) * 40;
    uint2 xp = make_uint2(0, 0);
    if (tid < 160) xp = *reinterpret_cast<const uint2*>(P.x + 4 * c4);
    else if (tid == 192) xp.x = *(volatile unsigned*)&g_epoch;
    else if (tid >= 224 && tid < 236) xp.x = reinterpret_cast<const unsigned short*>(P.b1)[cta * 12 + lane];
    __syncwarp();
    if (elect()) {
#pragma unroll
        for (int i = 0; i < 7; i++) mbar_init(barw + i * 8, 1);
        mbar_init(SM_CBAR + warp * 8, 1); mbar_init(SM_CBAR + 64 + warp * 8, 1);
        if (warp == 0) mbar_init(SM_QBAR, 6);
        asm volatile("fence.mbarrier_init.release.cluster;" ::: "memory");
        sts64(warp * 8, SM_CNT, 0, 0);
        sts64(warp * 8, SM_ZQ, 0, 0);
    }
    uint32_t kc[192];
#pragma unroll
    for (int i = 0; i < 192; i++) asm volatile("mov.b32 %0, 0;" : "=r"(kc[i]));
    const int rowc = (cta >> 2) * SK + (SK - WIN) + (cta & 3) * 64;
    const int roww = __shfl_sync(~0u, rowc + warp * 8, 0);
    const CUtensorMap* tmk = reinterpret_cast<const CUtensorMap*>(__shfl_sync(~0u, (u64)&P.tm[0] + (lane >> 5), 0));

    auto wait_due = [&](int i, int extra) {
        const uint32_t due = lds32(0, SM_T0) + PACE0 + extra + i * PACE;
#pragma unroll 1
        for (int it = 0; it < 4096; it++) if ((int)(gtime() - due) >= 0) break;
    };
    auto issue_wo = [&](int k) {
        wait_due(64, k * WOPACE + WOD);
        mbar_expect(SM_CBAR + 32 + k * 8, 4 * WOU);
        asm volatile("cp.async.bulk.tensor.4d.shared::cluster.global.mbarrier::complete_tx::bytes.L2::cache_hint [%0], [%1, {%2, %3, %4, %5}], [%6], %7;"
                     :: "r"(SM_RING + k * 4 * WOU), "l"(tmk + TM_WO4), "r"(0), "r"(5 * (cta & 3)), "r"((k >> 1) * 8), "r"((cta >> 2) * 8 + (k & 1) * 4),
                        "r"(SM_CBAR + 32 + k * 8), "l"((u64)(WOKEEP == 1 && k < 4 ? POL_NORMAL : POL_FIRST) << 32) : "memory");
        if (WOKEEP == 2 && k < 4)
            asm volatile("cp.async.bulk.prefetch.tensor.4d.L2.global.tile.L2::cache_hint [%0, {%1, %2, %3, %4}], %5;"
                         :: "l"(tmk + TM_WOP), "r"(0), "r"(5 * (cta & 3)), "r"((k >> 1) * 8), "r"((cta >> 2) * 8 + (k & 1) * 4), "l"((u64)POL_NORMAL << 32) : "memory");
    };
    auto issue_kv = [&](int i, int slot, int bar) {
        const int row = rowc + (i & 30) * 128 + (i & 1) * 32;
        mbar_expect(SM_CBAR + bar * 8, HT);
        tma3(SM_RING + slot * HT, tmk + TM_K + (i >> 5), 0, row, SM_CBAR + bar * 8, POL_FIRST);
        if (i >= KEEP0) tma3_pf(tmk + TM_VP, 0, row, POL_NORMAL);
    };
    auto issue_w1 = [&]() {
#pragma unroll 1
        for (int i = 0; i < 5; i++) {
            mbar_expect(SM_CBAR + 80 + i * 8, 4096);
            asm volatile("cp.async.bulk.tensor.2d.shared::cluster.global.mbarrier::complete_tx::bytes.L2::cache_hint [%0], [%1, {%2, %3}], [%4], %5;"
                         :: "r"(SM_RING + i * 4096), "l"(tmk + TM_W1), "r"(cta * 12 - (cta & 1) * 4), "r"(i * 128), "r"(SM_CBAR + 80 + i * 8), "l"((u64)POL_FIRST << 32) : "memory");
        }
    };
    __syncwarp();
    if (warp < NI0) { wait_due(warp, 0); if (elect()) issue_kv(warp, warp == 4 ? 0 : warp + 1, warp); }
    if (warp >= 3) mbar_wait(barw + 56, 0);
    if (tid == 192) sts32(0, SM_EPOCH, xp.x);
    if (tid >= 224 && tid < 236) sts32((lane + (cta & 1) * 4) * 8, SM_B1, xp.x << 16);
    __syncthreads();
    TSB(10);
    if (warp >= NI0 && elect()) {
        if (warp < 5) issue_kv(warp, warp == 4 ? 0 : warp + 1, warp);
        else if (warp < 5 + NPF0) tma3_pf(tmk + TM_K, 0, rowc + (warp & 30) * 128 + (warp & 1) * 32, POL_FIRST);
    }
    const uint32_t ep4 = __shfl_sync(~0u, lds32(0, SM_EPOCH) * 4, 0);

    auto load_v3 = [&](uint4* v, uint32_t u, int o, bool odd) {
        if (!odd) { v[0] = lds128(ad(offV0, u), o); v[1] = lds128(ad(offV0 ^ 16, u), o + 128); v[2] = lds128(ad(offV2, u), o + 256); }
        else { v[0] = lds128(ad(offV2 ^ 16, u), o + 384); v[1] = lds128(ad(offV0 ^ 64, u), o + 512); v[2] = lds128(ad(offV0 ^ 80, u), o + 640); }
    };
    auto load_v = [&](uint4 (&v)[6], uint32_t u, int o) { load_v3(v, u, o, false); load_v3(v + 3, u, o, true); };
    const uint32_t wqw = warp * SUB, ksw = warp * HT;
    auto slot_o = [&](int s) { return s < 2 ? SM_WQ + s * 8 * SUB : s == 2 ? 0 : SM_KS + (s - 3) * SUB; };
    const uint32_t w2w = warp < 4 ? SM_WQ + 16 * SUB + wqw : slot_o(IC<PL.slot[16]>::value) + (IC<PL.slot[16]>::value < 2 ? wqw : ksw);
    auto slot_u = [&](int s) { return s < 2 ? wqw : s == 2 ? w2w : ksw; };
    auto issue2 = [&](auto I) {
        constexpr int p = I.value == 16 ? 2 : I.value, s = PL.slot[p];
        __syncwarp();
        TR(5, 2 + I.value);
        if ((p != 2 || (warp < 4) == (I.value == 2)) && elect()) {
            mbar_expect(barw + s * 8, p < 16 ? SUB : 2 * WOU);
            if constexpr (p < 16) tma3(slot_u(s) + slot_o(s), tmk + TM_V8, 0, roww + vunit(p) * 256, barw + s * 8, POL_FIRST);
            else tma3(slot_u(s) + slot_o(s), tmk + TM_WO, 5 * (cta & 3), (cta >> 2) * DH + warp * 24, barw + s * 8, POL_FIRST);
        }
    };
    uint4 wq0[6], wqh[3];
    uint32_t xna;
    auto load_wq = [&]() {
        load_v(wq0, wqw, SM_WQ);
        const int r = c4 - j40;
        xna = pin((tid < 160 && r >= 0 && r < 40) ? SM_VEC + r * 8 : 0u);
    };
    auto load_wqh = [&]() {
        const int r0 = 6 * t + 3 * (warp & 1);
#pragma unroll
        for (int j = 0; j < 3; j++) wqh[j] = lds128(ad(r0 * 128 + ((g ^ ((r0 + j) & 7)) << 4), (warp >> 1) * SUB), SM_WQ + 16 * SUB + j * 128);
    };
    const uint32_t prow = warp * 768;
    float acc[3][4], rstd_q;

    auto q_stage = [&](auto L) {
        constexpr int layer = L.value;
        if (xna) sts64(xna, 0, xp.x, xp.y);
        __syncthreads();
        if (layer) TSB(20);
        uint32_t p0 = lds32(ad(t * 4, warp * 16), SM_VEC), p1 = lds32(ad(t * 4, warp * 16), SM_VEC + 128), ph = lds32(ad(t * 4, (warp >> 1) * 16), SM_VEC + 256);
        const float x0 = bf_lo(xp.x), x1 = bf_hi(xp.x), x2 = bf_lo(xp.y), x3 = bf_hi(xp.y);
        float s1 = (x0 + x1) + (x2 + x3), s2 = (x0 * x0 + x1 * x1) + (x2 * x2 + x3 * x3);
        float ss = ((lane & 16) ? s2 : s1) + shx((lane & 16) ? s1 : s2, 16);
        if (layer == 0 && g >= 4) p0 = p1 = ph = ONES;
        const uint32_t dH = __byte_perm(ph, 0, (warp & 1) ? 0x3232 : 0x1010);
#pragma unroll
        for (int j = 0; j < 3; j++) { zero4(acc[j]); mma(acc[j], wqh[j], dH & maskA, dH & maskB); }
        load_v3(wqh, wqw, SM_WQ + 8 * SUB, false);
        ss += shx(ss, 8);
        const uint32_t dA = __byte_perm(p0, 0, 0x1010), dB = __byte_perm(p0, 0, 0x3232);
#pragma unroll
        for (int j = 0; j < 3; j++) mma(acc[j], wq0[j], dA & maskA, dA & maskB);
        load_v3(wq0, wqw, SM_WQ + 8 * SUB, true);
        ss += shx(ss, 4);
#pragma unroll
        for (int j = 0; j < 3; j++) mma(acc[j], wq0[j + 3], dB & maskA, dB & maskB);
        if constexpr (layer == 1 && !QLATE) {
            issue2(IC<2>{});
            issue2(IC<1>{});
        }
        ss += shx(ss, 2);
        const uint32_t dC = __byte_perm(p1, 0, 0x1010), dD = __byte_perm(p1, 0, 0x3232);
#pragma unroll
        for (int j = 0; j < 3; j++) mma(acc[j], wqh[j], dC & maskA, dC & maskB);
        ss += shx(ss, 1);
#pragma unroll
        for (int j = 0; j < 3; j++) mma(acc[j], wq0[j], dD & maskA, dD & maskB);
        if ((lane & 15) == 0 && warp < 5) stsf(tid >> 2, SM_STAT, ss);
        if (t < 2 || layer == 0) {
            const uint32_t a = (t < 2 ? prow : ksw + (SM_KS + 11264 - SM_PART)) + (8 * g + 4 * (t & 1)) * 4;
#pragma unroll
            for (int j = 0; j < 3; j++) sts128f(a, SM_PART + j * 256, acc[j]);
        }
        u64* dst = &g_ll[layer][cta][tid];
        float cs = 0.f;
        if (layer) cs = ldsf(tid * 4, SM_CS);
        if (layer) TS(21);
        __syncthreads();
        if (layer) TSB(22);
        uint32_t dep = 0;
        rstd_q = 0.f;
        if (warp < 6) {
            if (layer == 0) { cs = sum8(tid * 4, SM_KS + 11264, HT); stsf(tid * 4, SM_CS, cs); }
            const float s = sum8(tid * 4, SM_PART, 768);
            float mean, msq;
            ln_final(mean, rstd_q, msq);
            const float r = layer ? s - mean * cs : (s - mean * cs) * rstd_q;
            st_rlx(dst, ll_pack(r, ep4 + 1 + 2 * layer));
            dep = __float_as_uint(r);
            if (tid == 0) stsf(0, SM_FXS, fx_scale(msq));
        }
        if (layer) TS(23);
        refresh_after(dep);
    };
    auto q_addr = [&]() { return (((tid >> 1) & 1) * 4 + ((tid >> 4) & 3)) * 48 + ((tid >> 6) * 2 + ((tid >> 3) & 1)) * 8 + ((tid >> 2) & 1) * 4 + (tid & 1) * 2; };
    auto score6 = [&](const uint4 (&v)[6], const uint32_t (&qf)[12]) {
        float d[2][4];
#pragma unroll
        for (int i = 0; i < 6; i++) { if (i < 2) zero4(d[i]); mma(d[i & 1], v[i], qf[2 * i], qf[2 * i + 1]); }
        return (d[0][0] + d[0][3]) + (d[1][0] + d[1][3]);
    };
    auto softmax = [&](auto L, const float (&S)[4]) {
        constexpr int layer = L.value;
        DBG(0 + 8 * layer, S[0] + S[1] + S[2] + S[3]);
        const float mrun = warp_max(fmaxf(fmaxf(S[0], S[1]), fmaxf(S[2], S[3])));
        const float p0 = ex2((S[0] - mrun) * CS), p1 = ex2((S[1] - mrun) * CS), p2 = ex2((S[2] - mrun) * CS), p3 = ex2((S[3] - mrun) * CS);
        const uint32_t pa = pack_bf(p0, p1), pb = pack_bf(p2, p3), pw = prow + t * 64 + g * 2;
        sts16(pw, SM_PART + 256, pa); sts16(pw, SM_PART + 272, pa >> 16); sts16(pw, SM_PART + 288, pb); sts16(pw, SM_PART + 304, pb >> 16);
        const float l = warp_sum((p0 + p1) + (p2 + p3));
        if (layer == 1 && warp < 6) st_rlx(&g_ll[2][cta][tid], 0ull);
        uint32_t old = 0;
        if (lane == 0) {
            sts64f(warp * 8, SM_ML, mrun, l);
            asm volatile("atom.acq_rel.cta.shared.inc.u32 %0, [%1], 7;" : "=r"(old) : "r"(SM_CNT + 48) : "memory");
        }
        if (__any_sync(~0u, old == 7)) {
            __syncwarp();
            const float2 ml = lds64f((lane & 7) * 8, SM_ML);
            float M = fmaxf(ml.x, shx(ml.x, 1)); M = fmaxf(M, shx(M, 2)); M = fmaxf(M, shx(M, 4));
            const float f = ex2((ml.x - M) * CS);
            float Lc = f * ml.y; Lc += shx(Lc, 1); Lc += shx(Lc, 2); Lc += shx(Lc, 4);
            if (layer == 0) { if (lane == 0) sts64f(0, SM_STAT, M, Lc); }
            else if (lane < 4) st_rlx(&g_ll[2][cta][192 + lane], ll_pack(lane == 0 ? M : Lc, ep4 + 4));
        }
        __syncwarp();
#pragma unroll
        for (int j = 0; j < 3; j++) zero4(acc[j]);
    };
    auto pv = [&](const uint4 (&v)[6], uint32_t pp) {
        const uint32_t dA = __byte_perm(pp, 0, 0x1010), dB = __byte_perm(pp, 0, 0x3232);
        mma(acc[0], v[0], dA & maskA, dA & maskB); mma(acc[1], v[1], dA & maskA, dA & maskB); mma(acc[2], v[2], dA & maskA, dA & maskB);
        mma(acc[0], v[3], dB & maskA, dB & maskB); mma(acc[1], v[4], dB & maskA, dB & maskB); mma(acc[2], v[5], dB & maskA, dB & maskB);
    };

    float fw;
    auto head_weight = [&](auto L, u64 pm, u64 pl) {
        const uint32_t tag = ep4 + 2 + 2 * L.value;
#pragma unroll 1
        for (int it = 0; it < SPIN; it++) {
            if (__all_sync(~0u, ll_tag(pm) == tag && ll_tag(pl) == tag)) break;
            ld_rlx2(&g_ll[1 + L.value][cta ^ t][192], pm, pl);
        }
        float M = fmaxf(ll_val(pm), shx(ll_val(pm), 1)); M = fmaxf(M, shx(M, 2));
        float Lh = ex2((ll_val(pm) - M) * CS) * ll_val(pl); Lh += shx(Lh, 1); Lh += shx(Lh, 2);
        fw = ex2((ldsf(warp * 8, SM_ML) - M) * CS) * rcp(Lh);
        xp = lds64(prow + lane * 8, SM_PART);
    };

    auto tail = [&](auto L) {
        constexpr int layer = L.value;
        unsigned char* const accb = g_acc + 2 * layer * ACC_BYTES;
        unsigned char* ra;
        auto park = [&]() { sts128(tid * 16, SM_PK, kc[8], kc[9], kc[10], kc[11]); };
        {
            if (t < 2) {
#pragma unroll
                for (int j = 0; j < 3; j++) {
                    const float a[4] = {acc[j][0] * fw, acc[j][1] * fw, acc[j][2] * fw, acc[j][3] * fw};
                    sts128f(prow + (8 * g + 4 * t) * 4, SM_PART + 256 * j, a);
                }
            }
            const uint32_t tag = ep4 + 2 + 2 * layer;
            const int d = warp * 24 + min(lane, 23);
            const u64* const lp = &g_ll[1 + layer][cta & ~3][d];
            __syncthreads();
            TSB(4 + 10 * layer);
            const float own = sum8(d * 4, SM_PART, 768);
            DBG(1 + 8 * layer, own);
            if (lane < 24) st_rlx(const_cast<u64*>(lp) + (cta & 3) * 256, ll_pack(own, tag));
            const uint32_t c0 = clk();
            __syncthreads();
            refresh_after(__float_as_uint(own));
            if (layer == 0 && warp < 3) { if (elect()) issue_wo(3 + warp); __syncwarp(); }
            const int rowA = (lane & 1) + 2 * (lane & 2);
            uint32_t wa[5];
#pragma unroll
            for (int k = 0; k < 5; k++) {
                const int row = rowA + 2 * (k < 4 ? k >> 1 : g >> 2), j = k < 4 ? 2 * (k & 1) + (g >> 2) : 4;
                wa[k] = row * 320 + j * 64 + (((g & 3) ^ (((5 * row + j) >> 1) & 3)) << 4);
            }
            auto load_u = [&](uint4 (&a)[5], uint32_t u, int o) {
#pragma unroll
                for (int k = 0; k < 5; k++) a[k] = lds128(ad(wa[k], u), o);
            };
            auto red_addr = [&]() {
                const int word = t * 160 + j40 + (tid >> 2);
                ra = accb + pin((word >> 3) * ACC_PITCH + (word & 7) * 8);
            };
            uint4 v[5], u[5], z[5];
            if constexpr (layer == 1) { load_u(z, warp * WOU, SM_RING + 16 * WOU); red_addr(); }
            while (clk() - c0 < (layer ? ODELAY2 : ODELAY1));
            u64 w1 = ld_rlx(lp + ((cta ^ 1) & 3) * 256), w2 = ld_rlx(lp + ((cta ^ 2) & 3) * 256), w3 = ld_rlx(lp + ((cta ^ 3) & 3) * 256);
            if constexpr (layer == 1) {
                mbar_wait(barw + 40, IC<PL.par[17]>::value);
                TS(30);
                load_u(v, ksw, slot_o(5)); load_u(u, ksw, slot_o(5) + WOU);
            }
#pragma unroll 1
            for (int it = 0; it < SPIN; it++) {
                if (__all_sync(~0u, ll_tag(w1) == tag && ll_tag(w2) == tag && ll_tag(w3) == tag)) break;
                w1 = ld_rlx(lp + ((cta ^ 1) & 3) * 256); w2 = ld_rlx(lp + ((cta ^ 2) & 3) * 256); w3 = ld_rlx(lp + ((cta ^ 3) & 3) * 256);
            }
            TS(5 + 10 * layer);
            if constexpr (layer == 0) {
                mbar_wait(SM_CBAR + 32 + (warp >> 2) * 8, 0);
                load_u(v, warp * WOU, SM_RING);
                __syncwarp();
                if (elect() && atoms_inc(SM_CNT + 40, 7) == 7) { wait_due(69, W1D); TSA(32); issue_w1(); }
                __syncwarp();
            }
            const float o = (own + ll_val(w1)) + (ll_val(w2) + ll_val(w3));
            const uint32_t od = pack_bf(o, o);
            DBG(2 + 8 * layer, o);
            float y[3][4];
            uint32_t oA, oB;
            auto unit_b = [&](int p) { oA = __shfl_sync(~0u, od, 8 * p + rowA); oB = __shfl_sync(~0u, od, 8 * p + 2 + rowA); };
            auto unit = [&](const uint4 (&a)[5]) {
                const uint32_t oC = g < 4 ? oA : oB;
                mma(y[0], a[0], oA & maskA, oA & maskB); mma(y[1], a[1], oA & maskA, oA & maskB); mma(y[2], a[4], oC & maskA, oC & maskB);
                mma(y[0], a[2], oB & maskA, oB & maskB); mma(y[1], a[3], oB & maskA, oB & maskB);
            };
#pragma unroll
            for (int j = 0; j < 3; j++) zero4(y[j]);
            unit_b(0); unit(v);
            if constexpr (layer == 0) {
                mbar_wait(SM_CBAR + 48 + (warp >> 2) * 8, 0);
                load_u(u, warp * WOU, SM_RING + 8 * WOU);
                __syncwarp();
                if (elect() && atoms_inc(SM_CNT + 44, 7) == 7) { mbar_expect(SM_CBAR + 120, 15360); tma3(SM_W2, tmk + TM_W2, 0, cta * 12, SM_CBAR + 120, POL_FIRST); }
                __syncwarp();
            }
            unit_b(1); unit(u);
            unit_b(2);
            if constexpr (layer == 0) {
                red_addr();
                mbar_wait(SM_CBAR + 64 + (warp >> 2) * 8, 0);
                TS(28);
                load_u(z, warp * WOU, SM_RING + 16 * WOU);
            }
            unit(z);
            const uint32_t ya = prow + (8 * g + 4 * (t & 1)) * 4;
            if ((t >> 1) == (g >> 2)) sts128f(ya, SM_PART + 512, y[2]);
            if (t < 2) { sts128f(ya, SM_PART, y[0]); sts128f(ya, SM_PART + 256, y[1]); }
        }
        float fxs = ldsf(0, SM_FXS);
        __syncthreads();
        if (warp < 5) {
            {
                float s = sum8(tid * 4, SM_PART, 768);
                if (warp == 4) s += sum8(tid * 4, SM_PART + 128, 768);
                DBG(3 + 8 * layer, s);
                const u64 w = fx_pack(s, fxs);
                asm volatile("red.relaxed.gpu.global.add.u64 [%0], %1;" :: "l"(ra), "l"(w) : "memory");
                TS(6 + 10 * layer);
                refresh_after(lo32(w));
            }
            uint4 wf[8], w2r[6];
            const uint32_t la = pin((tid >> 5) * 4096 + (64 * ((lane >> 2) & 1) + 4 * ((lane >> 1) & 1) + (lane & 1) + 2 * (lane >> 4)) * 32 + ((((lane >> 3) ^ (lane >> 1)) & 1) << 4));
            const uint32_t w2a = pin((10 * t + 2 * (tid >> 5)) * 128 + ((g ^ ((2 * t + 2 * (tid >> 5)) & 7)) << 4));
            const uint32_t hpa = pin((tid >> 5) * 64 + (t * 8 + g) * 4);
            auto load_w1 = [&]() {
                if (layer == 0) mbar_wait(SM_CBAR + 80 + warp * 8, 0);
                if (layer == 0) TS(29);
#pragma unroll
                for (int j = 0; j < 8; j++) wf[j] = ldsm_t(la, SM_RING + j * 256);
            };
            auto load_w2 = [&]() {
#pragma unroll
                for (int i = 0; i < 6; i++) w2r[i] = lds128(w2a ^ ((i & 1) * 16), SM_W2 + (i >> 1) * 5120 + (i & 1) * 128);
            };
            if (layer == 1 || W1FIRST == 1) load_w1();
            if (layer == 1) load_w2();
            unsigned char* ap = accb + (uint32_t)((c4 >> 3) * ACC_PITCH + (c4 & 7) * 8);
            {
                u64 w[4];
                const float inv = fx_inv(fxs);
                fx_poll(ap, w);
                TS(7 + 10 * layer);
                if (layer == 0 && W1FIRST == 0) load_w1();
                xp = make_uint2(pack_bf(bf_lo(xp.x) + fx_val(w[0]) * inv, bf_hi(xp.x) + fx_val(w[1]) * inv),
                                pack_bf(bf_lo(xp.y) + fx_val(w[2]) * inv, bf_hi(xp.y) + fx_val(w[3]) * inv));
            }
            DBG(4 + 8 * layer, bf_lo(xp.x) + bf_hi(xp.y));
            {
                const float x0 = bf_lo(xp.x), x1 = bf_hi(xp.x), x2 = bf_lo(xp.y), x3 = bf_hi(xp.y);
                const float s1 = (x0 + x1) + (x2 + x3), s2 = (x0 * x0 + x1 * x1) + (x2 * x2 + x3 * x3);
                float ss = ((lane & 16) ? s2 : s1) + shx((lane & 16) ? s1 : s2, 16);
                ss += shx(ss, 8);
                if (layer == 0 && W1FIRST == 2) {
                    ss += shx(ss, 4); ss += shx(ss, 2); ss += shx(ss, 1);
                    if ((lane & 15) == 0) stsf(tid >> 2, SM_STAT, ss);
                    load_w1();
                }
                const bool ev = layer || !(g & 1), od = layer || (g & 1);
                const uint32_t e0 = ev ? xp.x : ONES, e1 = ev ? xp.y : ONES, o0 = od ? xp.x : ONES, o1 = od ? xp.y : ONES;
                float d[8][4];
#pragma unroll
                for (int j = 0; j < 8; j++) { zero4(d[j]); mma(d[j], wf[j], (j & 1) ? o0 : e0, (j & 1) ? o1 : e1); }
                float lo = d[0][0] + d[1][1], hi = d[0][2] + d[1][3];
#pragma unroll
                for (int m = 1; m < 4; m++) if (t == m) { lo = d[2 * m][0] + d[2 * m + 1][1]; hi = d[2 * m][2] + d[2 * m + 1][3]; }
                float dd = ((t & 1) ? hi : lo) + shx((t & 1) ? lo : hi, 1);
                dd += shx(dd, 2);
                if (layer == 1 || W1FIRST != 2) {
                    ss += shx(ss, 4); ss += shx(ss, 2); ss += shx(ss, 1);
                    if ((lane & 15) == 0) stsf(tid >> 2, SM_STAT, ss);
                }
                if (t < 2) {
                    if (layer == 0) {
                        const float cl = ((d[0][1] + d[1][0]) + (d[2][1] + d[3][0])) + ((d[4][1] + d[5][0]) + (d[6][1] + d[7][0]));
                        const float ch = ((d[0][3] + d[1][2]) + (d[2][3] + d[3][2])) + ((d[4][3] + d[5][2]) + (d[6][3] + d[7][2]));
                        stsf(hpa, SM_C1, t ? ch : cl);
                    }
                    stsf(hpa, SM_QU, dd);
                }
            }
            float2 bc = lds64f((lane & 15) * 8, SM_B1);
            ap = accb + ACC_BYTES + (uint32_t)((c4 >> 2) * ACC_PITCH + (c4 & 3) * 8);
            if (layer == 0) mbar_wait(SM_CBAR + 120, 0);
            bar_sync(1, 160);
            TSB(26 + layer);
            float mean, rstd, msq;
            ln_final(mean, rstd, msq);
            float hp[5];
#pragma unroll
            for (int w = 0; w < 5; w++) hp[w] = ldsf((lane & 15) * 4, SM_QU + w * 64);
            if constexpr (layer == 0) {
                float c[5];
#pragma unroll
                for (int w = 0; w < 5; w++) c[w] = ldsf((lane & 15) * 4, SM_C1 + w * 64);
                bc.y = ((c[0] + c[1]) + (c[2] + c[3])) + c[4];
                load_w2();
            }
            float hv = ((((hp[0] + hp[1]) + (hp[2] + hp[3])) + hp[4]) - mean * bc.y) * rstd + bc.x;
            hv = hv * rcp(1.f + ex2(hv * (-2.302208198f - 0.1029432397f * hv * hv)));
            const uint32_t hd = pack_bf(hv, hv);
            DBG(5 + 8 * layer, ((lane - (cta & 1) * 4) & 15) < 12 ? hv : 0.f);
            fxs = fx_scale(msq);
            float yA[4] = {0.f, 0.f, 0.f, 0.f}, yB[4] = {0.f, 0.f, 0.f, 0.f};
#pragma unroll
            for (int i = 0; i < 3; i++) {
                const uint32_t hh = __shfl_sync(~0u, hd, 4 * i + t + (cta & 1) * 4);
                mma(yA, w2r[2 * i], hh & maskA, hh & maskB);
                mma(yB, w2r[2 * i + 1], hh & maskA, hh & maskB);
            }
            const float sc2 = __uint_as_float((uint32_t)(127 + 16 - max(((int)(__float_as_uint(msq) >> 23) - 127) >> 1, -100)) << 23);
            float y[4];
#pragma unroll
            for (int k = 0; k < 4; k++) y[k] = ((t & 2) ? yB[k] : yA[k]) * sc2;
            u64 w[2] = {fx2_pack(y[0], y[1]), fx2_pack(y[2], y[3])};
            DBG(6 + 8 * layer, y[0] + y[1] + y[2] + y[3]);
            const float inv = fx_inv(sc2);
            if (!(fmaxf(fmaxf(fabsf(y[0]), fabsf(y[1])), fmaxf(fabsf(y[2]), fabsf(y[3]))) < FX2LIM)) {
#pragma unroll
                for (int k = 0; k < 4; k++)
                    asm volatile("red.relaxed.gpu.global.add.u64 [%0], %1;" :: "l"(ap + (k >> 1) * 40 * ACC_PITCH + 64 + (k & 1) * 32), "l"(fx_pack(y[k] * inv, fxs)) : "memory");
                __threadfence();
#pragma unroll
                for (int k = 0; k < 2; k++) { asm volatile("red.relaxed.gpu.global.or.b64 [%0], 256;" :: "l"(ap + k * 40 * ACC_PITCH) : "memory"); w[k] = 1; }
            }
            float xb[4], invu;
            auto add_b2 = [&]() {
                uint2 b2v;
                asm volatile("ld.global.nc.v2.u32 {%0,%1}, [%2];" : "=r"(b2v.x), "=r"(b2v.y) : "l"(P.b2 + 4 * c4));
                stsf(0, SM_FXS, fxs);
                invu = uni(inv);
                xb[0] = bf_lo(xp.x) + bf_lo(b2v.x); xb[1] = bf_hi(xp.x) + bf_hi(b2v.x); xb[2] = bf_lo(xp.y) + bf_lo(b2v.y); xb[3] = bf_hi(xp.y) + bf_hi(b2v.y);
            };
            auto add_mlp = [&]() {
                if ((lo32(w[0]) | lo32(w[1])) & 256) {
                    __threadfence();
#pragma unroll
                    for (int k = 0; k < 4; k++) xb[k] += fx_val(ld_rlx(ap + (k >> 1) * 40 * ACC_PITCH + 64 + (k & 1) * 32)) * fx_inv(ldsf(0, SM_FXS));
                }
                xp = make_uint2(pack_bf(xb[0] + fx2_lo(w[0]) * invu, xb[1] + fx2_hi(w[0]) * invu), pack_bf(xb[2] + fx2_lo(w[1]) * invu, xb[3] + fx2_hi(w[1]) * invu));
            };
            if constexpr (layer == 1) {
                u64 old[2];
#pragma unroll
                for (int k = 0; k < 2; k++) asm volatile("atom.relaxed.gpu.global.add.u64 %0, [%1], %2;" : "=l"(old[k]) : "l"(ap + k * 40 * ACC_PITCH), "l"(w[k]) : "memory");
                TS(18);
                refresh_after(lo32(w[1]));
                add_b2();
#pragma unroll
                for (int k = 0; k < 2; k++) w[k] += old[k];
                add_mlp();
                uint32_t* op = reinterpret_cast<uint32_t*>(P.out) + 2 * c4;
                if (w[0] & 128) { op[0] = xp.x; if (tid == 0) g_epoch = (ep4 >> 2) + 1; }
                if (w[1] & 128) op[1] = xp.y;
                TS(19);
            } else {
#pragma unroll
                for (int k = 0; k < 2; k++) asm volatile("red.relaxed.gpu.global.add.u64 [%0], %1;" :: "l"(ap + k * 40 * ACC_PITCH), "l"(w[k]) : "memory");
                TS(8);
                const uint32_t c0 = clk();
                refresh_after(lo32(w[1]));
                add_b2();
                stsf((lane & 15) * 8, SM_B1 + 4, bc.y);
                park();
                load_wq();
                load_wqh();
                while (clk() - c0 < ARDELAY);
                if (warp < TB) issue2(IC<0>{});
                fx_poll(ap, w);
                if (warp >= TB) issue2(IC<0>{});
                add_mlp();
                TS(9);
                DBG(7, bf_lo(xp.x) + bf_hi(xp.y));
            }
        } else if constexpr (layer == 0) {
            const uint32_t c0 = clk();
            refresh();
            park();
            load_wq();
            load_wqh();
            while (clk() - c0 < S6D + (warp - 5) * S6G);
            issue2(IC<0>{});
            if (NPFC && warp == 5) {
#pragma unroll 1
                for (int k = 0; k < NPFC; k++) {
                    while (clk() - c0 < PFD + k * PFG);
                    if (elect()) tma3_pf(tmk + TM_V8, 0, rowc + (k >> 3) * 256 + (k & 7) * 8, PFPOL);
                }
            }
        }
    };

    load_wq();
    load_wqh();
    q_stage(IC<0>{});
    __syncthreads();
    sts64(prow + lane * 8, SM_PART, xp.x, xp.y);
    TS(1);
    {
        int it = (warp >> 2) + 5, slot = (warp >> 2) + 1, bar = warp >> 2, par = 0;
        auto refill = [&](bool kv) {
            uint32_t old;
            asm volatile("{\n.reg .pred p;\nelect.sync _|p, 0xffffffff;\nmov.u32 %0, 0;\n@p atom.relaxed.cta.shared.inc.u32 %0, [%1], 3;\n}" : "=r"(old) : "r"(SM_CNT + slot * 8) : "memory");
            if (__any_sync(~0u, old == 3)) {
                if (!kv && it >= 64) {
#pragma unroll 1
                    for (int k = 0; k < SPIN; k++) {
                        int f; asm volatile("ld.volatile.shared.u32 %0, [%1];" : "=r"(f) : "r"(SM_CNT + 4) : "memory");
                        if (f >= slot) break;
                    }
                    sts32(0, SM_CNT + 4, slot + 1);
                    if (elect()) issue_wo(slot);
                } else {
                    wait_due(it, 0);
                    if (elect()) issue_kv(it, slot, bar < 5 ? bar + 5 : bar - 5);
                }
                __syncwarp();
            }
        };
        auto advance = [&]() { it += 2; slot += 2; if (slot >= 5) slot -= 5; bar += 2; if (bar >= 10) { bar -= 10; par ^= 1; } };
        {
            uint32_t offK[3], qf[12];
#pragma unroll
            for (int j = 0; j < 3; j++) offK[j] = pin(((tid >> 5) & 3) * SUB + 3 * g * 128 + (((2 * t) ^ ((3 * g + j) & 7)) << 4));
#pragma unroll
            for (int i = 0; i < 12; i++) qf[i] = 0;
            const uint32_t ksl = pin(ksw + lane * 16), sca = pin(prow + g * 64);
            int n0 = 0;
#pragma unroll 1
            for (int e = 0; e < 16; e++) {
                TR(1, 1 + 2 * e);
                mbar_wait(SM_CBAR + bar * 8, par);
                TR(1, 2 + 2 * e); TR(2, 1 + 2 * e);
                uint4 v[6];
#pragma unroll
                for (int i = 0; i < 6; i++) v[i] = lds128(ad(offK[i >> 1] ^ ((i & 1) * 16), slot * HT), SM_RING + (i >> 1) * 128);
                refill(true);
                TR(2, 2 + 2 * e);
                advance();
                if ((0xc20 | ((2 << NP) - 1)) >> e & 1) {
                    refresh();
                    static_for<0, NP>([&](auto E) {
                        if (e == E.value) {
#pragma unroll
                            for (int i = 0; i < 6; i++) {
                                uint32_t* k = kc + 90 + 24 * E.value + 4 * i;
                                asm volatile("mov.b32 %0, %4; mov.b32 %1, %5; mov.b32 %2, %6; mov.b32 %3, %7;" : "=r"(k[0]), "=r"(k[1]), "=r"(k[2]), "=r"(k[3]) : "r"(v[i].x), "r"(v[i].y), "r"(v[i].z), "r"(v[i].w));
                            }
                            if (E.value == NP - 2 && warp < 6) {
#pragma unroll
                                for (int i = 0; i < 2; i++)
                                    asm volatile("cp.async.cg.shared.global [%0], [%1], 16;" :: "r"(ksl + SM_KS + 10240 + i * 512),
                                                 "l"(&g_ll[0][(cta & ~3) + 2 * i + (lane >> 4)][warp * 32 + (lane & 15) * 2]) : "memory");
                            }
                            if (E.value == NP - 1 && warp < 6) {
                                asm volatile("cp.async.wait_all;" ::: "memory");
                                __syncwarp();
                                const uint32_t a = ksw + lane * 8;
                                const float q = ll_gather4(&g_ll[0][cta & ~3][tid], ep4 + 1, lds_u64(a, SM_KS + 10240), lds_u64(a, SM_KS + 10496), lds_u64(a, SM_KS + 10752), lds_u64(a, SM_KS + 11008));
                                sts16(q_addr(), SM_QU, pack_bf(q, q));
                                __syncwarp();
                                if (elect()) mbar_arrive(SM_QBAR);
                            }
                        }
                    });
                    if (e == NP) {
                        mbar_wait(SM_QBAR, 0);
#pragma unroll
                        for (int k = 0; k < 3; k++) lds128(qf + 4 * k, (lane & 7) * 48, SM_QU + k * 16);
                        static_for<0, NP>([&](auto E) {
                            uint4 r[6];
#pragma unroll
                            for (int i = 0; i < 6; i++) { const uint32_t* k = kc + 90 + 24 * E.value + 4 * i; r[i] = make_uint4(k[0], k[1], k[2], k[3]); }
                            stsf(sca, SM_PART + 256 + (E.value + 6) * 4, score6(r, qf));
                        });
#pragma unroll
                        for (int i = 0; i < 24; i++) asm volatile("mov.b32 %0, 0;" : "=r"(kc[i]));
                    } else if (e == 5) {
#pragma unroll
                        for (int k = 0; k < 22; k++) lds128(kc + 4 * k, ksl, SM_KS + k * 512);
                        lds64(kc + 88, ksl, SM_KS + 22 * 512);
                        n0 = 0;
                    } else if (e == 10) {
#pragma unroll
                        for (int k = 0; k < 22; k++)
                            asm volatile("ld.shared.v4.b32 {%0,%1,%2,%3}, [%4];" : "=r"(kc[90 + 4 * k]), "=r"(kc[91 + 4 * k]), "=r"(kc[92 + 4 * k]), "=r"(kc[93 + 4 * k]) : "r"(ad(ksl, SM_KS + k * 512)) : "memory");
                        asm volatile("ld.shared.v2.b32 {%0,%1}, [%2];" : "=r"(kc[178]), "=r"(kc[179]) : "r"(ad(ksl, SM_KS + 22 * 512)) : "memory");
                        n0 = 0;
                    } else if (e == 11) {
                        lds64(kc + 180, ksl, SM_KS + 520); lds128(kc + 182, ksl, SM_KS + 1024); lds128(kc + 186, ksl, SM_KS + 1536); lds64(kc + 190, ksl, SM_KS + 2048);
                        n0 = 3;
                    }
                }
                const int n = (e + 6) & 15;
                stsf(ad(sca, n * 4), SM_PART + 256, score6(v, qf));
                uint32_t m = bf2_amax(bf2_amax(v[0].x, v[0].y), bf2_amax(v[0].z, v[0].w)), mn = bf2_amin(bf2_amin(v[0].x, v[0].y), bf2_amin(v[0].z, v[0].w));
#pragma unroll
                for (int i = 1; i < 6; i++) m = bf2_amax(m, bf2_amax(bf2_amax(v[i].x, v[i].y), bf2_amax(v[i].z, v[i].w)));
                m = max(m & 0x7fff, (m >> 16) & 0x7fff);
                m = max(m, __shfl_xor_sync(~0u, m, 1)); m = max(m, __shfl_xor_sync(~0u, m, 2));
#pragma unroll
                for (int i = 1; i < 6; i++) mn = bf2_amin(mn, bf2_amin(bf2_amin(v[i].x, v[i].y), bf2_amin(v[i].z, v[i].w)));
                mn = min(mn & 0x7fff, (mn >> 16) & 0x7fff);
                const int sh = min(max((int)(m >> 7) - 15, 0), 126);
                asm volatile("st.shared.u8 [%0], %1;" :: "r"(ad(ad((tid >> 2) * 16, n), SM_SH)), "r"(sh) : "memory");
                const uint32_t dn = (127 - sh) * 0x00800080u;
                if (__any_sync(~0u, (int)(mn >> 7) <= sh || m >= (142 << 7))) {
                    if (m >= (142 << 7)) sts32(0, SM_BIG, 1);
                    const uint32_t up = (127 + 256 + sh) * 0x00800080u;
#pragma unroll
                    for (int i = 0; i < 6; i++) {
                        const uint32_t r0 = bf2_fma(bf2_mul(v[i].x, dn), up, v[i].x), r1 = bf2_fma(bf2_mul(v[i].y, dn), up, v[i].y);
                        const uint32_t r2 = bf2_fma(bf2_mul(v[i].z, dn), up, v[i].z), r3 = bf2_fma(bf2_mul(v[i].w, dn), up, v[i].w);
                        asm volatile("{\n.reg .pred p;\n.reg .u32 x, a;\nsetp.ne.u32 p, %0, 0;\nmov.u32 x, %7;\n@p atom.relaxed.cta.shared.inc.u32 x, [%6], 0x7fffffff;\n"
                                     "setp.lt.u32 p, x, %7;\nmad.lo.u32 a, x, 16, %8;\n@p st.shared.v4.u32 [a], {%1,%2,%3,%4};\n"
                                     "mad.lo.u32 a, x, 4, %9;\n@p st.shared.u32 [a], %5;\n}"
                                     :: "r"(r0 | r1 | r2 | r3), "r"(r0), "r"(r1), "r"(r2), "r"(r3), "r"(tid << 16 | n << 8 | i * 8), "r"(SM_XN), "n"(XCAP), "n"(SM_XR), "n"(SM_XM) : "memory");
                    }
                }
                const uint32_t ae = (n0 >> 1) * 512 + (n0 & 1) * 8, ao = ((n0 + 1) >> 1) * 512 + (~n0 & 1) * 8;
                uint32_t o[18];
#pragma unroll
                for (int i = 0; i < 6; i++) {
                    const uint32_t y0 = bf2_mulv(v[i].x, dn), y1 = bf2_mulv(v[i].y, dn), y2 = bf2_mulv(v[i].z, dn), y3 = bf2_mulv(v[i].w, dn);
                    o[3 * i] = __byte_perm(y0, y1, 0x6420); o[3 * i + 1] = __byte_perm(y2, y3, 0x6420);
                    const uint32_t hb = __byte_perm(y2, y3, 0x7531);
                    o[3 * i + 2] = __byte_perm(y0, y1, 0x7531) | __funnelshift_l(hb, hb, 4);
                    if (i & 1) {
#pragma unroll
                        for (int k = 3 * (i >> 1); k < 3 * (i >> 1) + 3; k++) sts64(ad(ksl, (k & 1) ? ao : ae), SM_KS + (k >> 1) * 512, o[2 * k], o[2 * k + 1]);
                    }
                }
                n0 += 9;
            }
            fence_async();
        }
        TS(2);
        refresh();
        {
            const uint4 sc = lds128(prow + lane * 16, SM_PART + 256);
            const float S[4] = {__uint_as_float(sc.x), __uint_as_float(sc.y), __uint_as_float(sc.z), __uint_as_float(sc.w)};
            softmax(IC<0>{}, S);
        }
        fw = 0.f; xp = make_uint2(0, 0);
#pragma unroll 1
        for (int e = 0; e < 16; e++) {
            if ((1 << PUBAT | 1 << ZCHK | 1 << 15) >> e & 1) {
                if (e == PUBAT) {
                    if (tid < 196) st_rlx(&g_ll[1][cta][tid], tid < 192 ? 0ull : ll_pack(ldsf((tid > 192) * 4, SM_STAT), ep4 + 2));
                } else if (e == ZCHK) {
                    if (lane < 4) asm volatile("cp.async.cg.shared.global [%0], [%1], 16;" :: "r"(SM_PART + 512 + prow + lane * 16), "l"(&g_ll[1][cta ^ lane][192]) : "memory");
                    if (warp == 7) {
#pragma unroll 1
                        for (int k = 0; k < SPIN; k++) {
                            uint32_t v; asm volatile("ld.acquire.gpu.global.u32 %0, [%1];" : "=r"(v) : "l"(&g_zflag) : "memory");
                            if (__all_sync(~0u, v * 4 == ep4 + 4)) break;
                        }
                    }
                } else {
                    asm volatile("cp.async.wait_all;" ::: "memory");
                    __syncwarp();
                    head_weight(IC<0>{}, lds_u64(prow + t * 16, SM_PART + 512), lds_u64(prow + t * 16, SM_PART + 520));
                }
                __syncwarp();
            }
            const uint32_t pp = lds32(ad(t * 4, prow + ((e + 6) & 15) * 16), SM_PART + 256);
            TR(3, 1 + 2 * e);
            mbar_wait(SM_CBAR + bar * 8, par);
            TR(3, 2 + 2 * e);
            uint4 v[6];
            load_v(v, (warp & 3) * SUB + slot * HT, SM_RING);
            if (e < 15) refill(false);
            advance();
            pv(v, pp);
        }
    }
    TS(3);
    tail(IC<0>{});

    q_stage(IC<1>{});
    {
        const uint32_t c0 = clk();
        const uint32_t ksl = pin(ksw + lane * 16), qa = pin(q_addr()), qb0 = pin(lane < 8 ? lane * 48 : SM_ZQ - SM_VEC);
        const u64* qp = &g_ll[1][cta & ~3][tid];
        uint32_t ks[96], qf[12];
        u64 qw[4] = {0, 0, 0, 0};
#pragma unroll
        for (int k = 0; k < PRE; k++) lds128(ks + 4 * k, ksl, SM_KS + k * 512);
        while (clk() - c0 < QDELAY);
        if (warp < 6) {
#pragma unroll
            for (int i = 0; i < 4; i++) qw[i] = ld_rlx(qp + i * 256);
        }
        if constexpr (E3) issue2(IC<3>{});
        if constexpr (QLATE) {
            issue2(IC<2>{});
            issue2(IC<1>{});
        }
        if (warp < 6) {
            const float q = ll_gather4(qp, ep4 + 3, qw[0], qw[1], qw[2], qw[3]) * rstd_q;
            TS(24);
            const uint32_t qq = bf2_mul(pack_bf(q, q), 0x3f807180u);
            sts16(qa, SM_VEC, qq); sts16(qa, SM_QU, qq >> 16);
            if (!(fabsf(q) < 1048576.f)) sts32(0, SM_BIG, 1);
            __syncwarp();
            if (elect()) mbar_arrive(SM_QBAR);
        } else if (!E3) mbar_wait(SM_QBAR, 1);
        if constexpr (!E3) issue2(IC<3>{});
        mbar_wait(SM_QBAR, 1);
        TS(12); TR(4, 1); TR(5, 1);
        auto load_q = [&](int u, int k) { lds128(qf + 4 * k, u == 0 ? qb0 : (lane >> 3) == u ? lane * 48 : SM_ZQ - SM_VEC + u * 384, SM_VEC - u * 384 + k * 16); };
        load_q(0, 1); load_q(0, 2); load_q(0, 0);
        float D[4][4];
        uint4 vb[NPK + 2][6];
        uint32_t xn;
        auto step = [&](auto Q) {
            constexpr int st = Q.value, p = cord(st), s = PL.slot[p];
            TR(4, 2 + 2 * st);
            mbar_wait(barw + s * 8, IC<PL.par[p]>::value);
            TR(4, 3 + 2 * st);
            load_v(vb[st < NPK ? st : NPK + (st & 1)], slot_u(s), slot_o(s));
            static_for<0, PL.nld[st]>([&](auto K) { issue2(IC<PL.ld[st][K.value]>{}); });
        };
        static_for<0, 96>([&](auto I) {
            constexpr int F = I.value, n = F / 6, i = n ? F % 6 : (F + 2) % 6;
            const uint32_t* c = n == 0 ? (i < 2 ? ks + 3 * i : kc + 174 + 3 * i) : n < 6 ? ks + 18 * n - 12 + 3 * i : kc + 18 * (n - 6) + 3 * i;
            const uint32_t ha = c[2] & 0x87878787u, hb = __funnelshift_r(c[2], c[2], 4) & 0x87878787u;
            if (F < 24 && F % 6 == 0) zero4(D[n]);
            mma(D[n & 3], __byte_perm(c[0], ha, 0x5140), __byte_perm(c[0], ha, 0x7362), __byte_perm(c[1], hb, 0x5140), __byte_perm(c[1], hb, 0x7362), qf[2 * i], qf[2 * i + 1]);
            if constexpr ((n & 3) == 3 && n < 15 && (i & 1)) load_q((n + 1) >> 2, i >> 1);
            static_for<PRE, 24>([&](auto U) {
                if constexpr (((U.value - PRE + 1) * 4 + 2) / 3 - 1 + KSL == F) {
                    lds128(ks + 4 * U.value, ksl, SM_KS + U.value * 512);
                    if constexpr (U.value % 6 == 5) issue2(IC<3 + U.value / 6>{});
                }
            });
            if constexpr (F == 2) sts64(prow + lane * 8, SM_PART, xp.x, xp.y);
            if constexpr (F == XAT) {
                                { const uint2 x = lds64(0, SM_XN); xn = x.y ? XCAP + 1 : x.x; }
                sts128(prow + lane * 16, SM_PART + 256, 0, 0, 0, 0);
                __syncwarp();
#pragma unroll 1
                for (uint32_t idx = lane; idx < (xn > XCAP ? 0 : xn); idx += 32) {
                    const uint32_t m = lds32(idx * 4, SM_XM);
                    if ((m >> 21) == warp) {
                        const uint4 r = lds128(idx * 16, SM_XR);
                        const uint32_t qo = ((m >> 16) & 3) * 48 + (m & 255);
                        const uint2 a = lds64(qo, SM_QU), b = lds64(qo, SM_QU + 192);
                        const float s = ((bf_lo(r.x) * bf_lo(a.x) + bf_hi(r.x) * bf_hi(a.x)) + (bf_lo(r.y) * bf_lo(b.x) + bf_hi(r.y) * bf_hi(b.x))) +
                                        ((bf_lo(r.z) * bf_lo(a.y) + bf_hi(r.z) * bf_hi(a.y)) + (bf_lo(r.w) * bf_lo(b.y) + bf_hi(r.w) * bf_hi(b.y)));
                        asm volatile("red.relaxed.cta.shared.add.f32 [%0], %1;" :: "r"(SM_PART + 256 + prow + ((m >> 18) & 7) * 64 + ((m >> 8) & 15) * 4), "f"(s) : "memory");
                    }
                }
                __syncwarp();
            }
            if constexpr (F == PK0 - 2) { refresh(); lds128(kc + 8, tid * 16, SM_PK); }
            static_for<0, NPK>([&](auto Q) { if constexpr (F == PK0 + Q.value * PKD) step(Q); });
        });
        float S[4];
        {
            const uint32_t shp = lds32(tid * 4, SM_SH);
            const uint4 cr = lds128(prow + lane * 16, SM_PART + 256);
            const uint32_t c[4] = {cr.x, cr.y, cr.z, cr.w};
#pragma unroll
            for (int j = 0; j < 4; j++) S[j] = (D[j][0] + D[j][3]) * __uint_as_float((((shp >> (8 * j)) & 255) + 27) << 23) + __uint_as_float(c[j]);
        }
        if (xn > XCAP) {
#pragma unroll
            for (int k = 0; k < 3; k++) lds128(qf + 4 * k, (lane & 7) * 48, SM_QU + k * 16);
#pragma unroll 1
            for (int e = 0; e < 16; e++) {
                uint4 v[6];
#pragma unroll
                for (int i = 0; i < 6; i++) v[i] = ldg128(P.k + (size_t)(roww + 256 * e + g) * DH + (i >> 1) * 64 + (2 * t + (i & 1)) * 8);
                const float s = score6(v, qf);
#pragma unroll
                for (int j = 0; j < 4; j++) if (4 * t + j == ((e + 6) & 15)) S[j] = s;
            }
        }
        TS(25);
        softmax(IC<1>{}, S);
        auto pv_at = [&](auto Q) { constexpr int st = Q.value; pv(vb[st < NPK ? st : NPK + (st & 1)], lds32(ad(t * 4, prow), SM_PART + 256 + ((vunit(cord(st)) + 6) & 15) * 16)); };
        u64 pm, pl;
        static_for<NPK, 16>([&](auto Q) {
            constexpr int st = Q.value;
            if constexpr (st == HWAT) ld_rlx2(&g_ll[2][cta ^ t][192], pm, pl);
            if constexpr (st == HWC) head_weight(IC<1>{}, pm, pl);
            step(Q);
            if constexpr (st == WOPF) { if (elect()) tma3_pf(tmk + TM_WO, 5 * (cta & 3), (cta >> 2) * DH + warp * 24, POL_NORMAL); }
            if constexpr (st - NPK < NPK) pv_at(IC<st - NPK>{});
            if constexpr (st > NPK) pv_at(IC<st - 1>{});
        });
        pv_at(IC<15>{});
    }
    TS(13);
    tail(IC<1>{});
}

typedef CUresult (*EncodeFn)(CUtensorMap*, CUtensorMapDataType, cuuint32_t, void*, const cuuint64_t*, const cuuint64_t*, const cuuint32_t*,
                             const cuuint32_t*, CUtensorMapInterleave, CUtensorMapSwizzle, CUtensorMapL2promotion, CUtensorMapFloatOOBfill);

}

extern "C" void kernel_launch(void* const* d_in, const int* in_sizes, int n_in, void* d_out, int out_size) {
    (void)in_sizes; (void)n_in; (void)out_size;
    static EncodeFn enc = nullptr;
    if (!enc) {
        void* fn = nullptr;
        cudaDriverEntryPointQueryResult qr;
        cudaGetDriverEntryPoint("cuTensorMapEncodeTiled", &fn, cudaEnableDefault, &qr);
        enc = (EncodeFn)fn;
        cudaFuncSetAttribute(fused_kernel, cudaFuncAttributeMaxDynamicSharedMemorySize, SM_TOTAL);
    }
    Params P;
    const cuuint32_t ones[3] = {1, 1, 1};
    for (int m = TM_K; m <= TM_V8; m++) {
        const cuuint64_t dim[3] = {64, 3, (cuuint64_t)NHEAD * SK}, str[2] = {128, DH * 2};
        const cuuint32_t box[3] = {m == TM_VP ? 8u : 64u, 3, m == TM_V8 ? 8u : 32u};
        enc(&P.tm[m], CU_TENSOR_MAP_DATA_TYPE_BFLOAT16, 3, d_in[m == TM_K ? 1 : 2], dim, str, box, ones, CU_TENSOR_MAP_INTERLEAVE_NONE,
            m == TM_VP ? CU_TENSOR_MAP_SWIZZLE_NONE : CU_TENSOR_MAP_SWIZZLE_128B, CU_TENSOR_MAP_L2_PROMOTION_NONE, CU_TENSOR_MAP_FLOAT_OOB_FILL_NONE);
    }
    {
        const cuuint64_t dim[3] = {64, NHEAD * 3, D_MODEL}, str[2] = {128, NHEAD * DH * 2};
        const cuuint32_t box[3] = {64, 3, 32};
        enc(&P.tm[TM_WQ], CU_TENSOR_MAP_DATA_TYPE_BFLOAT16, 3, d_in[3], dim, str, box, ones, CU_TENSOR_MAP_INTERLEAVE_NONE,
            CU_TENSOR_MAP_SWIZZLE_128B, CU_TENSOR_MAP_L2_PROMOTION_NONE, CU_TENSOR_MAP_FLOAT_OOB_FILL_NONE);
    }
    {
        const cuuint64_t dim[2] = {DFF, D_MODEL}, str[1] = {DFF * 2};
        const cuuint32_t box[2] = {16, 128};
        enc(&P.tm[TM_W1], CU_TENSOR_MAP_DATA_TYPE_BFLOAT16, 2, d_in[6], dim, str, box, ones, CU_TENSOR_MAP_INTERLEAVE_NONE,
            CU_TENSOR_MAP_SWIZZLE_32B, (CUtensorMapL2promotion)W1PROMO, CU_TENSOR_MAP_FLOAT_OOB_FILL_NONE);
    }
    {
        const cuuint64_t dim[3] = {32, 20, NHEAD * DH}, str[2] = {64, D_MODEL * 2};
        const cuuint32_t box[3] = {32, 5, 16};
        enc(&P.tm[TM_WO], CU_TENSOR_MAP_DATA_TYPE_BFLOAT16, 3, d_in[4], dim, str, box, ones, CU_TENSOR_MAP_INTERLEAVE_NONE,
            CU_TENSOR_MAP_SWIZZLE_64B, CU_TENSOR_MAP_L2_PROMOTION_L2_128B, CU_TENSOR_MAP_FLOAT_OOB_FILL_NONE);
    }
    {
        const cuuint64_t dim[4] = {32, 20, 24, NHEAD * 8}, str[3] = {64, D_MODEL * 2, 24 * D_MODEL * 2};
        const cuuint32_t box[4] = {32, 5, 8, 4}, ones4[4] = {1, 1, 1, 1};
        enc(&P.tm[TM_WO4], CU_TENSOR_MAP_DATA_TYPE_BFLOAT16, 4, d_in[4], dim, str, box, ones4, CU_TENSOR_MAP_INTERLEAVE_NONE,
            CU_TENSOR_MAP_SWIZZLE_64B, (CUtensorMapL2promotion)WOPROMO, CU_TENSOR_MAP_FLOAT_OOB_FILL_NONE);
        const cuuint32_t thin[4] = {8, 5, 8, 4};
        enc(&P.tm[TM_WOP], CU_TENSOR_MAP_DATA_TYPE_BFLOAT16, 4, d_in[4], dim, str, thin, ones4, CU_TENSOR_MAP_INTERLEAVE_NONE,
            CU_TENSOR_MAP_SWIZZLE_NONE, CU_TENSOR_MAP_L2_PROMOTION_NONE, CU_TENSOR_MAP_FLOAT_OOB_FILL_NONE);
    }
    {
        const cuuint64_t dim[3] = {64, 10, DFF}, str[2] = {128, D_MODEL * 2};
        const cuuint32_t box[3] = {64, 10, 12};
        enc(&P.tm[TM_W2], CU_TENSOR_MAP_DATA_TYPE_BFLOAT16, 3, d_in[8], dim, str, box, ones, CU_TENSOR_MAP_INTERLEAVE_NONE,
            CU_TENSOR_MAP_SWIZZLE_128B, CU_TENSOR_MAP_L2_PROMOTION_NONE, CU_TENSOR_MAP_FLOAT_OOB_FILL_NONE);
    }
    P.x = (const __nv_bfloat16*)d_in[0];
    P.k = (const __nv_bfloat16*)d_in[1];
    P.b1 = (const __nv_bfloat16*)d_in[7];
    P.b2 = (const __nv_bfloat16*)d_in[9];
    P.out = (__nv_bfloat16*)d_out;
    fused_kernel<<<NCTA + 1, NTHR, SM_TOTAL, cudaStreamPerThread>>>(P);
}
```

```cpp
#include <cuda_runtime.h>
#include <cuda_bf16.h>
#include <cuda.h>
#include <stdint.h>

namespace {

constexpr int D_MODEL = 640, NHEAD = 32, SK = 32768, DH = 192, WIN = 4096, DFF = 1536;
constexpr int NCTA = 128, NTHR = 256;
constexpr int SUB = 8 * DH * 2;
constexpr int HT = 4 * SUB;
constexpr int WOU = 8 * 320;
constexpr int XCAP = 48;
constexpr int SM_RING = 1024;
constexpr int SM_W2 = SM_RING + 8 * WOU;
constexpr int SM_WQ = SM_RING + 5 * HT;
constexpr int SM_KS = SM_WQ + 5 * HT;
constexpr int SM_PART = SM_KS + 8 * HT;
constexpr int SM_BAR = SM_PART + 6144;
constexpr int SM_VEC = SM_BAR + 512;
constexpr int SM_QU = SM_VEC + 384;
constexpr int SM_ZQ = SM_QU + 384;
constexpr int SM_CS = SM_ZQ + 64;
constexpr int SM_XR = SM_CS + 768;
constexpr int SM_XM = SM_XR + XCAP * 16;
constexpr int SM_SH = SM_XM + XCAP * 4;
constexpr int SM_C1 = SM_SH + 1024;
constexpr int SM_ML = SM_C1 + 320;
constexpr int SM_B1 = SM_ML + 64;
constexpr int SM_STAT = SM_B1 + 128;
constexpr int SM_QBAR = SM_STAT + 40;
constexpr int SM_CBAR = SM_QBAR + 8;
constexpr int SM_CNT = SM_CBAR + 128;
constexpr int SM_XN = SM_CNT + 56;
constexpr int SM_BIG = SM_XN + 4;
constexpr int SM_EPOCH = SM_BIG + 4;
constexpr int SM_FXS = SM_EPOCH + 4;
constexpr int SM_T0 = SM_FXS + 4;
constexpr int SM_TS = SM_T0 + 4;
constexpr int SM_TOTAL = 232448;
static_assert(SM_TS + 160 <= SM_RING + SM_TOTAL, "smem");

constexpr int SPIN = 1 << 20;
enum { TM_WQ = 0, TM_K = 1, TM_V = 2, TM_VP = 3, TM_V8 = 4, TM_WO = 5, TM_W1 = 6, TM_WO4 = 7, TM_W2 = 8, TM_WOP = 9 };
constexpr uint32_t POL_NORMAL = 0x16F00000u, POL_FIRST = 0x12F00000u;

#define PACE 484
#define PACE0 1800
#define KEEP0 32
#define NP 3
#define VORD 0x456789a23b10cdefull
#define CORD 0x2fedcba987654310ull
#define ISS 0x0100111010111111ull
#define X2AT 9
#define R56 6
#define PRE 6
#define KSL 0
#define PK0 34
#define PKD 12
#define NPK 6
#define XAT 94
#define LEAD 4
#define ARDELAY 600
#define QDELAY 300
#define PUBAT 8
#define ZCHK 14
#define S6D 900
#define S6G 200
#define XD 600
#define XG 200
#define TB 2
#define WOPACE 403
#define WOD 0
#define NPF0 0
#define HWAT 11
#define HWC 15
#define ODELAY1 600
#define ODELAY2 200
#define W1P 9999
#define W2P 600
#define W2LATE 0
#define NOW12 0
#define W1PROMO 2
#define W1FIRST 1
#define WOPROMO 2
#define NPFC 6
#define PFD 1200
#define PFG 150
#define PFPOL POL_NORMAL
#define E3 0
#define SKIP 0
#define W1G 150
#define KA 27
#define KAD 600
#define KAD2 900
#define PVNOW 13
#define I0D 100
#define I0G 0
#define I2D 0
#define I2G 0
#define FX2_MASK 0xfff00000u
#define LNLATE 0
#define AR1D 400
#define I0LATE 0
#define I1D 0
#define I1G 0
#define WFIRST 1
#define PREP1 10
#define PREP2 11
#define HZD 9000
#define B2AT 12
#define AR1DN 1000
#define ARDN 600
#define NI0 3
#define W1ST 0
#define W1D 100
#define W1POL POL_FIRST
#define WOKEEP 2
#define WPF2 8
#define WOPF 99
#define QLATE 0
#define W2POL POL_NORMAL
#define FX2LIM 524288.f

struct Plan { int slot[18], par[18], nld[16], ld[16][3]; bool ok; };
__host__ __device__ constexpr int cord(int s) { return (int)(CORD >> (4 * s) & 15); }
constexpr Plan make_plan() {
    Plan s{};
    int phase[7] = {}, state[18] = {}, freeat[7] = {}, k = 0;
    for (int p = 0; p < 7; p++) { s.slot[p] = p; phase[p] = p != 1; state[p] = 1; freeat[p] = -1; }
    s.ok = true;
    for (int st = 0; st < 16; st++) {
        const int p = cord(st);
        if (state[p] != 1 || (p == 2 && !state[16])) s.ok = false;
        state[p] = 2;
        freeat[p == 2 ? s.slot[16] : s.slot[p]] = st;
        for (int n = (int)(ISS >> (4 * st) & 15); n > 0; n--, k++) {
            const int it = k < X2AT ? 7 + k : k == X2AT ? 16 : k < 10 ? 6 + k : 17;
            int best = -1;
            for (int c = 0; c < 7; c++) if (c != 2 && freeat[c] >= 0 && (c < 5 || k < R56) && (best < 0 || freeat[c] < freeat[best])) best = c;
            if (it == 17) best = freeat[5] >= 0 && freeat[6] >= 0 ? 5 : -1;
            if (best < 0 || k > 10 || s.nld[st] == 3) { s.ok = false; return s; }
            s.slot[it] = best; freeat[best] = -1; state[it] = 1;
            if (it != 16) s.par[it] = phase[best]++ & 1;
            s.ld[st][s.nld[st]++] = it;
        }
    }
    if (k != 11) s.ok = false;
    for (int st = B2AT; st < 16; st++) if (s.slot[cord(st) == 2 ? 16 : cord(st)] == 6) s.ok = false;
    return s;
}
constexpr Plan PL = make_plan();
static_assert(PL.ok, "bad pass-2 plan");
__host__ __device__ constexpr int vunit(int p) { return (int)(VORD >> (4 * p) & 15); }

template <int I> struct IC { static constexpr int value = I; };
template <int A, int B, class F> __device__ __forceinline__ void static_for(F&& f) {
    if constexpr (A < B) { f(IC<A>{}); static_for<A + 1, B>(f); }
}

struct Params {
    CUtensorMap tm[10];
    const __nv_bfloat16 *x, *b1, *b2, *k;
    __nv_bfloat16* out;
};

typedef unsigned long long u64;
constexpr int ACC_PITCH = 256;
constexpr int ACC_BYTES = 80 * ACC_PITCH;
__device__ __align__(1024) unsigned char g_acc[4 * ACC_BYTES];
__device__ __align__(8192) u64 g_ll[NCTA][256];
__device__ unsigned g_epoch;
__device__ __align__(128) unsigned g_zflag;
#define NXTRA 0
#define DBG(i, v)
#define TS(i)
#define TSB(i)
#define TSA(i)
#define TR(k, i)

__device__ __forceinline__ void mbar_wait(uint32_t bar, uint32_t parity) {
    asm volatile("{\n.reg .pred p, q;\n.reg .u32 n;\nmov.u32 n, 0;\n"
                 "LOOP:\nmbarrier.try_wait.parity.shared::cta.b64 p, [%0], %1;\n"
                 "add.u32 n, n, 1;\nsetp.lt.and.u32 q, n, 0x100000, !p;\n@q bra.uni LOOP;\n}"
                 :: "r"(bar), "r"(parity) : "memory");
}
__device__ __forceinline__ bool mbar_test(uint32_t bar, uint32_t parity) {
    uint32_t done;
    asm volatile("{\n.reg .pred p;\nmbarrier.test_wait.parity.shared::cta.b64 p, [%1], %2;\nselp.u32 %0, 1, 0, p;\n}" : "=r"(done) : "r"(bar), "r"(parity) : "memory");
    return __any_sync(~0u, done);
}
__device__ __forceinline__ bool elect() {
    uint32_t r;
    asm volatile("{\n.reg .pred p;\nelect.sync _|p, 0xffffffff;\nselp.u32 %0, 1, 0, p;\n}" : "=r"(r));
    return r != 0;
}
__device__ __forceinline__ void mbar_init(uint32_t bar, uint32_t n) { asm volatile("mbarrier.init.shared::cta.b64 [%0], %1;" :: "r"(bar), "r"(n) : "memory"); }
__device__ __forceinline__ void mbar_arrive(uint32_t bar) { asm volatile("mbarrier.arrive.shared::cta.b64 _, [%0];" :: "r"(bar) : "memory"); }
__device__ __forceinline__ void mbar_expect(uint32_t bar, uint32_t bytes) {
    asm volatile("mbarrier.arrive.expect_tx.shared::cta.b64 _, [%0], %1;" :: "r"(bar), "r"(bytes) : "memory");
}
__device__ __forceinline__ void fence_async() { asm volatile("fence.proxy.async.shared::cta;" ::: "memory"); }
#define DI __device__ __forceinline__
DI uint32_t ad(uint32_t a, uint32_t o) { uint32_t r; asm("add.u32 %0, %1, %2;" : "=r"(r) : "r"(a), "r"(o)); return r; }
DI uint4 lds128(uint32_t a, int o) {
    uint4 v; asm volatile("ld.shared.v4.u32 {%0,%1,%2,%3}, [%4];" : "=r"(v.x), "=r"(v.y), "=r"(v.z), "=r"(v.w) : "r"(ad(a, o)) : "memory"); return v;
}
DI void lds128(uint32_t* v, uint32_t a, int o) {
    asm volatile("ld.shared.v4.u32 {%0,%1,%2,%3}, [%4];" : "=r"(v[0]), "=r"(v[1]), "=r"(v[2]), "=r"(v[3]) : "r"(ad(a, o)) : "memory");
}
DI void lds64(uint32_t* v, uint32_t a, int o) { asm volatile("ld.shared.v2.u32 {%0,%1}, [%2];" : "=r"(v[0]), "=r"(v[1]) : "r"(ad(a, o)) : "memory"); }
DI uint4 ldsm_t(uint32_t a, int o) {
    uint4 v; asm volatile("ldmatrix.sync.aligned.m8n8.x4.trans.shared.b16 {%0,%1,%2,%3}, [%4];" : "=r"(v.x), "=r"(v.y), "=r"(v.z), "=r"(v.w) : "r"(ad(a, o)) : "memory"); return v;
}
DI uint2 lds64(uint32_t a, int o) { uint2 v; asm volatile("ld.shared.v2.u32 {%0,%1}, [%2];" : "=r"(v.x), "=r"(v.y) : "r"(ad(a, o)) : "memory"); return v; }
DI float2 lds64f(uint32_t a, int o) { const uint2 v = lds64(a, o); return make_float2(__uint_as_float(v.x), __uint_as_float(v.y)); }
DI uint32_t lds32(uint32_t a, int o) { uint32_t v; asm volatile("ld.shared.u32 %0, [%1];" : "=r"(v) : "r"(ad(a, o)) : "memory"); return v; }
DI float ldsf(uint32_t a, int o) { return __uint_as_float(lds32(a, o)); }
DI void sts32(uint32_t a, int o, uint32_t v) { asm volatile("st.shared.u32 [%0], %1;" :: "r"(ad(a, o)), "r"(v) : "memory"); }
DI void stsf(uint32_t a, int o, float v) { sts32(a, o, __float_as_uint(v)); }
DI void sts16(uint32_t a, int o, uint32_t v) { asm volatile("st.shared.u16 [%0], %1;" :: "r"(ad(a, o)), "h"((uint16_t)v) : "memory"); }
DI void sts64(uint32_t a, int o, uint32_t x, uint32_t y) { asm volatile("st.shared.v2.u32 [%0], {%1,%2};" :: "r"(ad(a, o)), "r"(x), "r"(y) : "memory"); }
DI void sts64f(uint32_t a, int o, float x, float y) { sts64(a, o, __float_as_uint(x), __float_as_uint(y)); }
DI void sts128(uint32_t a, int o, uint32_t x, uint32_t y, uint32_t z, uint32_t w) {
    asm volatile("st.shared.v4.u32 [%0], {%1,%2,%3,%4};" :: "r"(ad(a, o)), "r"(x), "r"(y), "r"(z), "r"(w) : "memory");
}
DI void sts128f(uint32_t a, int o, const float (&v)[4]) {
    asm volatile("st.shared.v4.f32 [%0], {%1,%2,%3,%4};" :: "r"(ad(a, o)), "f"(v[0]), "f"(v[1]), "f"(v[2]), "f"(v[3]) : "memory");
}
DI void sts128f_if(bool p, uint32_t a, int o, float x, float y, float z, float w) {
    asm volatile("{\n.reg .pred p;\nsetp.ne.u32 p, %5, 0;\n@p st.shared.v4.f32 [%0], {%1,%2,%3,%4};\n}" :: "r"(ad(a, o)), "f"(x), "f"(y), "f"(z), "f"(w), "r"((int)p) : "memory");
}
DI void sts32_if(bool p, uint32_t a, int o, uint32_t v) {
    asm volatile("{\n.reg .pred p;\nsetp.ne.u32 p, %2, 0;\n@p st.shared.u32 [%0], %1;\n}" :: "r"(ad(a, o)), "r"(v), "r"((int)p) : "memory");
}
__device__ __forceinline__ uint32_t atoms_inc(uint32_t a, uint32_t lim) {
    uint32_t old; asm volatile("atom.relaxed.cta.shared.inc.u32 %0, [%1], %2;" : "=r"(old) : "r"(a), "r"(lim) : "memory"); return old;
}
__device__ __forceinline__ void mma(float (&c)[4], uint32_t a0, uint32_t a1, uint32_t a2, uint32_t a3, uint32_t b0, uint32_t b1) {
    asm volatile("mma.sync.aligned.m16n8k16.row.col.f32.bf16.bf16.f32 {%0,%1,%2,%3}, {%4,%5,%6,%7}, {%8,%9}, {%0,%1,%2,%3};"
                 : "+f"(c[0]), "+f"(c[1]), "+f"(c[2]), "+f"(c[3]) : "r"(a0), "r"(a1), "r"(a2), "r"(a3), "r"(b0), "r"(b1));
}
__device__ __forceinline__ void mma(float (&c)[4], const uint4& a, uint32_t b0, uint32_t b1) { mma(c, a.x, a.y, a.z, a.w, b0, b1); }
__device__ __forceinline__ void zero4(float (&c)[4]) { c[0] = c[1] = c[2] = c[3] = 0.f; }
__device__ __forceinline__ u64 ld_rlx(const void* p) {
    u64 a; asm volatile("ld.relaxed.gpu.global.u64 %0, [%1];" : "=l"(a) : "l"(p) : "memory"); return a;
}
__device__ __forceinline__ void ld_rlx2(const void* p, u64& a, u64& b) {
    asm volatile("ld.relaxed.gpu.global.v2.u64 {%0,%1}, [%2];" : "=l"(a), "=l"(b) : "l"(p) : "memory");
}
__device__ __forceinline__ void st_rlx(void* p, u64 a) { asm volatile("st.relaxed.gpu.global.u64 [%0], %1;" :: "l"(p), "l"(a) : "memory"); }
__device__ __forceinline__ uint4 ldg128(const void* p) {
    uint4 v; asm volatile("ld.global.nc.L1::no_allocate.L2::cache_hint.v4.u32 {%0,%1,%2,%3}, [%4], %5;" : "=r"(v.x), "=r"(v.y), "=r"(v.z), "=r"(v.w) : "l"(p), "l"((u64)POL_FIRST << 32)); return v;
}
__device__ __forceinline__ u64 ll_pack(float v, uint32_t tag) { return ((u64)tag << 32) | __float_as_uint(v); }
__device__ __forceinline__ float ll_val(u64 w) { return __uint_as_float((uint32_t)w); }
__device__ __forceinline__ uint32_t ll_tag(u64 w) { return (uint32_t)(w >> 32); }
__device__ __forceinline__ float bf_lo(uint32_t u) { return __uint_as_float(u << 16); }
__device__ __forceinline__ float bf_hi(uint32_t u) { return __uint_as_float(u & 0xffff0000u); }
__device__ __forceinline__ uint32_t pack_bf(float lo, float hi) {
    uint32_t r; asm("cvt.rn.bf16x2.f32 %0, %1, %2;" : "=r"(r) : "f"(hi), "f"(lo)); return r;
}
__device__ __forceinline__ uint32_t pick(uint32_t a, uint32_t sel) { uint32_t r; asm("prmt.b32 %0, %1, 0, %2;" : "=r"(r) : "r"(a), "r"(sel)); return r; }
__device__ __forceinline__ uint32_t bf2_amax(uint32_t a, uint32_t b) { uint32_t r; asm("max.NaN.xorsign.abs.bf16x2 %0, %1, %2;" : "=r"(r) : "r"(a), "r"(b)); return r; }
__device__ __forceinline__ uint32_t bf2_amin(uint32_t a, uint32_t b) { uint32_t r; asm("min.xorsign.abs.bf16x2 %0, %1, %2;" : "=r"(r) : "r"(a), "r"(b)); return r; }
__device__ __forceinline__ uint32_t bf2_mulv(uint32_t a, uint32_t b) { uint32_t r; asm volatile("mul.rn.bf16x2 %0, %2, %1;" : "=r"(r) : "r"(a), "r"(b)); return r; }
__device__ __forceinline__ uint32_t bf2_mul(uint32_t a, uint32_t b) { uint32_t r; asm("mul.rn.bf16x2 %0, %1, %2;" : "=r"(r) : "r"(a), "r"(b)); return r; }
__device__ __forceinline__ uint32_t bf2_fma(uint32_t a, uint32_t b, uint32_t c) { uint32_t r; asm("fma.rn.bf16x2 %0, %1, %2, %3;" : "=r"(r) : "r"(a), "r"(b), "r"(c)); return r; }
__device__ __forceinline__ float ex2(float v) { float r; asm("ex2.approx.ftz.f32 %0, %1;" : "=f"(r) : "f"(v)); return r; }
__device__ __forceinline__ float rcp(float v) { float r; asm("rcp.approx.ftz.f32 %0, %1;" : "=f"(r) : "f"(v)); return r; }
__device__ __forceinline__ float rsq(float v) { float r; asm("rsqrt.approx.ftz.f32 %0, %1;" : "=f"(r) : "f"(v)); return r; }
__device__ __forceinline__ void bar_sync(int id, int n) { asm volatile("bar.sync %0, %1;" :: "r"(id), "r"(n) : "memory"); }
__device__ __forceinline__ uint32_t clk() { uint32_t c; asm volatile("mov.u32 %0, %clock;" : "=r"(c)); return c; }
__device__ __forceinline__ uint32_t gtime() { uint32_t c; asm volatile("mov.u32 %0, %globaltimer_lo;" : "=r"(c)); return c; }
__device__ __forceinline__ void spin(uint32_t cycles) { const uint32_t c0 = clk(); while (clk() - c0 < cycles); }
__device__ __forceinline__ uint32_t pin(uint32_t v) { return __shfl_xor_sync(~0u, v, 0); }
__device__ __forceinline__ uint32_t pin(uint32_t v, uint32_t dep) {
    uint32_t r; asm volatile("{\n.reg .u32 b;\nshl.b32 b, %2, 5;\nshfl.sync.bfly.b32 %0, %1, b, 31, 0xffffffff;\n}" : "=r"(r) : "r"(v), "r"(dep)); return r;
}
__device__ __forceinline__ float pinf(float v) { return __shfl_xor_sync(~0u, v, 0); }
template <class T> __device__ __forceinline__ T* pinp(T* p) { return reinterpret_cast<T*>(__shfl_xor_sync(~0u, (u64)p, 0)); }
__device__ __forceinline__ u64 mk64(uint32_t lo, uint32_t hi) { u64 r; asm("mov.b64 %0, {%1, %2};" : "=l"(r) : "r"(lo), "r"(hi)); return r; }
__device__ __forceinline__ float uni(float v) { return __shfl_sync(~0u, v, 0); }
__device__ __forceinline__ float shx(float v, int o) { return __shfl_xor_sync(~0u, v, o); }

__device__ __forceinline__ u64 fx_pack(float v) {
    u64 r; asm("{\n.reg .u32 a, b;\n.reg .s64 w;\ncvt.rni.s64.f32 w, %1;\nmov.b64 {a, b}, w;\nprmt.b32 a, a, 1, 0x3214;\nmov.b64 %0, {a, b};\n}" : "=l"(r) : "f"(v)); return r;
}
__device__ __forceinline__ float fx_scale(float meansq) {
    const int e = max(((int)(__float_as_uint(meansq) >> 23) - 127) >> 1, -6);
    return __uint_as_float((uint32_t)(127 + 32 - e) << 23);
}
__device__ __forceinline__ float fx_inv(float scale) { return __uint_as_float((254u << 23) - __float_as_uint(scale)); }
__device__ __forceinline__ uint32_t lo32(u64 w) { uint32_t l; asm("mov.b64 {%0, _}, %1;" : "=r"(l) : "l"(w)); return l; }
__device__ __forceinline__ int hi32(u64 w) { int h; asm("mov.b64 {_, %0}, %1;" : "=r"(h) : "l"(w)); return h; }
__device__ __forceinline__ float fx_val(u64 w) { return (float)hi32(w) * 4294967296.f + (float)lo32(w); }
__device__ __forceinline__ void fx_poll(const unsigned char* ap, u64 (&w)[4]) {
    asm volatile("{\n.reg .pred p, q;\n.reg .u32 n, a, b, c, d;\nmov.u32 n, 0;\nLOOP:\n"
                 "ld.relaxed.gpu.global.u64 %0, [%4];\nld.relaxed.gpu.global.u64 %1, [%4+5120];\n"
                 "ld.relaxed.gpu.global.u64 %2, [%4+10240];\nld.relaxed.gpu.global.u64 %3, [%4+15360];\n"
                 "add.u32 n, n, 1;\nsetp.ge.u32 q, n, 0x100000;\n@q bra.uni DONE;\n"
                 "mov.b64 {a, _}, %0;\nmov.b64 {b, _}, %1;\nmov.b64 {c, _}, %2;\nmov.b64 {d, _}, %3;\n"
                 "lop3.b32 a, a, b, c, 0x80;\nlop3.b32 a, a, d, 32, 0x80;\nsetp.eq.u32 p, a, 0;\n"
                 "vote.sync.any.pred p, p, 0xffffffff;\n@p bra.uni LOOP;\nDONE:\n}"
                 : "=l"(w[0]), "=l"(w[1]), "=l"(w[2]), "=l"(w[3]) : "l"(ap) : "memory");
}
constexpr u64 FX2_INIT = 256ull + 32 - 96 * ((1ull << 28) + (1ull << 55)), FX2_NONE = 1ull + (1ull << 28) + (1ull << 55);
constexpr float FX2_MAGIC = 12582912.f + 524288.f;

__device__ __forceinline__ void tma3(uint32_t dst, const CUtensorMap* tm, int c1, int c2, uint32_t bar, uint32_t pol) {
    asm volatile("cp.async.bulk.tensor.3d.shared::cluster.global.mbarrier::complete_tx::bytes.L2::cache_hint [%0], [%1, {%2, %3, %4}], [%5], %6;"
                 :: "r"(dst), "l"(tm), "r"(0), "r"(c1), "r"(c2), "r"(bar), "l"((u64)pol << 32) : "memory");
}
__device__ __forceinline__ void tma3_pf(const CUtensorMap* tm, int c1, int c2, uint32_t pol) {
    asm volatile("cp.async.bulk.prefetch.tensor.3d.L2.global.tile.L2::cache_hint [%0, {%1, %2, %3}], %4;"
                 :: "l"(tm), "r"(0), "r"(c1), "r"(c2), "l"((u64)pol << 32) : "memory");
}
__device__ __forceinline__ void bulk_pf(const void* p, uint32_t bytes, uint32_t pol) {
    asm volatile("cp.async.bulk.prefetch.L2.global.L2::cache_hint [%0], %1, %2;" :: "l"(p), "r"(bytes), "l"((u64)pol << 32) : "memory");
}
__device__ __forceinline__ float warp_max(float v) {
#pragma unroll
    for (int o = 16; o; o >>= 1) v = fmaxf(v, shx(v, o));
    return v;
}
__device__ __forceinline__ float warp_sum(float v) {
#pragma unroll
    for (int o = 16; o; o >>= 1) v += shx(v, o);
    return v;
}
__device__ __forceinline__ u64 ll_pack2(float a, float b, uint32_t tag) { return mk64(__byte_perm(__float_as_uint(a), tag, 0x3214), __float_as_uint(b)); }
__device__ __forceinline__ float lof(u64 w) { return __uint_as_float(lo32(w)); }
__device__ __forceinline__ float hif(u64 w) { return __int_as_float(hi32(w)); }
__device__ __forceinline__ void ll_gather4(const u64* buf, uint32_t tag, u64 (&w)[4]) {
#pragma unroll 1
    for (int it = 0; it < SPIN; it++) {
        if (it) { w[0] = ld_rlx(buf); w[1] = ld_rlx(buf + 256); w[2] = ld_rlx(buf + 512); w[3] = ld_rlx(buf + 768); }
        if (!__any_sync(~0u, (((lo32(w[0]) ^ tag) | (lo32(w[1]) ^ tag)) | ((lo32(w[2]) ^ tag) | (lo32(w[3]) ^ tag))) & 255)) break;
    }
}
__device__ __forceinline__ u64 lds_u64(uint32_t a, int o) { const uint2 v = lds64(a, o); return v.x | (u64)v.y << 32; }
__device__ __forceinline__ float sum8(uint32_t a, int o, int pitch) {
    float s[8];
#pragma unroll
    for (int w = 0; w < 8; w++) s[w] = ldsf(a, o + w * pitch);
    return ((s[0] + s[1]) + (s[2] + s[3])) + ((s[4] + s[5]) + (s[6] + s[7]));
}
__device__ __forceinline__ void ln_final(float& mean, float& rstd, float& msq) {
    float2 v[5];
#pragma unroll
    for (int w = 0; w < 5; w++) v[w] = lds64f(0, SM_STAT + w * 8);
    mean = (((v[0].x + v[1].x) + (v[2].x + v[3].x)) + v[4].x) * (1.f / D_MODEL);
    msq = (((v[0].y + v[1].y) + (v[2].y + v[3].y)) + v[4].y) * (1.f / D_MODEL);
    rstd = rsq(fmaxf(msq - mean * mean, 0.f) + 1e-5f);
}
constexpr float CS = 0.07216878364870322f * 1.4426950408889634f;
constexpr uint32_t ONES = 0x3f803f80u;

__global__ void __launch_bounds__(NTHR, 1) fused_kernel(const __grid_constant__ Params P) {
    extern __shared__ __align__(1024) unsigned char smem[];
    const int warp = __shfl_sync(~0u, threadIdx.x >> 5, 0), bx = blockIdx.x;
    const int cta = (((bx >> 1) & 15) + (bx >> 6) * 16) * 4 + ((bx >> 5) & 1) * 2 + (bx & 1);

    if (bx == NCTA) {
        if ((uint32_t)__cvta_generic_to_shared(smem) != SM_RING) __trap();
        const uint32_t ep = *(volatile unsigned*)&g_epoch;
        if (threadIdx.x == 0) {
#pragma unroll 1
            for (int it = 0; it < SPIN; it++) { if (ll_tag(ld_rlx(&g_ll[0][192])) == ep * 4 + 2) break; __nanosleep(200); }
            const uint32_t t0 = gtime();
#pragma unroll 1
            for (int it = 0; it < 1024; it++) { if (gtime() - t0 > HZD) break; __nanosleep(100); }
        }
        __syncthreads();
#pragma unroll 1
        for (int i = threadIdx.x; i < 4 * 80 * 8; i += NTHR)
        {
            const u64 v = (i / 640 & 1) && (i & 7) < 2 ? FX2_INIT : 0ull;
            *reinterpret_cast<ulonglong2*>(g_acc + (i >> 3) * ACC_PITCH + (i & 7) * 16) = make_ulonglong2(v, v);
        }
        __threadfence();
        __syncthreads();
        if (threadIdx.x == 0) asm volatile("st.relaxed.gpu.global.u32 [%0], %1;" :: "l"(&g_zflag), "r"(ep + 1) : "memory");
        return;
    }
    const uint32_t barw = SM_BAR + warp * 64;
    if (elect()) {
        if (warp < NI0) sts32(0, SM_T0, gtime());
        if (warp >= 3) {
            mbar_init(barw + 56, 1);
            asm volatile("fence.mbarrier_init.release.cluster;" ::: "memory");
            mbar_expect(barw + 56, HT);
            tma3(SM_WQ - 3 * HT + warp * HT, &P.tm[TM_WQ], (cta >> 2) * 3, (cta & 3) * 160 - 96 + warp * 32, barw + 56, POL_FIRST);
        }
        TS(31);
    }
    int tid = threadIdx.x, lane, g, t, c4;
    uint32_t selA, selB, offV0, offV2;
    auto derive = [&]() {
        lane = tid & 31; g = lane >> 2; t = lane & 3;
        c4 = (tid & 0xe1) + 16 * (t >> 1) + 2 * g;
        selA = (g & 2) ? 0x4444u : (g & 1) ? 0x1044u : 0x4410u;
        selB = (g & 2) ? ((g & 1) ? 0x1044u : 0x4410u) : 0x4444u;
        offV0 = (6 * t) * 128 + ((g ^ ((6 * t) & 7)) << 4);
        offV2 = (6 * t) * 128 + ((g ^ ((6 * t + 2) & 7)) << 4);
    };
    auto refresh = [&]() { tid = pin(tid); derive(); };
    auto refresh_late = [&]() { mbar_wait(SM_BAR + 3 * 64 + 56, 0); refresh(); };
    derive();
    const int j40 = (cta & 3) * 40;
    const bool mlp = (cta & 3) != 3;
    const int hu = ((cta >> 2) * 3 + (cta & 3)) * 16;
    uint2 xp = make_uint2(0, 0);
    if (tid < 160) xp = *reinterpret_cast<const uint2*>(P.x + 4 * c4);
    else if (tid == 192) xp.x = *(volatile unsigned*)&g_epoch;
    else if (tid >= 224 && tid < 240 && mlp) xp.x = reinterpret_cast<const unsigned short*>(P.b1)[hu + lane];
    __syncwarp();
    if (elect()) {
#pragma unroll
        for (int i = 0; i < 7; i++) mbar_init(barw + i * 8, 1);
        if (warp < 4) mbar_arrive(barw);
        mbar_init(SM_CBAR + warp * 8, 1); mbar_init(SM_CBAR + 64 + warp * 8, 1);
        if (warp == 0) { mbar_init(SM_QBAR, 6); mbar_init(SM_BAR + 56, 8); }
        asm volatile("fence.mbarrier_init.release.cluster;" ::: "memory");
        sts64(warp * 8, SM_CNT, 0, 0);
        sts64(warp * 8, SM_ZQ, 0, 0);
    }
    uint32_t kc[192];
#pragma unroll
    for (int i = 12; i < 192; i++) asm volatile("mov.b32 %0, 0;" : "=r"(kc[i]));
    const int rowc = (cta >> 2) * SK + (SK - WIN) + (cta & 3) * 64;
    const int roww = __shfl_sync(~0u, rowc + warp * 8, 0);
    const CUtensorMap* tmk = reinterpret_cast<const CUtensorMap*>(__shfl_sync(~0u, (u64)&P.tm[0] + (lane >> 5), 0));

    auto wait_due = [&](int i, int extra) {
        const uint32_t due = lds32(0, SM_T0) + PACE0 + extra + i * PACE;
#pragma unroll 1
        for (int it = 0; it < 4096; it++) if ((int)(gtime() - due) >= 0) break;
    };
    auto issue_wo = [&](int k) {
        wait_due(64, k * WOPACE + WOD);
        mbar_expect(SM_CBAR + 32 + k * 8, 4 * WOU);
        asm volatile("cp.async.bulk.tensor.4d.shared::cluster.global.mbarrier::complete_tx::bytes.L2::cache_hint [%0], [%1, {%2, %3, %4, %5}], [%6], %7;"
                     :: "r"(SM_RING + k * 4 * WOU), "l"(tmk + TM_WO4), "r"(0), "r"(5 * (cta & 3)), "r"((k >> 1) * 8), "r"((cta >> 2) * 8 + (k & 1) * 4),
                        "r"(SM_CBAR + 32 + k * 8), "l"((u64)(WOKEEP == 1 && k < 4 ? POL_NORMAL : POL_FIRST) << 32) : "memory");
        if (WOKEEP == 2 && k < 4 && mlp)
            asm volatile("cp.async.bulk.prefetch.tensor.4d.L2.global.tile.L2::cache_hint [%0, {%1, %2, %3, %4}], %5;"
                         :: "l"(tmk + TM_WOP), "r"(0), "r"(5 * (cta & 3)), "r"((k >> 1) * 8), "r"((cta >> 2) * 8 + (k & 1) * 4), "l"((u64)POL_NORMAL << 32) : "memory");
    };
    auto issue_kv = [&](int i, int slot, int bar) {
        const int row = rowc + (i & 30) * 128 + (i & 1) * 32;
        mbar_expect(SM_CBAR + bar * 8, HT);
        tma3(SM_RING + slot * HT, tmk + TM_K + (i >> 5), 0, row, SM_CBAR + bar * 8, POL_FIRST);
        if (i >= KEEP0) tma3_pf(tmk + TM_VP, 0, row, POL_NORMAL);
    };
    __syncwarp();
    if (warp < NI0) { wait_due(warp, 0); if (elect()) issue_kv(warp, warp == 4 ? 0 : warp + 1, warp); }
    if (warp >= 3) mbar_wait(barw + 56, 0);
    if (tid == 192) sts32(0, SM_EPOCH, xp.x);
    if (tid >= 224 && tid < 240) sts32(lane * 4, SM_B1, xp.x << 16);
    __syncthreads();
    TSB(10);
    if (warp >= NI0 && elect()) {
        if (warp < 5) issue_kv(warp, warp == 4 ? 0 : warp + 1, warp);
        else if (warp < 5 + NPF0) tma3_pf(tmk + TM_K, 0, rowc + (warp & 30) * 128 + (warp & 1) * 32, POL_FIRST);
    }
    const uint32_t ep4 = __shfl_sync(~0u, lds32(0, SM_EPOCH) * 4, 0);

    auto load_v3 = [&](uint4* v, uint32_t u, int o, bool odd) {
        if (!odd) { v[0] = lds128(ad(offV0, u), o); v[1] = lds128(ad(offV0 ^ 16, u), o + 128); v[2] = lds128(ad(offV2, u), o + 256); }
        else { v[0] = lds128(ad(offV2 ^ 16, u), o + 384); v[1] = lds128(ad(offV0 ^ 64, u), o + 512); v[2] = lds128(ad(offV0 ^ 80, u), o + 640); }
    };
    auto load_v = [&](uint4 (&v)[6], uint32_t u, int o) { load_v3(v, u, o, false); load_v3(v + 3, u, o, true); };
    const uint32_t wqw = warp * SUB, ksw = warp * HT;
    auto slot_o = [&](int s) { return s < 2 ? SM_WQ + s * 8 * SUB : s == 2 ? 0 : SM_KS + (s - 3) * SUB; };
    const uint32_t w2w = warp < 4 ? SM_WQ + 16 * SUB + wqw : slot_o(IC<PL.slot[16]>::value) + (IC<PL.slot[16]>::value < 2 ? wqw : ksw);
    auto slot_u = [&](int s) { return s < 2 ? wqw : s == 2 ? w2w : ksw; };
    const uint32_t zero = __shfl_sync(~0u, lds32(0, SM_ZQ), 0);
    auto issue2 = [&](auto I, uint32_t dep) {
        constexpr int p = I.value == 16 ? 2 : I.value, s = PL.slot[p];
        __syncwarp();
        TR(5, 2 + I.value);
        if (I.value >= 16 && (SKIP >> (I.value & 1) & 1)) { if ((p != 2 || warp >= 4) && elect()) mbar_arrive(barw + s * 8); }
        else if ((p == 2 ? (warp < 4) == (I.value == 2) : p < 16 || mlp) && elect()) {
            mbar_expect(barw + s * 8, (dep & zero) | (p < 16 ? SUB : 2 * WOU));
            if constexpr (p < 16) tma3(slot_u(s) + slot_o(s), tmk + TM_V8, 0, roww + vunit(p) * 256, barw + s * 8, POL_FIRST);
            else tma3(slot_u(s) + slot_o(s), tmk + TM_WO, 5 * (cta & 3), (cta >> 2) * DH + warp * 24, barw + s * 8, POL_FIRST);
        }
    };
    auto issue_help = [&]() {
        if (elect())
            tma3(SM_WQ + (warp == 7 ? 0 : warp == 6 ? 16 * SUB : 4 * SUB), tmk + (warp == 5 ? TM_V8 : TM_V), 0,
                 rowc + (warp == 6 ? vunit(2) * 256 : warp == 5 ? vunit(0) * 256 + 32 : vunit(0) * 256), warp == 5 ? SM_BAR + 4 * 64 : SM_CBAR - 32 + warp * 8, POL_FIRST);
    };
    auto issue_item1 = [&]() {
        if (elect()) {
            mbar_expect(SM_CBAR - 48 + warp * 8, HT);
            tma3(SM_WQ - 4 * HT + warp * HT, tmk + TM_V, 0, rowc - 192 + warp * 32 + vunit(1) * 256, SM_CBAR - 48 + warp * 8, POL_FIRST);
        }
    };
    const uint32_t prow = warp * 768;
    uint4 wq0[6], wqh[3];
    uint32_t xna;
    auto load_wq = [&]() {
        load_v(wq0, wqw, SM_WQ);
        const int r0 = 6 * t + 3 * (warp & 1);
#pragma unroll
        for (int j = 0; j < 3; j++) wqh[j] = lds128(ad(r0 * 128 + ((g ^ ((r0 + j) & 7)) << 4), (warp >> 1) * SUB), SM_WQ + 16 * SUB + j * 128);
        const int r = c4 - j40;
        xna = pin((tid < 160 && r >= 0 && r < 40) ? SM_VEC + r * 8 : 0u);
        selA = pin(selA); selB = pin(selB);
        offV0 = pin(offV0 + wqw); offV2 = pin(offV2 + wqw);
    };
    float acc[3][4];
    uint32_t cq;
    auto mma3 = [&](const uint4* v, uint32_t pp, uint32_t hi) {
        const uint32_t b0 = pick(pp, selA | hi), b1 = pick(pp, selB | hi);
        mma(acc[0], v[0], b0, b1); mma(acc[1], v[1], b0, b1); mma(acc[2], v[2], b0, b1);
    };
    auto ln_part = [&]() {
        const float x0 = bf_lo(xp.x), x1 = bf_hi(xp.x), x2 = bf_lo(xp.y), x3 = bf_hi(xp.y);
        const float s1 = (x0 + x1) + (x2 + x3), s2 = (x0 * x0 + x1 * x1) + (x2 * x2 + x3 * x3);
        float ss = ((tid & 16) ? s2 : s1) + shx((tid & 16) ? s1 : s2, 16);
        ss += shx(ss, 8); ss += shx(ss, 4); ss += shx(ss, 2); ss += shx(ss, 1);
        sts32_if((tid & 15) == 0 && tid < 160, tid >> 2, SM_STAT, __float_as_uint(ss));
    };

    auto tick = [&](float (&c)[4]) { const uint32_t z = lds32(0, SM_ZQ); mma(c, z, z, z, z, z, z); };
    auto tick_done = [&](const float (&c)[4]) { if (c[0] != 0.f) sts32(0, SM_ZQ + 60, 0); };

    auto q_stage = [&](auto L) {
        constexpr int layer = L.value;
        asm volatile("{\n.reg .pred p;\nsetp.ne.u32 p, %0, 0;\n@p st.shared.v2.u32 [%0], {%1,%2};\n}" :: "r"(xna), "r"(xp.x), "r"(xp.y) : "memory");
        uint4 wq1[6];
        load_v3(wq1, 0, SM_WQ + 8 * SUB, false);
        const uint32_t xra = (tid & 3) * 4;
        __syncthreads();
        if (layer) TSB(20);
        uint32_t p0 = lds32(ad(xra, warp * 16), SM_VEC), ph = lds32(ad(xra, (warp >> 1) * 16), SM_VEC + 256), p1 = lds32(ad(xra, warp * 16), SM_VEC + 128);
        if (layer == 1 && I0LATE && warp >= 5) issue_help();
        if (layer == 0 && g >= 4) p0 = p1 = ph = ONES;
#pragma unroll
        for (int j = 0; j < 3; j++) zero4(acc[j]);
        mma3(wq0, p0, 0); mma3(wq0 + 3, p0, 0x2222);
        load_v3(wq1 + 3, 0, SM_WQ + 8 * SUB, true);
        mma3(wqh, ph, (warp & 1) * 0x2222); mma3(wq1, p1, 0); mma3(wq1 + 3, p1, 0x2222);
        if (layer == 1) { lds128(kc + 8, prow + (tid & 31) * 16, SM_PART); __syncwarp(); }
        u64* dst = &g_ll[cta][tid];
        const uint32_t qpa = ((layer == 0 && (tid & 2)) ? ksw - (SM_PART - SM_KS - 11264) : prow) + (tid & 28) * 8 + (tid & 1) * 16;
#pragma unroll
        for (int j = 0; j < 3; j++) sts128f_if(layer == 0 || !(tid & 2), qpa, SM_PART + j * 256, acc[j][0], acc[j][1], acc[j][2], acc[j][3]);
        if (layer) TS(21);
        __syncthreads();
        if (layer) TSB(22);
        if (warp < 6) {
            const float s = sum8(tid * 4, SM_PART, 768);
            st_rlx(dst, layer ? mk64(2 * ep4 + 5, __float_as_uint(s)) : ll_pack2(sum8(tid * 4, SM_KS + 11264, HT), s, 2 * ep4 + 1));
        } else if (layer == 1 && !I1D) issue_item1();
        if (layer) TS(23);
        cq = clk();
        refresh_late();
        if (!LNLATE || !layer) {
            ln_part();
            __syncthreads();
            sts64(prow + lane * 8, SM_PART, xp.x, xp.y);
        }
    };
    auto q_addr = [&]() { return (((tid >> 1) & 1) * 4 + ((tid >> 4) & 3)) * 48 + ((tid >> 6) * 2 + ((tid >> 3) & 1)) * 8 + ((tid >> 2) & 1) * 4 + (tid & 1) * 2; };
    auto score6 = [&](const uint4 (&v)[6], const uint32_t (&qf)[12]) {
        float d[2][4];
#pragma unroll
        for (int i = 0; i < 6; i++) { if (i < 2) zero4(d[i]); mma(d[i & 1], v[i], qf[2 * i], qf[2 * i + 1]); }
        return (d[0][0] + d[0][3]) + (d[1][0] + d[1][3]);
    };
    auto softmax = [&](auto L, const float (&S)[4]) {
        constexpr int layer = L.value;
        DBG(0 + 8 * layer, S[0] + S[1] + S[2] + S[3]);
        const float mrun = warp_max(fmaxf(fmaxf(S[0], S[1]), fmaxf(S[2], S[3])));
        const float p0 = ex2((S[0] - mrun) * CS), p1 = ex2((S[1] - mrun) * CS), p2 = ex2((S[2] - mrun) * CS), p3 = ex2((S[3] - mrun) * CS);
        const uint32_t pa = pack_bf(p0, p1), pb = pack_bf(p2, p3), pw = prow + t * 64 + g * 2;
        sts16(pw, SM_PART + 256, pa); sts16(pw, SM_PART + 272, pa >> 16); sts16(pw, SM_PART + 288, pb); sts16(pw, SM_PART + 304, pb >> 16);
        const float l = warp_sum((p0 + p1) + (p2 + p3));
        uint32_t old = 0;
        if (lane == 0) {
            sts64f(warp * 8, SM_ML, mrun, l);
            asm volatile("atom.acq_rel.cta.shared.inc.u32 %0, [%1], 7;" : "=r"(old) : "r"(SM_CNT + 48) : "memory");
        }
        if (__any_sync(~0u, old == 7)) {
            __syncwarp();
            const float2 ml = lds64f((lane & 7) * 8, SM_ML);
            float M = fmaxf(ml.x, shx(ml.x, 1)); M = fmaxf(M, shx(M, 2)); M = fmaxf(M, shx(M, 4));
            const float f = ex2((ml.x - M) * CS);
            float Lc = f * ml.y; Lc += shx(Lc, 1); Lc += shx(Lc, 2); Lc += shx(Lc, 4);
            if (lane < 4) st_rlx(&g_ll[cta][192 + lane], ll_pack(lane == 0 ? M : Lc, ep4 + 2 + 2 * layer));
        }
        __syncwarp();
#pragma unroll
        for (int j = 0; j < 3; j++) zero4(acc[j]);
    };
    auto pv = [&](const uint4 (&v)[6], uint32_t pp) { mma3(v, pp, 0); mma3(v + 3, pp, 0x2222); };

    auto head_look = [&](auto L) {
        if (lane < 4) asm volatile("cp.async.cg.shared.global [%0], [%1], 16;" :: "r"(SM_PART + 512 + prow + lane * 16), "l"(&g_ll[cta ^ lane][192]) : "memory");
    };
    float fw;
    auto head_weight = [&](auto L) {
        const uint32_t tag = ep4 + 2 + 2 * L.value;
        uint4 ml;
#pragma unroll 1
        for (int it = 0; it < SPIN; it++) {
            if (it) head_look(L);
            asm volatile("cp.async.wait_all;" ::: "memory");
            __syncwarp();
            asm volatile("ld.volatile.shared.v4.u32 {%0,%1,%2,%3}, [%4];" : "=r"(ml.x), "=r"(ml.y), "=r"(ml.z), "=r"(ml.w) : "r"(SM_PART + 512 + prow + t * 16) : "memory");
            if (!__any_sync(~0u, (ml.y ^ tag) | (ml.w ^ tag))) break;
        }
        const float m = __uint_as_float(ml.x);
        float M = fmaxf(m, shx(m, 1)); M = fmaxf(M, shx(M, 2));
        float Lh = ex2((m - M) * CS) * __uint_as_float(ml.z); Lh += shx(Lh, 1); Lh += shx(Lh, 2);
        fw = ex2((ldsf(warp * 8, SM_ML) - M) * CS) * rcp(Lh) * ldsf(0, SM_FXS);
    };

    uint32_t wa[5], ya, oa, selC, selD;
    uint4 z[5];
    unsigned char* ra;
    const u64* lp;
    auto load_u = [&](uint4 (&a)[5], uint32_t u, int o) {
#pragma unroll
        for (int k = 0; k < 5; k++) a[k] = lds128(ad(wa[k], u), o);
    };
    auto tail_prep1 = [&](auto L) {
        xp = lds64(prow + lane * 8, SM_PART);
        ya = pin(prow + (8 * g + 4 * (t & 1)) * 4);
        oa = pin(((tid >> 5) * 12 + min(lane, 11)) * 8);
        lp = pinp(reinterpret_cast<const u64*>(reinterpret_cast<const char*>(&g_ll[cta][0]) + oa));
    };
    auto tail_prep2 = [&](auto L) {
#pragma unroll
        for (int k = 0; k < 5; k++) {
            const int row = (t & 1) + 2 * (t & 2) + 2 * (k < 4 ? k >> 1 : g >> 2), j = k < 4 ? 2 * (k & 1) + (g >> 2) : 4;
            wa[k] = pin(row * 320 + j * 64 + (((g & 3) ^ (((5 * row + j) >> 1) & 3)) << 4));
        }
        selA = pin(selA); selB = pin(selB);
        selC = selA | (g >> 2) * 0x2222; selD = selB | (g >> 2) * 0x2222;
    };
    auto red_addr = [&](auto L) {
        const int word = t * 160 + j40 + (tid >> 2);
        ra = pinp(g_acc + 2 * L.value * ACC_BYTES + (uint32_t)((word >> 3) * ACC_PITCH + (word & 7) * 8));
    };
    uint4 wf[8], w2r[8];
    uint32_t la, w2a, hpa, ha, *op;
    uint2 b2v;
    const unsigned char* ap;
    unsigned char* ap2;
    float inv1;
    auto load_w1 = [&]() {
#pragma unroll
        for (int j = 0; j < 8; j++) wf[j] = ldsm_t(la, SM_RING + j * 256);
    };
    auto load_w2 = [&]() {
#pragma unroll
        for (int i = 0; i < 8; i++) w2r[i] = lds128(w2a ^ ((i & 1) * 16), SM_W2 + (i >> 1) * 5120 + (i & 1) * 128);
    };
    auto load_b2 = [&]() { asm volatile("ld.global.nc.v2.u32 {%0,%1}, [%2];" : "=r"(b2v.x), "=r"(b2v.y) : "l"(P.b2 + 4 * min(c4, 159))); };
    auto mlp_prep = [&](auto L) {
        unsigned char* const accb = g_acc + 2 * L.value * ACC_BYTES;
        la = (tid >> 5) * 4096 + (64 * ((lane >> 2) & 1) + 4 * ((lane >> 1) & 1) + (lane & 1) + 2 * (lane >> 4)) * 32 + ((((lane >> 3) ^ (lane >> 1)) & 1) << 4);
        w2a = pin((10 * t + 2 * (tid >> 5)) * 128 + ((g ^ ((2 * t + 2 * (tid >> 5)) & 7)) << 4));
        hpa = pin((tid >> 5) * 64 + (t * 8 + g) * 4); ha = pin((lane & 15) * 4);
        if (L.value == 0) { selA = pin(selA); selB = pin(selB); }
        ap = accb + (uint32_t)((c4 >> 3) * ACC_PITCH + (c4 & 7) * 8);
        ap2 = pinp(accb + ACC_BYTES + (uint32_t)((c4 >> 2) * ACC_PITCH + (c4 & 3) * 8));
        inv1 = fx_inv(ldsf(0, SM_FXS));
        if (L.value == 1) { ap = pinp(ap); load_w1(); load_w2(); op = pinp(reinterpret_cast<uint32_t*>(P.out) + 2 * c4); }
    };
    auto tail = [&](auto L) {
        constexpr int layer = L.value;
        auto park = [&]() { sts128(prow + lane * 16, SM_PART, kc[8], kc[9], kc[10], kc[11]); };
        {
#pragma unroll
            for (int j = 0; j < 3; j++) sts128f_if(!(tid & 2), ya, SM_PART + 256 * j, acc[j][0] * fw, acc[j][2] * fw, acc[j][1] * fw, acc[j][3] * fw);
            const uint32_t tag = (2 * ep4 + 3 + 4 * layer) & 255;
            __syncthreads();
            TSB(4 + 10 * layer);
            float2 own;
            {
                float2 s[8];
#pragma unroll
                for (int w = 0; w < 8; w++) s[w] = lds64f(oa, SM_PART + w * 768);
                own.x = ((s[0].x + s[1].x) + (s[2].x + s[3].x)) + ((s[4].x + s[5].x) + (s[6].x + s[7].x));
                own.y = ((s[0].y + s[1].y) + (s[2].y + s[3].y)) + ((s[4].y + s[5].y) + (s[6].y + s[7].y));
                st_rlx(const_cast<u64*>(lp), ll_pack2(own.x, own.y, tag));
            }
            DBG(1 + 8 * layer, own.x + own.y);
            const uint32_t c0 = clk();
            if (layer == 0) refresh_late();
            uint4 v[5], u[5];
            if constexpr (layer == 0) {
                if (warp < 3) { if (elect()) issue_wo(3 + warp); __syncwarp(); }
                tail_prep2(L);
                mbar_wait(SM_CBAR + 32 + (warp >> 2) * 8, 0);
                load_u(v, warp * WOU, SM_RING);
                __syncthreads();
            }
            constexpr int YP = layer ? SM_WQ : SM_PART;
            float y[3][4];
#pragma unroll
            for (int j = 0; j < 3; j++) zero4(y[j]);
            const u64 *l1 = reinterpret_cast<const u64*>((u64)lp ^ 4096), *l2 = reinterpret_cast<const u64*>((u64)lp ^ 2048), *l3 = reinterpret_cast<const u64*>((u64)lp ^ 6144);
            while (clk() - c0 < (layer ? ODELAY2 : ODELAY1));
            const uint32_t w1due = layer ? 0 : lds32(0, SM_T0) + PACE0 + 69 * PACE + W1D + (warp - 3) * W1G;
            u64 w1 = ld_rlx(l1), w2 = ld_rlx(l2), w3 = ld_rlx(l3);
            if constexpr (layer == 1) {
                if (mlp) mbar_wait(barw + 40, IC<PL.par[17]>::value);
                TS(30);
                load_u(v, mlp ? ksw + slot_o(5) : SM_RING + warp * WOU, 0); load_u(u, mlp ? ksw + slot_o(5) + WOU : SM_RING + (8 + warp) * WOU, 0);
                if (KA & 8) tick(y[2]);
            }
            if (layer == 0 && warp >= 3 && mlp) {
#pragma unroll 1
                for (int it = 0; it < 4096; it++) if ((int)(gtime() - w1due) >= 0) break;
                if (elect()) {
                    mbar_expect(SM_CBAR + 56 + warp * 8, 4096);
                    asm volatile("cp.async.bulk.tensor.2d.shared::cluster.global.mbarrier::complete_tx::bytes.L2::cache_hint [%0], [%1, {%2, %3}], [%4], %5;"
                                 :: "r"(SM_RING + (warp - 3) * 4096), "l"(tmk + TM_W1), "r"(hu), "r"(warp * 128 - 384), "r"(SM_CBAR + 56 + warp * 8), "l"((u64)POL_FIRST << 32) : "memory");
                }
                __syncwarp();
            }
#pragma unroll 1
            for (int it = 0; it < SPIN; it++) {
                if (it) { w1 = ld_rlx(l1); w2 = ld_rlx(l2); w3 = ld_rlx(l3); }
                if (!__any_sync(~0u, ((lo32(w1) ^ tag) | (lo32(w2) ^ tag) | (lo32(w3) ^ tag)) & 255)) break;
            }
            TS(5 + 10 * layer);
            const uint32_t od = pack_bf((own.x + __uint_as_float(lo32(w1) ^ tag)) + (__uint_as_float(lo32(w2) ^ tag) + __uint_as_float(lo32(w3) ^ tag)),
                                        (own.y + __int_as_float(hi32(w1))) + (__int_as_float(hi32(w2)) + __int_as_float(hi32(w3))));
            DBG(2 + 8 * layer, bf_lo(od) + bf_hi(od));
            const uint32_t o0 = __shfl_sync(~0u, od, tid & 3), o1 = __shfl_sync(~0u, od, (tid & 3) + 4), o2 = __shfl_sync(~0u, od, (tid & 3) + 8);
            auto narrow = [&](const uint4 (&a)[5], uint32_t o) { mma(y[2], a[4], pick(o, selC), pick(o, selD)); };
            auto wide = [&](const uint4 (&a)[5], uint32_t o) {
                const uint32_t b0 = pick(o, selA), b1 = pick(o, selB), b2 = pick(o, selA | 0x2222), b3 = pick(o, selB | 0x2222);
                mma(y[0], a[0], b0, b1); mma(y[1], a[1], b0, b1); mma(y[0], a[2], b2, b3); mma(y[1], a[3], b2, b3);
            };
            narrow(v, o0); wide(v, o0);
            if constexpr (layer == 0) {
                mbar_wait(SM_CBAR + 48 + (warp >> 2) * 8, 0);
                load_u(u, warp * WOU, SM_RING + 8 * WOU);
                __syncwarp();
                if (mlp && elect() && atoms_inc(SM_CNT + 44, 7) == 7) { mbar_expect(SM_CBAR + 120, 20480); tma3(SM_W2, tmk + TM_W2, 0, hu, SM_CBAR + 120, POL_FIRST); }
                __syncwarp();
                narrow(u, o1); wide(u, o1);
                red_addr(L);
                mbar_wait(SM_CBAR + 64 + (warp >> 2) * 8, 0);
                TS(28);
                load_u(z, warp * WOU, SM_RING + 16 * WOU);
                narrow(z, o2);
            } else { narrow(u, o1); narrow(z, o2); wide(u, o1); }
            wide(z, o2);
#pragma unroll
            for (int k = 0; k < 4; k++) y[2][k] += shx(y[2][k], 18);
            sts128f_if(!(tid & 18), ya, YP + 512, y[2][0], y[2][1], y[2][2], y[2][3]);
            sts128f_if(!(tid & 2), ya, YP, y[0][0], y[0][1], y[0][2], y[0][3]);
            sts128f_if(!(tid & 2), ya, YP + 256, y[1][0], y[1][1], y[1][2], y[1][3]);
            __syncthreads();
            if (warp < 5) {
                const float s = sum8(tid * 4, YP, 768);
                DBG(3 + 8 * layer, s);
                asm volatile("red.relaxed.gpu.global.add.u64 [%0], %1;" :: "l"(ra), "l"(fx_pack(s)) : "memory");
            }
            TS(6 + 10 * layer);
            cq = clk();
            if (layer == 0) refresh_late();
        }
        if (layer == 1 && !mlp) return;
        if (warp < 5) {
            if (layer == 0) { mlp_prep(L); if (mlp) mbar_wait(SM_CBAR + 80 + warp * 8, 0); TS(29); load_w1(); }
            {
                u64 w[4];
                while (clk() - cq < (layer || mlp ? AR1D : AR1DN));
                if (layer) TS(11);
                fx_poll(ap, w);
                TS(7 + 10 * layer);
                xp = make_uint2(pack_bf(bf_lo(xp.x) + fx_val(w[0]) * inv1, bf_hi(xp.x) + fx_val(w[1]) * inv1),
                                pack_bf(bf_lo(xp.y) + fx_val(w[2]) * inv1, bf_hi(xp.y) + fx_val(w[3]) * inv1));
            }
            DBG(4 + 8 * layer, bf_lo(xp.x) + bf_hi(xp.y));
            {
                const bool ev = layer || !(tid & 4), od = layer || (tid & 4);
                const uint32_t e0 = ev ? xp.x : ONES, e1 = ev ? xp.y : ONES, o0 = od ? xp.x : ONES, o1 = od ? xp.y : ONES;
                float d[8][4];
#pragma unroll
                for (int j = 0; j < 8; j++) { zero4(d[j]); mma(d[j], wf[j], (j & 1) ? o0 : e0, (j & 1) ? o1 : e1); }
                float lo = d[0][0] + d[1][1], hi = d[0][2] + d[1][3];
#pragma unroll
                for (int m = 1; m < 4; m++) if ((tid & 3) == m) { lo = d[2 * m][0] + d[2 * m + 1][1]; hi = d[2 * m][2] + d[2 * m + 1][3]; }
                float dd = ((tid & 1) ? hi : lo) + shx((tid & 1) ? lo : hi, 1);
                dd += shx(dd, 2);
                ln_part();
                if (layer == 0) {
                    const float cl = ((d[0][1] + d[1][0]) + (d[2][1] + d[3][0])) + ((d[4][1] + d[5][0]) + (d[6][1] + d[7][0]));
                    const float ch = ((d[0][3] + d[1][2]) + (d[2][3] + d[3][2])) + ((d[4][3] + d[5][2]) + (d[6][3] + d[7][2]));
                    sts32_if(!(tid & 2), hpa, SM_C1, __float_as_uint((tid & 1) ? ch : cl));
                }
                sts32_if(!(tid & 2), hpa, SM_QU, __float_as_uint(dd));
            }
            const float b1v = ldsf(ha, SM_B1);
            float csum = layer ? ldsf(ha, SM_B1 + 64) : 0.f;
            bar_sync(1, layer ? 160 : 192);
            TSB(26 + layer);
            float mean, rstd, msq;
            ln_final(mean, rstd, msq);
            float hp[5];
#pragma unroll
            for (int w = 0; w < 5; w++) hp[w] = ldsf(ha, SM_QU + w * 64);
            if constexpr (layer == 0) {
                float c[5];
#pragma unroll
                for (int w = 0; w < 5; w++) c[w] = ldsf(ha, SM_C1 + w * 64);
                csum = ((c[0] + c[1]) + (c[2] + c[3])) + c[4];
                load_w2();
            }
            float hv = ((((hp[0] + hp[1]) + (hp[2] + hp[3])) + hp[4]) - mean * csum) * rstd + b1v;
            hv = hv * rcp(1.f + ex2(hv * (-2.302208198f - 0.1029432397f * hv * hv)));
            const uint32_t hd = pack_bf(hv, hv);
            DBG(5 + 8 * layer, mlp ? hv : 0.f);
            float yA[4] = {0.f, 0.f, 0.f, 0.f}, yB[4] = {0.f, 0.f, 0.f, 0.f};
            const uint32_t hh[4] = {__shfl_sync(~0u, hd, tid & 3), __shfl_sync(~0u, hd, (tid & 3) + 4), __shfl_sync(~0u, hd, (tid & 3) + 8), __shfl_sync(~0u, hd, (tid & 3) + 12)};
#pragma unroll
            for (int i = 0; i < 4; i++) {
                const uint32_t b0 = pick(hh[i], selA), b1 = pick(hh[i], selB);
                mma(yA, w2r[2 * i], b0, b1); mma(yB, w2r[2 * i + 1], b0, b1);
            }
            const float sc2 = __uint_as_float((uint32_t)(127 + 16 - max(((int)(__float_as_uint(msq) >> 23) - 127) >> 1, -100)) << 23);
            float y[4];
            uint32_t yb[4];
#pragma unroll
            for (int k = 0; k < 4; k++) { y[k] = (tid & 2) ? yB[k] : yA[k]; yb[k] = __float_as_uint(fmaf(y[k], sc2, FX2_MAGIC)); }
            DBG(6 + 8 * layer, mlp ? y[0] + y[1] + y[2] + y[3] : 0.f);
            const uint32_t big = !mlp ? 0 : (((yb[0] ^ 0x4b400000u) | (yb[1] ^ 0x4b400000u)) | ((yb[2] ^ 0x4b400000u) | (yb[3] ^ 0x4b400000u))) & FX2_MASK;
            u64 w[2], old[2];
#pragma unroll
            for (int k = 0; k < 2; k++) {
                w[k] = mk64(big ? 0 : yb[2 * k] * 512 + 0x80000001u, big ? 0 : yb[2 * k + 1] * 16 + 0x4c000000u);
                if (layer == 0) { if (mlp) asm volatile("red.relaxed.gpu.global.add.u64 [%0], %1;" :: "l"(ap2 + k * 40 * ACC_PITCH), "l"(w[k]) : "memory"); }
                else asm volatile("atom.relaxed.gpu.global.add.u64 %0, [%1], %2;" : "=l"(old[k]) : "l"(ap2 + k * 40 * ACC_PITCH), "l"(w[k]) : "memory");
            }
            TS(8 + 10 * layer);
            const uint32_t c0 = clk();
            if (__any_sync(~0u, big)) {
                if (big) {
#pragma unroll
                    for (int k = 0; k < 4; k++)
                        asm volatile("red.relaxed.gpu.global.add.u64 [%0], %1;" :: "l"(ap2 + (k >> 1) * 40 * ACC_PITCH + 64 + (k & 1) * 32), "l"(fx_pack(y[k] * fx_scale(msq))) : "memory");
                    __threadfence();
#pragma unroll
                    for (int k = 0; k < 2; k++) {
                        asm volatile("red.relaxed.gpu.global.and.b64 [%0], %1;" :: "l"(ap2 + k * 40 * ACC_PITCH), "l"(~256ull) : "memory");
                        w[k] = FX2_NONE;
                        asm volatile("atom.relaxed.gpu.global.add.u64 %0, [%1], %2;" : "=l"(old[k]) : "l"(ap2 + k * 40 * ACC_PITCH), "l"(FX2_NONE) : "memory");
                    }
                }
                __syncwarp();
            }
            if (layer == 0) { refresh(); load_b2(); park(); stsf(ha, SM_B1 + 64, csum); }
            stsf(0, SM_FXS, msq);
            const float inv32 = fx_inv(sc2) * 0.03125f;
            float xb[4] = {bf_lo(xp.x) + bf_lo(b2v.x) - 24.f * inv32, bf_hi(xp.x) + bf_hi(b2v.x), bf_lo(xp.y) + bf_lo(b2v.y) - 24.f * inv32, bf_hi(xp.y) + bf_hi(b2v.y)};
            auto add_wide = [&]() {
                __threadfence();
#pragma unroll
                for (int k = 0; k < 4; k++) xb[k] += fx_val(ld_rlx(ap2 + (k >> 1) * 40 * ACC_PITCH + 64 + (k & 1) * 32)) * fx_inv(fx_scale(ldsf(0, SM_FXS)));
            };
            auto sum2 = [&](int k) {
                return pack_bf(xb[2 * k] + (float)(int)__funnelshift_r(lo32(w[k]), hi32(w[k]), 4) * inv32, xb[2 * k + 1] + (float)hi32(w[k]) * (inv32 + inv32));
            };
            if constexpr (layer == 1) {
#pragma unroll
                for (int k = 0; k < 4; k++) xb[k] = pinf(xb[k]);
                mbar_wait(SM_BAR + 3 * 64 + 56, 0);
#pragma unroll
                for (int k = 0; k < 2; k++) {
                    w[k] += old[k];
                    asm volatile("{\n.reg .pred p;\nsetp.eq.u32 p, %2, 0;\n@p st.global.u32 [%0], %1;\n}" :: "l"(op + k), "r"(sum2(k)), "r"(~lo32(w[k]) & 0x180) : "memory");
                }
                TS(19);
                if (((lo32(w[0]) & ~(lo32(w[0]) >> 1)) | (lo32(w[1]) & ~(lo32(w[1]) >> 1))) & 128) {
                    add_wide();
                    if (w[0] & 128) op[0] = sum2(0);
                    if (w[1] & 128) op[1] = sum2(1);
                }
            } else {
                load_wq();
                __syncwarp();
                if (elect()) mbar_arrive(SM_BAR + 56);
#pragma unroll
                for (int k = 0; k < 4; k++) xb[k] = pinf(xb[k]);
                while (clk() - c0 < (mlp ? ARDELAY : ARDN));
                uint32_t want = 0x180;
#pragma unroll 1
                for (int it = 0; it < SPIN; it++) {
                    if (it && !__any_sync(~0u, ~(lo32(w[0]) & lo32(w[1])) & 128)) { add_wide(); want = 128; }
                    w[0] = ld_rlx(ap2); w[1] = ld_rlx(ap2 + 40 * ACC_PITCH);
                    if (!__any_sync(~0u, ~(lo32(w[0]) & lo32(w[1])) & want)) break;
                }
                xp = make_uint2(sum2(0), sum2(1));
                TS(9);
                DBG(7, bf_lo(xp.x) + bf_hi(xp.y));
            }
        } else if constexpr (layer == 1) {
            if ((KA & 16) && warp == 7) {
                float c[4] = {0.f, 0.f, 0.f, 0.f};
                const uint32_t c1 = clk();
                while (clk() - c1 < KAD2) tick(c);
                tick_done(c);
            }
        } else {
            const uint32_t c0 = clk();
            load_wq();
            __syncwarp();
            if (elect()) mbar_arrive(SM_BAR + 56);
            float c[4] = {0.f, 0.f, 0.f, 0.f};
            if (warp == 5) {
                if (mlp) mbar_wait(SM_CBAR + 120, 0);
                asm volatile("bar.arrive 1, 192;" ::: "memory");
            }
            while (clk() - c0 < S6D + (warp - 5) * S6G) if (KA & 2) tick(c);
            issue2(IC<0>{}, wq0[0].x | wq0[1].x | wq0[2].x | wq0[3].x | wq0[4].x | wq0[5].x);
            if (warp == 5) {
#pragma unroll 1
                for (int k = 0; k < NPFC; k++) {
                    while (clk() - c0 < PFD + k * PFG);
                    if (elect()) tma3_pf(tmk + TM_V8, 0, rowc + (k >> 3) * 256 + (k & 7) * 8, PFPOL);
                }
            }
            if (elect()) mbar_expect(warp == 5 ? SM_BAR + 4 * 64 : SM_CBAR - 32 + warp * 8, warp == 5 ? SUB : HT);
#pragma unroll 1
            for (int it = 0; it < SPIN; it++) { if (mbar_test(SM_BAR + 56, 0)) break; if (KA & 2) tick(c); }
            const uint32_t c1 = clk();
            park();
            while (clk() - c1 < I0D + (7 - warp) * I0G) if (KA & 2) tick(c);
            if (!I0LATE) issue_help();
            tick_done(c);
        }
    };

    load_wq();
    q_stage(IC<0>{});
    TS(1);
    {
        int it = (warp >> 2) + 5, slot = (warp >> 2) + 1, bar = warp >> 2, par = 0;
        auto refill = [&](bool kv) {
            uint32_t old;
            asm volatile("{\n.reg .pred p;\nelect.sync _|p, 0xffffffff;\nmov.u32 %0, 0;\n@p atom.relaxed.cta.shared.inc.u32 %0, [%1], 3;\n}" : "=r"(old) : "r"(SM_CNT + slot * 8) : "memory");
            if (__any_sync(~0u, old == 3)) {
                if (!kv && it >= 64) {
#pragma unroll 1
                    for (int k = 0; k < SPIN; k++) {
                        int f; asm volatile("ld.volatile.shared.u32 %0, [%1];" : "=r"(f) : "r"(SM_CNT + 4) : "memory");
                        if (f >= slot) break;
                    }
                    sts32(0, SM_CNT + 4, slot + 1);
                    if (elect()) issue_wo(slot);
                } else {
                    wait_due(it, 0);
                    if (elect()) issue_kv(it, slot, bar < 5 ? bar + 5 : bar - 5);
                }
                __syncwarp();
            }
        };
        auto advance = [&]() { it += 2; slot += 2; if (slot >= 5) slot -= 5; bar += 2; if (bar >= 10) { bar -= 10; par ^= 1; } };
        {
            uint32_t offK[3], qf[12];
#pragma unroll
            for (int j = 0; j < 3; j++) offK[j] = pin(((tid >> 5) & 3) * SUB + 3 * g * 128 + (((2 * t) ^ ((3 * g + j) & 7)) << 4));
#pragma unroll
            for (int i = 0; i < 12; i++) qf[i] = kc[i] = 0;
            const uint32_t ksl = pin(ksw + lane * 16), sca = pin(prow + g * 64);
            int n0 = 0;
#pragma unroll 1
            for (int e = 0; e < 16; e++) {
                TR(1, 1 + 2 * e);
                mbar_wait(SM_CBAR + bar * 8, par);
                TR(1, 2 + 2 * e); TR(2, 1 + 2 * e);
                uint4 v[6];
#pragma unroll
                for (int i = 0; i < 6; i++) v[i] = lds128(ad(offK[i >> 1] ^ ((i & 1) * 16), slot * HT), SM_RING + (i >> 1) * 128);
                refill(true);
                TR(2, 2 + 2 * e);
                advance();
                if ((0xc20 | ((2 << NP) - 1)) >> e & 1) {
                    refresh();
                    static_for<0, NP>([&](auto E) {
                        if (e == E.value) {
#pragma unroll
                            for (int i = 0; i < 6; i++) {
                                uint32_t* k = kc + 90 + 24 * E.value + 4 * i;
                                asm volatile("mov.b32 %0, %4; mov.b32 %1, %5; mov.b32 %2, %6; mov.b32 %3, %7;" : "=r"(k[0]), "=r"(k[1]), "=r"(k[2]), "=r"(k[3]) : "r"(v[i].x), "r"(v[i].y), "r"(v[i].z), "r"(v[i].w));
                            }
                            if (E.value == NP - 2 && warp < 6) {
#pragma unroll
                                for (int i = 0; i < 2; i++)
                                    asm volatile("cp.async.cg.shared.global [%0], [%1], 16;" :: "r"(ksl + SM_KS + 10240 + i * 512),
                                                 "l"(&g_ll[(cta & ~3) + 2 * i + (lane >> 4)][warp * 32 + (lane & 15) * 2]) : "memory");
                            }
                            if (E.value == NP - 1 && warp < 6) {
                                asm volatile("cp.async.wait_all;" ::: "memory");
                                __syncwarp();
                                const uint32_t a = ksw + lane * 8;
                                u64 w[4] = {lds_u64(a, SM_KS + 10240), lds_u64(a, SM_KS + 10496), lds_u64(a, SM_KS + 10752), lds_u64(a, SM_KS + 11008)};
                                ll_gather4(&g_ll[cta & ~3][tid], 2 * ep4 + 1, w);
                                const float cs = (lof(w[0] & ~255ull) + lof(w[1] & ~255ull)) + (lof(w[2] & ~255ull) + lof(w[3] & ~255ull));
                                float q = (hif(w[0]) + hif(w[1])) + (hif(w[2]) + hif(w[3]));
                                stsf(tid * 4, SM_CS, cs);
                                float mean, rstd, msq;
                                ln_final(mean, rstd, msq);
                                stsf(0, SM_FXS, fx_scale(msq));
                                q = (q - mean * cs) * rstd;
                                sts16(q_addr(), SM_QU, pack_bf(q, q));
                                __syncwarp();
                                if (elect()) mbar_arrive(SM_QBAR);
#pragma unroll
                                for (int i = 0; i < 12; i++) asm volatile("mov.b32 %0, 0;" : "=r"(kc[i]));
                            }
                        }
                    });
                    if (e == NP) {
                        mbar_wait(SM_QBAR, 0);
#pragma unroll
                        for (int k = 0; k < 3; k++) lds128(qf + 4 * k, (lane & 7) * 48, SM_QU + k * 16);
                        static_for<0, NP>([&](auto E) {
                            uint4 r[6];
#pragma unroll
                            for (int i = 0; i < 6; i++) { const uint32_t* k = kc + 90 + 24 * E.value + 4 * i; r[i] = make_uint4(k[0], k[1], k[2], k[3]); }
                            stsf(sca, SM_PART + 256 + (E.value + 6) * 4, score6(r, qf));
                        });
#pragma unroll
                        for (int i = 0; i < 24; i++) asm volatile("mov.b32 %0, 0;" : "=r"(kc[i]));
                    } else if (e == 5) {
#pragma unroll
                        for (int k = 0; k < 22; k++) lds128(kc + 4 * k, ksl, SM_KS + k * 512);
                        lds64(kc + 88, ksl, SM_KS + 22 * 512);
                        n0 = 0;
                    } else if (e == 10) {
#pragma unroll
                        for (int k = 0; k < 22; k++)
                            asm volatile("ld.shared.v4.b32 {%0,%1,%2,%3}, [%4];" : "=r"(kc[90 + 4 * k]), "=r"(kc[91 + 4 * k]), "=r"(kc[92 + 4 * k]), "=r"(kc[93 + 4 * k]) : "r"(ad(ksl, SM_KS + k * 512)) : "memory");
                        asm volatile("ld.shared.v2.b32 {%0,%1}, [%2];" : "=r"(kc[178]), "=r"(kc[179]) : "r"(ad(ksl, SM_KS + 22 * 512)) : "memory");
                        n0 = 0;
                    } else if (e == 11) {
                        lds64(kc + 180, ksl, SM_KS + 520); lds128(kc + 182, ksl, SM_KS + 1024); lds128(kc + 186, ksl, SM_KS + 1536); lds64(kc + 190, ksl, SM_KS + 2048);
                        n0 = 3;
                    }
                }
                const int n = (e + 6) & 15;
                stsf(ad(sca, n * 4), SM_PART + 256, score6(v, qf));
                uint32_t m = bf2_amax(bf2_amax(v[0].x, v[0].y), bf2_amax(v[0].z, v[0].w)), mn = bf2_amin(bf2_amin(v[0].x, v[0].y), bf2_amin(v[0].z, v[0].w));
#pragma unroll
                for (int i = 1; i < 6; i++) m = bf2_amax(m, bf2_amax(bf2_amax(v[i].x, v[i].y), bf2_amax(v[i].z, v[i].w)));
                m = max(m & 0x7fff, (m >> 16) & 0x7fff);
                m = max(m, __shfl_xor_sync(~0u, m, 1)); m = max(m, __shfl_xor_sync(~0u, m, 2));
#pragma unroll
                for (int i = 1; i < 6; i++) mn = bf2_amin(mn, bf2_amin(bf2_amin(v[i].x, v[i].y), bf2_amin(v[i].z, v[i].w)));
                mn = min(mn & 0x7fff, (mn >> 16) & 0x7fff);
                const int sh = min(max((int)(m >> 7) - 15, 0), 126);
                asm volatile("st.shared.u8 [%0], %1;" :: "r"(ad(ad((tid >> 2) * 16, n), SM_SH)), "r"(sh) : "memory");
                const uint32_t dn = (127 - sh) * 0x00800080u;
                if (__any_sync(~0u, (int)(mn >> 7) <= sh || m >= (142 << 7))) {
                    if (m >= (142 << 7)) sts32(0, SM_BIG, 1);
                    const uint32_t up = (127 + 256 + sh) * 0x00800080u;
#pragma unroll
                    for (int i = 0; i < 6; i++) {
                        const uint32_t r0 = bf2_fma(bf2_mul(v[i].x, dn), up, v[i].x), r1 = bf2_fma(bf2_mul(v[i].y, dn), up, v[i].y);
                        const uint32_t r2 = bf2_fma(bf2_mul(v[i].z, dn), up, v[i].z), r3 = bf2_fma(bf2_mul(v[i].w, dn), up, v[i].w);
                        asm volatile("{\n.reg .pred p;\n.reg .u32 x, a;\nsetp.ne.u32 p, %0, 0;\nmov.u32 x, %7;\n@p atom.relaxed.cta.shared.inc.u32 x, [%6], 0x7fffffff;\n"
                                     "setp.lt.u32 p, x, %7;\nmad.lo.u32 a, x, 16, %8;\n@p st.shared.v4.u32 [a], {%1,%2,%3,%4};\n"
                                     "mad.lo.u32 a, x, 4, %9;\n@p st.shared.u32 [a], %5;\n}"
                                     :: "r"(r0 | r1 | r2 | r3), "r"(r0), "r"(r1), "r"(r2), "r"(r3), "r"(tid << 16 | n << 8 | i * 8), "r"(SM_XN), "n"(XCAP), "n"(SM_XR), "n"(SM_XM) : "memory");
                    }
                }
                const uint32_t ae = (n0 >> 1) * 512 + (n0 & 1) * 8, ao = ((n0 + 1) >> 1) * 512 + (~n0 & 1) * 8;
                uint32_t o[18];
#pragma unroll
                for (int i = 0; i < 6; i++) {
                    const uint32_t y0 = bf2_mulv(v[i].x, dn), y1 = bf2_mulv(v[i].y, dn), y2 = bf2_mulv(v[i].z, dn), y3 = bf2_mulv(v[i].w, dn);
                    o[3 * i] = __byte_perm(y0, y1, 0x6420); o[3 * i + 1] = __byte_perm(y2, y3, 0x6420);
                    const uint32_t hb = __byte_perm(y2, y3, 0x7531);
                    o[3 * i + 2] = __byte_perm(y0, y1, 0x7531) | __funnelshift_l(hb, hb, 4);
                    if (i & 1) {
#pragma unroll
                        for (int k = 3 * (i >> 1); k < 3 * (i >> 1) + 3; k++) sts64(ad(ksl, (k & 1) ? ao : ae), SM_KS + (k >> 1) * 512, o[2 * k], o[2 * k + 1]);
                    }
                }
                n0 += 9;
            }
            fence_async();
        }
        TS(2);
        refresh();
        {
            const uint4 sc = lds128(prow + lane * 16, SM_PART + 256);
            const float S[4] = {__uint_as_float(sc.x), __uint_as_float(sc.y), __uint_as_float(sc.z), __uint_as_float(sc.w)};
            softmax(IC<0>{}, S);
        }
        fw = 0.f;
#pragma unroll 1
        for (int e = 0; e < 16; e++) {
            if ((1 << (PUBAT - 3) | 1 << PUBAT | 1 << ZCHK) >> e & 1) {
                if (e == PUBAT - 3) head_look(IC<0>{});
                else if (e == PUBAT) {
                    head_weight(IC<0>{});
                    if (tid < 196) st_rlx(&g_ll[cta][tid + (tid >> 6 == 3) * 4], 0ull);
                } else if (warp == 7) {
#pragma unroll 1
                    for (int k = 0; k < SPIN; k++) {
                        uint32_t v; asm volatile("ld.acquire.gpu.global.u32 %0, [%1];" : "=r"(v) : "l"(&g_zflag) : "memory");
                        if (__all_sync(~0u, v * 4 == ep4 + 4)) break;
                    }
                }
                __syncwarp();
            }
            const uint32_t pp = lds32(ad(t * 4, prow + ((e + 6) & 15) * 16), SM_PART + 256);
            TR(3, 1 + 2 * e);
            mbar_wait(SM_CBAR + bar * 8, par);
            TR(3, 2 + 2 * e);
            uint4 v[6];
            load_v(v, (warp & 3) * SUB + slot * HT, SM_RING);
            if (e < 15) refill(false);
            advance();
            pv(v, pp);
        }
    }
    TS(3);
    tail_prep1(IC<0>{});
    __syncwarp();
    tail(IC<0>{});

    q_stage(IC<1>{});
    {
        const u64* qp = &g_ll[cta & ~3][tid];
        u64 w[4] = {0, 0, 0, 0};
        while (clk() - cq < QDELAY);
        if (warp < 6) { w[0] = ld_rlx(qp); w[1] = ld_rlx(qp + 256); w[2] = ld_rlx(qp + 512); w[3] = ld_rlx(qp + 768); }
        if (LNLATE) { ln_part(); __syncthreads(); sts64(prow + lane * 8, SM_PART, xp.x, xp.y); }
        const uint32_t ksl = ksw + lane * 16, qa = pin(q_addr()), qb0 = pin(lane < 8 ? lane * 48 : SM_ZQ - SM_VEC);
        uint32_t ks[96], qf[12];
        float mean, rstd, msq;
        ln_final(mean, rstd, msq);
        const float qc = pinf(-mean * rstd * ldsf(tid * 4, SM_CS));
#pragma unroll
        for (int k = 0; k < PRE; k++) lds128(ks + 4 * k, ksl, SM_KS + k * 512);
        stsf(0, SM_FXS, fx_scale(msq));
        if (warp < 6) {
            ll_gather4(qp, 2 * ep4 + 5, w);
            const float q = ((hif(w[0]) + hif(w[1])) + (hif(w[2]) + hif(w[3]))) * rstd + qc;
            TS(24);
            const uint32_t qq = bf2_mul(pack_bf(q, q), 0x3f807180u);
            sts16(qa, SM_VEC, qq); sts16(qa, SM_QU, qq >> 16);
            sts32_if(!(fabsf(q) < 1048576.f), 0, SM_BIG, 1);
            __syncwarp();
            if (elect()) mbar_arrive(SM_QBAR);
        } else {
            float c[4] = {0.f, 0.f, 0.f, 0.f};
            if (cta == 0 && tid == 255) g_epoch = (ep4 >> 2) + 1;
            if (I1D) { tick(c); while (clk() - cq < I1D + (warp - 6) * I1G); issue_item1(); }
#pragma unroll 1
            for (int it = 0; it < SPIN; it++) { if (mbar_test(SM_QBAR, 1)) break; if (KA & 1) tick(c); }
            tick_done(c);
        }
        if constexpr (!E3) issue2(IC<3>{}, ks[0] | ks[4] | ks[8] | ks[12] | ks[16] | ks[20]);
        mbar_wait(SM_QBAR, 1);
        TS(12); TR(4, 1); TR(5, 1);
        auto load_q = [&](int u, int k) { lds128(qf + 4 * k, u == 0 ? qb0 : (lane >> 3) == u ? lane * 48 : SM_ZQ - SM_VEC + u * 384, SM_VEC - u * 384 + k * 16); };
        load_q(0, 1); load_q(0, 2); load_q(0, 0);
        if constexpr (E3) issue2(IC<3>{}, ks[0] | ks[4] | ks[8] | ks[12] | ks[16] | ks[20]);
        float D[4][4];
        uint4 vb[NPK + 2][6];
        uint32_t xn;
        auto step = [&](auto Q) {
            constexpr int st = Q.value, p = cord(st), s = PL.slot[p];
            TR(4, 2 + 2 * st);
            if (p == 1) mbar_wait(SM_CBAR + (warp >> 2) * 8, 1);
            else if (p == 0 || p == 2) mbar_wait(warp < 4 ? SM_CBAR + 24 - p * 4 : barw + s * 8, warp < 4);
            else mbar_wait(barw + s * 8, IC<PL.par[p]>::value);
            TR(4, 3 + 2 * st);
            uint4 (&v)[6] = vb[st < NPK ? st : NPK + (st & 1)];
            load_v(v, slot_u(s), slot_o(s));
            static_for<0, PL.nld[st]>([&](auto K) { issue2(IC<PL.ld[st][K.value]>{}, v[0].x | v[1].x | v[2].x | v[3].x | v[4].x | v[5].x); });
        };
        static_for<0, 96>([&](auto I) {
            constexpr int F = I.value, n = F / 6, i = n ? F % 6 : (F + 2) % 6;
            const uint32_t* c = n == 0 ? (i < 2 ? ks + 3 * i : kc + 174 + 3 * i) : n < 6 ? ks + 18 * n - 12 + 3 * i : kc + 18 * (n - 6) + 3 * i;
            const uint32_t ha = c[2] & 0x87878787u, hb = __funnelshift_r(c[2], c[2], 4) & 0x87878787u;
            if (F < 24 && F % 6 == 0) zero4(D[n]);
            mma(D[n & 3], __byte_perm(c[0], ha, 0x5140), __byte_perm(c[0], ha, 0x7362), __byte_perm(c[1], hb, 0x5140), __byte_perm(c[1], hb, 0x7362), qf[2 * i], qf[2 * i + 1]);
            if constexpr ((n & 3) == 3 && n < 15 && (i & 1)) load_q((n + 1) >> 2, i >> 1);
            static_for<PRE, 24>([&](auto U) {
                if constexpr (((U.value - PRE + 1) * 4 + 2) / 3 - 1 + KSL == F) {
                    lds128(ks + 4 * U.value, ksl, SM_KS + U.value * 512);
                    if constexpr (U.value % 6 == 5) { const uint32_t* k = ks + 4 * U.value - 17; issue2(IC<3 + U.value / 6>{}, k[0] | k[4] | k[8] | k[12] | k[16] | k[20]); }
                }
            });
            if constexpr (F == XAT) {
                                { const uint2 x = lds64(0, SM_XN); xn = x.y ? XCAP + 1 : x.x; }
                sts128(prow + lane * 16, SM_PART + 256, 0, 0, 0, 0);
                __syncwarp();
#pragma unroll 1
                for (uint32_t idx = lane; idx < (xn > XCAP ? 0 : xn); idx += 32) {
                    const uint32_t m = lds32(idx * 4, SM_XM);
                    if ((m >> 21) == warp) {
                        const uint4 r = lds128(idx * 16, SM_XR);
                        const uint32_t qo = ((m >> 16) & 3) * 48 + (m & 255);
                        const uint2 a = lds64(qo, SM_QU), b = lds64(qo, SM_QU + 192);
                        const float s = ((bf_lo(r.x) * bf_lo(a.x) + bf_hi(r.x) * bf_hi(a.x)) + (bf_lo(r.y) * bf_lo(b.x) + bf_hi(r.y) * bf_hi(b.x))) +
                                        ((bf_lo(r.z) * bf_lo(a.y) + bf_hi(r.z) * bf_hi(a.y)) + (bf_lo(r.w) * bf_lo(b.y) + bf_hi(r.w) * bf_hi(b.y)));
                        asm volatile("red.relaxed.cta.shared.add.f32 [%0], %1;" :: "r"(SM_PART + 256 + prow + ((m >> 18) & 7) * 64 + ((m >> 8) & 15) * 4), "f"(s) : "memory");
                    }
                }
                __syncwarp();
            }
            if constexpr (F == PK0 - 2) refresh();
            static_for<0, NPK>([&](auto Q) { if constexpr (F == PK0 + Q.value * PKD) step(Q); });
        });
        float S[4];
        {
            const uint32_t shp = lds32(tid * 4, SM_SH);
            const uint4 cr = lds128(prow + lane * 16, SM_PART + 256);
            const uint32_t c[4] = {cr.x, cr.y, cr.z, cr.w};
#pragma unroll
            for (int j = 0; j < 4; j++) S[j] = (D[j][0] + D[j][3]) * __uint_as_float((((shp >> (8 * j)) & 255) + 27) << 23) + __uint_as_float(c[j]);
        }
        if (xn > XCAP) {
#pragma unroll
            for (int k = 0; k < 3; k++) lds128(qf + 4 * k, (lane & 7) * 48, SM_QU + k * 16);
#pragma unroll 1
            for (int e = 0; e < 16; e++) {
                uint4 v[6];
#pragma unroll
                for (int i = 0; i < 6; i++) v[i] = ldg128(P.k + (size_t)(roww + 256 * e + g) * DH + (i >> 1) * 64 + (2 * t + (i & 1)) * 8);
                const float s = score6(v, qf);
#pragma unroll
                for (int j = 0; j < 4; j++) if (4 * t + j == ((e + 6) & 15)) S[j] = s;
            }
        }
        TS(25);
        softmax(IC<1>{}, S);
        auto p_of = [&](int st) { return lds32(ad(t * 4, prow), SM_PART + 256 + ((vunit(cord(st)) + 6) & 15) * 16); };
        auto pv_at = [&](auto Q) { constexpr int st = Q.value; pv(vb[st < NPK ? st : NPK + (st & 1)], p_of(st)); };
        static_for<NPK, 16>([&](auto Q) {
            constexpr int st = Q.value;
            if constexpr (st == HWAT) head_look(IC<1>{});
            if constexpr (st == B2AT) asm volatile("cp.async.ca.shared.global [%0], [%1], 8;" :: "r"(SM_KS + 11264 + ksw + lane * 8), "l"(P.b2 + 4 * min(c4, 159)) : "memory");
            if constexpr (st == HWC) { head_weight(IC<1>{}); b2v = lds64(ksw + lane * 8, SM_KS + 11264); }
            if constexpr (st == PREP1) { tail_prep1(IC<1>{}); tail_prep2(IC<1>{}); red_addr(IC<1>{}); load_u(z, warp * WOU, SM_RING + 16 * WOU); }
            if constexpr (st == PREP2) mlp_prep(IC<1>{});
            uint32_t pp;
            if constexpr (st >= PVNOW) pp = pin(p_of(st));
            step(Q);
            if constexpr (st - NPK < NPK) pv_at(IC<st - NPK>{});
            if constexpr (st > NPK && st <= PVNOW) pv_at(IC<st - 1>{});
            if constexpr (st >= PVNOW) pv(vb[NPK + (st & 1)], pp);
        });
    }
    TS(13);
    tail(IC<1>{});
}

typedef CUresult (*EncodeFn)(CUtensorMap*, CUtensorMapDataType, cuuint32_t, void*, const cuuint64_t*, const cuuint64_t*, const cuuint32_t*,
                             const cuuint32_t*, CUtensorMapInterleave, CUtensorMapSwizzle, CUtensorMapL2promotion, CUtensorMapFloatOOBfill);

}

extern "C" void kernel_launch(void* const* d_in, const int* in_sizes, int n_in, void* d_out, int out_size) {
    (void)in_sizes; (void)n_in; (void)out_size;
    static EncodeFn enc = nullptr;
    if (!enc) {
        void* fn = nullptr;
        cudaDriverEntryPointQueryResult qr;
        cudaGetDriverEntryPoint("cuTensorMapEncodeTiled", &fn, cudaEnableDefault, &qr);
        enc = (EncodeFn)fn;
        cudaFuncSetAttribute(fused_kernel, cudaFuncAttributeMaxDynamicSharedMemorySize, SM_TOTAL);
    }
    Params P;
    const cuuint32_t ones[3] = {1, 1, 1};
    for (int m = TM_K; m <= TM_V8; m++) {
        const cuuint64_t dim[3] = {64, 3, (cuuint64_t)NHEAD * SK}, str[2] = {128, DH * 2};
        const cuuint32_t box[3] = {m == TM_VP ? 8u : 64u, 3, m == TM_V8 ? 8u : 32u};
        enc(&P.tm[m], CU_TENSOR_MAP_DATA_TYPE_BFLOAT16, 3, d_in[m == TM_K ? 1 : 2], dim, str, box, ones, CU_TENSOR_MAP_INTERLEAVE_NONE,
            m == TM_VP ? CU_TENSOR_MAP_SWIZZLE_NONE : CU_TENSOR_MAP_SWIZZLE_128B, CU_TENSOR_MAP_L2_PROMOTION_NONE, CU_TENSOR_MAP_FLOAT_OOB_FILL_NONE);
    }
    {
        const cuuint64_t dim[3] = {64, NHEAD * 3, D_MODEL}, str[2] = {128, NHEAD * DH * 2};
        const cuuint32_t box[3] = {64, 3, 32};
        enc(&P.tm[TM_WQ], CU_TENSOR_MAP_DATA_TYPE_BFLOAT16, 3, d_in[3], dim, str, box, ones, CU_TENSOR_MAP_INTERLEAVE_NONE,
            CU_TENSOR_MAP_SWIZZLE_128B, CU_TENSOR_MAP_L2_PROMOTION_NONE, CU_TENSOR_MAP_FLOAT_OOB_FILL_NONE);
    }
    {
        const cuuint64_t dim[2] = {DFF, D_MODEL}, str[1] = {DFF * 2};
        const cuuint32_t box[2] = {16, 128};
        enc(&P.tm[TM_W1], CU_TENSOR_MAP_DATA_TYPE_BFLOAT16, 2, d_in[6], dim, str, box, ones, CU_TENSOR_MAP_INTERLEAVE_NONE,
            CU_TENSOR_MAP_SWIZZLE_32B, (CUtensorMapL2promotion)W1PROMO, CU_TENSOR_MAP_FLOAT_OOB_FILL_NONE);
    }
    {
        const cuuint64_t dim[3] = {32, 20, NHEAD * DH}, str[2] = {64, D_MODEL * 2};
        const cuuint32_t box[3] = {32, 5, 16};
        enc(&P.tm[TM_WO], CU_TENSOR_MAP_DATA_TYPE_BFLOAT16, 3, d_in[4], dim, str, box, ones, CU_TENSOR_MAP_INTERLEAVE_NONE,
            CU_TENSOR_MAP_SWIZZLE_64B, CU_TENSOR_MAP_L2_PROMOTION_L2_128B, CU_TENSOR_MAP_FLOAT_OOB_FILL_NONE);
    }
    {
        const cuuint64_t dim[4] = {32, 20, 24, NHEAD * 8}, str[3] = {64, D_MODEL * 2, 24 * D_MODEL * 2};
        const cuuint32_t box[4] = {32, 5, 8, 4}, ones4[4] = {1, 1, 1, 1};
        enc(&P.tm[TM_WO4], CU_TENSOR_MAP_DATA_TYPE_BFLOAT16, 4, d_in[4], dim, str, box, ones4, CU_TENSOR_MAP_INTERLEAVE_NONE,
            CU_TENSOR_MAP_SWIZZLE_64B, (CUtensorMapL2promotion)WOPROMO, CU_TENSOR_MAP_FLOAT_OOB_FILL_NONE);
        const cuuint32_t thin[4] = {8, 5, 8, 4};
        enc(&P.tm[TM_WOP], CU_TENSOR_MAP_DATA_TYPE_BFLOAT16, 4, d_in[4], dim, str, thin, ones4, CU_TENSOR_MAP_INTERLEAVE_NONE,
            CU_TENSOR_MAP_SWIZZLE_NONE, CU_TENSOR_MAP_L2_PROMOTION_NONE, CU_TENSOR_MAP_FLOAT_OOB_FILL_NONE);
    }
    {
        const cuuint64_t dim[3] = {64, 10, DFF}, str[2] = {128, D_MODEL * 2};
        const cuuint32_t box[3] = {64, 10, 16};
        enc(&P.tm[TM_W2], CU_TENSOR_MAP_DATA_TYPE_BFLOAT16, 3, d_in[8], dim, str, box, ones, CU_TENSOR_MAP_INTERLEAVE_NONE,
            CU_TENSOR_MAP_SWIZZLE_128B, CU_TENSOR_MAP_L2_PROMOTION_NONE, CU_TENSOR_MAP_FLOAT_OOB_FILL_NONE);
    }
    P.x = (const __nv_bfloat16*)d_in[0];
    P.k = (const __nv_bfloat16*)d_in[1];
    P.b1 = (const __nv_bfloat16*)d_in[7];
    P.b2 = (const __nv_bfloat16*)d_in[9];
    P.out = (__nv_bfloat16*)d_out;
    fused_kernel<<<NCTA + 1 + NXTRA, NTHR, SM_TOTAL, cudaStreamPerThread>>>(P);
}
```

```cpp
#include <cuda_runtime.h>
#include <cuda_bf16.h>
#include <cuda.h>
#include <stdint.h>

namespace {

constexpr int D_MODEL = 640, NHEAD = 32, SK = 32768, DH = 192, WIN = 4096, DFF = 1536;
constexpr int NCTA = 128, NTHR = 256;
constexpr int SUB = 8 * DH * 2;
constexpr int HT = 4 * SUB;
constexpr int WOU = 8 * 320;
constexpr int XCAP = 48;
constexpr int SM_RING = 1024;
constexpr int SM_W2 = SM_RING + 8 * WOU;
constexpr int SM_WQ = SM_RING + 5 * HT;
constexpr int SM_KS = SM_WQ + 5 * HT;
constexpr int SM_PART = SM_KS + 8 * HT;
constexpr int SM_BAR = SM_PART + 6144;
constexpr int SM_VEC = SM_BAR + 512;
constexpr int SM_QU = SM_VEC + 384;
constexpr int SM_ZQ = SM_QU + 384;
constexpr int SM_CS = SM_ZQ + 64;
constexpr int SM_XR = SM_CS + 768;
constexpr int SM_XM = SM_XR + XCAP * 16;
constexpr int SM_SH = SM_XM + XCAP * 4;
constexpr int SM_C1 = SM_SH + 1024;
constexpr int SM_ML = SM_C1 + 320;
constexpr int SM_B1 = SM_ML + 64;
constexpr int SM_STAT = SM_B1 + 128;
constexpr int SM_QBAR = SM_STAT + 40;
constexpr int SM_CBAR = SM_QBAR + 8;
constexpr int SM_CNT = SM_CBAR + 128;
constexpr int SM_XN = SM_CNT + 56;
constexpr int SM_BIG = SM_XN + 4;
constexpr int SM_EPOCH = SM_BIG + 4;
constexpr int SM_FXS = SM_EPOCH + 4;
constexpr int SM_T0 = SM_FXS + 4;
constexpr int SM_JUNK = SM_T0 + 4;
constexpr int SM_TS = SM_JUNK + 4;
constexpr int SM_TOTAL = 232448;
static_assert(SM_TS + 160 <= SM_RING + SM_TOTAL, "smem");

constexpr int SPIN = 1 << 20;
enum { TM_WQ = 0, TM_K = 1, TM_V = 2, TM_VP = 3, TM_V8 = 4, TM_WO = 5, TM_W1 = 6, TM_WO4 = 7, TM_W2 = 8, TM_WOP = 9 };
constexpr uint32_t POL_NORMAL = 0x16F00000u, POL_FIRST = 0x12F00000u;

#define PACE 484
#define PACE0 1800
#define KEEP0 32
#define NP 3
#define VORD 0x45678932a1b0cdefull
#define CORD 0xfedcba987654310ull
#define ISS 0x4f9e
#define X2AT 9
#define R56 13
#define PRE 6
#define KSL 0
#define PK0 34
#define PK1 52
#define P2A -700
#define P2B 400
#define P2W 0
#define PKD 21
#define NPK 4
#define XAT 94
#define LEAD 4
#define ARDELAY 600
#define QDELAY 300
#define PUBAT 8
#define ZCHK 14
#define S6D 900
#define S6G 100
#define XD 600
#define XG 200
#define TB 2
#define WOPACE 403
#define WOD 0
#define NPF0 0
#define HWAT 10
#define HWC 13
#define ODELAY1 600
#define ODELAY2 200
#define W1P 9999
#define W2P 600
#define W2LATE 0
#define NOW12 0
#define W1PROMO 2
#define W1FIRST 1
#define WOPROMO 2
#define NPFC 4
#define PFD 1200
#define PFG 150
#define PFPOL POL_NORMAL
#define E3 0
#define SKIP 0
#define W1G 150
#define KA 31
#define KAD 600
#define KAD2 900
#define PVNOW 12
#define I0D 300
#define I0G 0
#define I2D 0
#define I2G 0
#define FX2_MASK 0xfff00000u
#define LNLATE 0
#define AR1D 400
#define I0LATE 0
#define I1D 0
#define I1G 0
#define WFIRST 1
#define PREP1 8
#define PREP2 9
#define HZD 9500
#define B2AT 12
#define AR1DN 1000
#define ARDN 600
#define TOUCH 1
#define I2AT 94
#define PV2 9
#define XAT2 94
#define I6AT 0
#define EW1 0
#define S1D 1500
#define E3W 4
#define PREP3 99
#define PREP4 99
#define B2PF 1
#define DEC 1
#define PACEK 0
#define WOLATE 1
#define ZW 7
#define NI0 3
#define W1ST 0
#define W1D 100
#define W1POL POL_FIRST
#define WOKEEP 2
#define WPF2 8
#define WOPF 99
#define QLATE 0
#define W2POL POL_NORMAL
#define FX2LIM 524288.f

struct Plan { int slot[17], par[17], ld[15]; bool ok; };
__host__ __device__ constexpr int cord(int s) { return (int)(CORD >> (4 * s) & 15); }
constexpr Plan make_plan() {
    Plan s{};
    int phase[7] = {}, state[17] = {}, freeat[7] = {}, it = 7;
    for (int p = 0; p < 7; p++) { s.slot[p] = p; phase[p] = p != 1; state[p] = p != 2; freeat[p] = -1; }
    s.ok = true;
    for (int st = 0; st < 15; st++) {
        if (ISS >> st & 1) {
            int best = -1;
            for (int c = 0; c < 7; c++) if (freeat[c] >= 0 && (c < 5 || it < R56) && (best < 0 || freeat[c] < freeat[best])) best = c;
            if (it == 16) best = freeat[5] >= 0 && freeat[6] >= 0 ? 5 : -1;
            if (best < 0 || it > 16) { s.ok = false; return s; }
            s.slot[it] = best; freeat[best] = -1; state[it] = 1;
            s.par[it] = phase[best]++ & 1;
            s.ld[st] = it++;
        }
        const int p = cord(st);
        if (state[p] != 1) s.ok = false;
        state[p] = 2;
        freeat[s.slot[p]] = st;
    }
    if (it != 17) s.ok = false;
    for (int st = B2AT; st < 15; st++) if (s.slot[cord(st)] == 6) s.ok = false;
    return s;
}
constexpr Plan PL = make_plan();
static_assert(PL.ok, "bad pass-2 plan");
__host__ __device__ constexpr int vunit(int p) { return (int)(VORD >> (4 * p) & 15); }

template <int I> struct IC { static constexpr int value = I; };
template <int A, int B, class F> __device__ __forceinline__ void static_for(F&& f) {
    if constexpr (A < B) { f(IC<A>{}); static_for<A + 1, B>(f); }
}

struct Params {
    CUtensorMap tm[10];
    const __nv_bfloat16 *x, *b1, *b2, *k, *v;
    __nv_bfloat16* out;
};

typedef unsigned long long u64;
constexpr int ACC_PITCH = 256;
constexpr int ACC_BYTES = 80 * ACC_PITCH;
__device__ __align__(1024) unsigned char g_acc[4 * ACC_BYTES];
__device__ __align__(8192) u64 g_ll[NCTA][256];
__device__ unsigned g_epoch;
__device__ __align__(128) unsigned g_zflag;
#define NXTRA 0
#define DBG(i, v)
#define TS(i)
#define TSB(i)
#define TSA(i)
#define TR(k, i)

__device__ __forceinline__ void mbar_wait(uint32_t bar, uint32_t parity) {
    asm volatile("{\n.reg .pred p, q;\n.reg .u32 n;\nmov.u32 n, 0;\n"
                 "LOOP:\nmbarrier.try_wait.parity.shared::cta.b64 p, [%0], %1;\n"
                 "add.u32 n, n, 1;\nsetp.lt.and.u32 q, n, 0x100000, !p;\n@q bra.uni LOOP;\n}"
                 :: "r"(bar), "r"(parity) : "memory");
}
__device__ __forceinline__ bool mbar_test(uint32_t bar, uint32_t parity) {
    uint32_t done;
    asm volatile("{\n.reg .pred p;\nmbarrier.test_wait.parity.shared::cta.b64 p, [%1], %2;\nselp.u32 %0, 1, 0, p;\n}" : "=r"(done) : "r"(bar), "r"(parity) : "memory");
    return __any_sync(~0u, done);
}
__device__ __forceinline__ bool elect() {
    uint32_t r;
    asm volatile("{\n.reg .pred p;\nelect.sync _|p, 0xffffffff;\nselp.u32 %0, 1, 0, p;\n}" : "=r"(r));
    return r != 0;
}
__device__ __forceinline__ void mbar_init(uint32_t bar, uint32_t n) { asm volatile("mbarrier.init.shared::cta.b64 [%0], %1;" :: "r"(bar), "r"(n) : "memory"); }
__device__ __forceinline__ void mbar_arrive(uint32_t bar) { asm volatile("mbarrier.arrive.shared::cta.b64 _, [%0];" :: "r"(bar) : "memory"); }
__device__ __forceinline__ void mbar_expect(uint32_t bar, uint32_t bytes) {
    asm volatile("mbarrier.arrive.expect_tx.shared::cta.b64 _, [%0], %1;" :: "r"(bar), "r"(bytes) : "memory");
}
__device__ __forceinline__ void fence_async() { asm volatile("fence.proxy.async.shared::cta;" ::: "memory"); }
#define DI __device__ __forceinline__
DI uint32_t ad(uint32_t a, uint32_t o) { uint32_t r; asm("add.u32 %0, %1, %2;" : "=r"(r) : "r"(a), "r"(o)); return r; }
DI uint4 lds128(uint32_t a, int o) {
    uint4 v; asm volatile("ld.shared.v4.u32 {%0,%1,%2,%3}, [%4];" : "=r"(v.x), "=r"(v.y), "=r"(v.z), "=r"(v.w) : "r"(ad(a, o)) : "memory"); return v;
}
DI void lds128(uint32_t* v, uint32_t a, int o) {
    asm volatile("ld.shared.v4.u32 {%0,%1,%2,%3}, [%4];" : "=r"(v[0]), "=r"(v[1]), "=r"(v[2]), "=r"(v[3]) : "r"(ad(a, o)) : "memory");
}
DI void lds64(uint32_t* v, uint32_t a, int o) { asm volatile("ld.shared.v2.u32 {%0,%1}, [%2];" : "=r"(v[0]), "=r"(v[1]) : "r"(ad(a, o)) : "memory"); }
DI uint4 ldsm_t(uint32_t a, int o) {
    uint4 v; asm volatile("ldmatrix.sync.aligned.m8n8.x4.trans.shared.b16 {%0,%1,%2,%3}, [%4];" : "=r"(v.x), "=r"(v.y), "=r"(v.z), "=r"(v.w) : "r"(ad(a, o)) : "memory"); return v;
}
DI uint2 lds64(uint32_t a, int o) { uint2 v; asm volatile("ld.shared.v2.u32 {%0,%1}, [%2];" : "=r"(v.x), "=r"(v.y) : "r"(ad(a, o)) : "memory"); return v; }
DI float2 lds64f(uint32_t a, int o) { const uint2 v = lds64(a, o); return make_float2(__uint_as_float(v.x), __uint_as_float(v.y)); }
DI uint32_t lds32(uint32_t a, int o) { uint32_t v; asm volatile("ld.shared.u32 %0, [%1];" : "=r"(v) : "r"(ad(a, o)) : "memory"); return v; }
DI float ldsf(uint32_t a, int o) { return __uint_as_float(lds32(a, o)); }
DI void sts32(uint32_t a, int o, uint32_t v) { asm volatile("st.shared.u32 [%0], %1;" :: "r"(ad(a, o)), "r"(v) : "memory"); }
DI void stsf(uint32_t a, int o, float v) { sts32(a, o, __float_as_uint(v)); }
DI void sts16(uint32_t a, int o, uint32_t v) { asm volatile("st.shared.u16 [%0], %1;" :: "r"(ad(a, o)), "h"((uint16_t)v) : "memory"); }
DI void sts64(uint32_t a, int o, uint32_t x, uint32_t y) { asm volatile("st.shared.v2.u32 [%0], {%1,%2};" :: "r"(ad(a, o)), "r"(x), "r"(y) : "memory"); }
DI void sts64f(uint32_t a, int o, float x, float y) { sts64(a, o, __float_as_uint(x), __float_as_uint(y)); }
DI void sts128(uint32_t a, int o, uint32_t x, uint32_t y, uint32_t z, uint32_t w) {
    asm volatile("st.shared.v4.u32 [%0], {%1,%2,%3,%4};" :: "r"(ad(a, o)), "r"(x), "r"(y), "r"(z), "r"(w) : "memory");
}
DI void sts128f(uint32_t a, int o, const float (&v)[4]) {
    asm volatile("st.shared.v4.f32 [%0], {%1,%2,%3,%4};" :: "r"(ad(a, o)), "f"(v[0]), "f"(v[1]), "f"(v[2]), "f"(v[3]) : "memory");
}
DI void sts128f_if(bool p, uint32_t a, int o, float x, float y, float z, float w) {
    asm volatile("{\n.reg .pred p;\nsetp.ne.u32 p, %5, 0;\n@p st.shared.v4.f32 [%0], {%1,%2,%3,%4};\n}" :: "r"(ad(a, o)), "f"(x), "f"(y), "f"(z), "f"(w), "r"((int)p) : "memory");
}
DI void sts32_if(bool p, uint32_t a, int o, uint32_t v) {
    asm volatile("{\n.reg .pred p;\nsetp.ne.u32 p, %2, 0;\n@p st.shared.u32 [%0], %1;\n}" :: "r"(ad(a, o)), "r"(v), "r"((int)p) : "memory");
}
__device__ __forceinline__ uint32_t atoms_inc(uint32_t a, uint32_t lim) {
    uint32_t old; asm volatile("atom.relaxed.cta.shared.inc.u32 %0, [%1], %2;" : "=r"(old) : "r"(a), "r"(lim) : "memory"); return old;
}
__device__ __forceinline__ void mma(float (&c)[4], uint32_t a0, uint32_t a1, uint32_t a2, uint32_t a3, uint32_t b0, uint32_t b1) {
    asm volatile("mma.sync.aligned.m16n8k16.row.col.f32.bf16.bf16.f32 {%0,%1,%2,%3}, {%4,%5,%6,%7}, {%8,%9}, {%0,%1,%2,%3};"
                 : "+f"(c[0]), "+f"(c[1]), "+f"(c[2]), "+f"(c[3]) : "r"(a0), "r"(a1), "r"(a2), "r"(a3), "r"(b0), "r"(b1));
}
__device__ __forceinline__ void mma(float (&c)[4], const uint4& a, uint32_t b0, uint32_t b1) { mma(c, a.x, a.y, a.z, a.w, b0, b1); }
__device__ __forceinline__ void zero4(float (&c)[4]) { c[0] = c[1] = c[2] = c[3] = 0.f; }
__device__ __forceinline__ u64 ld_rlx(const void* p) {
    u64 a; asm volatile("ld.relaxed.gpu.global.u64 %0, [%1];" : "=l"(a) : "l"(p) : "memory"); return a;
}
__device__ __forceinline__ void ld_rlx2(const void* p, u64& a, u64& b) {
    asm volatile("ld.relaxed.gpu.global.v2.u64 {%0,%1}, [%2];" : "=l"(a), "=l"(b) : "l"(p) : "memory");
}
__device__ __forceinline__ void st_rlx(void* p, u64 a) { asm volatile("st.relaxed.gpu.global.u64 [%0], %1;" :: "l"(p), "l"(a) : "memory"); }
__device__ __forceinline__ uint4 ldg128(const void* p) {
    uint4 v; asm volatile("ld.global.nc.L1::no_allocate.L2::cache_hint.v4.u32 {%0,%1,%2,%3}, [%4], %5;" : "=r"(v.x), "=r"(v.y), "=r"(v.z), "=r"(v.w) : "l"(p), "l"((u64)POL_FIRST << 32)); return v;
}
__device__ __forceinline__ float bf_lo(uint32_t u) { return __uint_as_float(u << 16); }
__device__ __forceinline__ float bf_hi(uint32_t u) { return __uint_as_float(u & 0xffff0000u); }
__device__ __forceinline__ uint32_t pack_bf(float lo, float hi) {
    uint32_t r; asm("cvt.rn.bf16x2.f32 %0, %1, %2;" : "=r"(r) : "f"(hi), "f"(lo)); return r;
}
__device__ __forceinline__ uint32_t pick(uint32_t a, uint32_t sel) { uint32_t r; asm("prmt.b32 %0, %1, 0, %2;" : "=r"(r) : "r"(a), "r"(sel)); return r; }
__device__ __forceinline__ uint32_t bf2_amax(uint32_t a, uint32_t b) { uint32_t r; asm("max.NaN.xorsign.abs.bf16x2 %0, %1, %2;" : "=r"(r) : "r"(a), "r"(b)); return r; }
__device__ __forceinline__ uint32_t bf2_amin(uint32_t a, uint32_t b) { uint32_t r; asm("min.xorsign.abs.bf16x2 %0, %1, %2;" : "=r"(r) : "r"(a), "r"(b)); return r; }
__device__ __forceinline__ uint32_t bf2_mulv(uint32_t a, uint32_t b) { uint32_t r; asm volatile("mul.rn.bf16x2 %0, %2, %1;" : "=r"(r) : "r"(a), "r"(b)); return r; }
__device__ __forceinline__ uint32_t bf2_mul(uint32_t a, uint32_t b) { uint32_t r; asm("mul.rn.bf16x2 %0, %1, %2;" : "=r"(r) : "r"(a), "r"(b)); return r; }
__device__ __forceinline__ uint32_t bf2_fma(uint32_t a, uint32_t b, uint32_t c) { uint32_t r; asm("fma.rn.bf16x2 %0, %1, %2, %3;" : "=r"(r) : "r"(a), "r"(b), "r"(c)); return r; }
__device__ __forceinline__ float ex2(float v) { float r; asm("ex2.approx.ftz.f32 %0, %1;" : "=f"(r) : "f"(v)); return r; }
__device__ __forceinline__ float rcp(float v) { float r; asm("rcp.approx.ftz.f32 %0, %1;" : "=f"(r) : "f"(v)); return r; }
__device__ __forceinline__ float rsq(float v) { float r; asm("rsqrt.approx.ftz.f32 %0, %1;" : "=f"(r) : "f"(v)); return r; }
__device__ __forceinline__ void bar_sync(int id, int n) { asm volatile("bar.sync %0, %1;" :: "r"(id), "r"(n) : "memory"); }
__device__ __forceinline__ uint32_t clk() { uint32_t c; asm volatile("mov.u32 %0, %clock;" : "=r"(c)); return c; }
__device__ __forceinline__ uint32_t gtime() { uint32_t c; asm volatile("mov.u32 %0, %globaltimer_lo;" : "=r"(c)); return c; }
__device__ __forceinline__ void spin(uint32_t cycles) { const uint32_t c0 = clk(); while (clk() - c0 < cycles); }
__device__ __forceinline__ uint32_t pin(uint32_t v) { return __shfl_xor_sync(~0u, v, 0); }
__device__ __forceinline__ uint32_t pin(uint32_t v, uint32_t dep) {
    uint32_t r; asm volatile("{\n.reg .u32 b;\nshl.b32 b, %2, 5;\nshfl.sync.bfly.b32 %0, %1, b, 31, 0xffffffff;\n}" : "=r"(r) : "r"(v), "r"(dep)); return r;
}
__device__ __forceinline__ float pinf(float v) { return __shfl_xor_sync(~0u, v, 0); }
template <class T> __device__ __forceinline__ T* pinp(T* p) { return reinterpret_cast<T*>(__shfl_xor_sync(~0u, (u64)p, 0)); }
__device__ __forceinline__ u64 mk64(uint32_t lo, uint32_t hi) { u64 r; asm("mov.b64 %0, {%1, %2};" : "=l"(r) : "r"(lo), "r"(hi)); return r; }
__device__ __forceinline__ float uni(float v) { return __shfl_sync(~0u, v, 0); }
__device__ __forceinline__ float shx(float v, int o) { return __shfl_xor_sync(~0u, v, o); }

__device__ __forceinline__ u64 fx_pack(float v) {
    u64 r; asm("{\n.reg .u32 a, b;\n.reg .s64 w;\ncvt.rni.s64.f32 w, %1;\nmov.b64 {a, b}, w;\nprmt.b32 a, a, 1, 0x3214;\nmov.b64 %0, {a, b};\n}" : "=l"(r) : "f"(v)); return r;
}
__device__ __forceinline__ float fx_scale(float meansq) {
    const int e = max(((int)(__float_as_uint(meansq) >> 23) - 127) >> 1, -6);
    return __uint_as_float((uint32_t)(127 + 32 - e) << 23);
}
__device__ __forceinline__ float fx_inv(float scale) { return __uint_as_float((254u << 23) - __float_as_uint(scale)); }
__device__ __forceinline__ uint32_t lo32(u64 w) { uint32_t l; asm("mov.b64 {%0, _}, %1;" : "=r"(l) : "l"(w)); return l; }
__device__ __forceinline__ int hi32(u64 w) { int h; asm("mov.b64 {_, %0}, %1;" : "=r"(h) : "l"(w)); return h; }
__device__ __forceinline__ float fx_val(u64 w) { return (float)hi32(w) * 4294967296.f + (float)lo32(w); }
__device__ __forceinline__ void fx_poll(const unsigned char* ap, u64 (&w)[4]) {
    asm volatile("{\n.reg .pred p, q;\n.reg .u32 n, a, b, c, d;\nmov.u32 n, 0;\nLOOP:\n"
                 "ld.relaxed.gpu.global.u64 %0, [%4];\nld.relaxed.gpu.global.u64 %1, [%4+5120];\n"
                 "ld.relaxed.gpu.global.u64 %2, [%4+10240];\nld.relaxed.gpu.global.u64 %3, [%4+15360];\n"
                 "add.u32 n, n, 1;\nsetp.ge.u32 q, n, 0x100000;\n@q bra.uni DONE;\n"
                 "mov.b64 {a, _}, %0;\nmov.b64 {b, _}, %1;\nmov.b64 {c, _}, %2;\nmov.b64 {d, _}, %3;\n"
                 "lop3.b32 a, a, b, c, 0x80;\nlop3.b32 a, a, d, 32, 0x80;\nsetp.eq.u32 p, a, 0;\n"
                 "vote.sync.any.pred p, p, 0xffffffff;\n@p bra.uni LOOP;\nDONE:\n}"
                 : "=l"(w[0]), "=l"(w[1]), "=l"(w[2]), "=l"(w[3]) : "l"(ap) : "memory");
}
constexpr u64 FX2_INIT = 256ull + 32 - 96 * ((1ull << 28) + (1ull << 55)), FX2_NONE = 1ull + (1ull << 28) + (1ull << 55);
constexpr float FX2_MAGIC = 12582912.f + 524288.f;

__device__ __forceinline__ void tma3(uint32_t dst, const CUtensorMap* tm, int c1, int c2, uint32_t bar, uint32_t pol) {
    asm volatile("cp.async.bulk.tensor.3d.shared::cluster.global.mbarrier::complete_tx::bytes.L2::cache_hint [%0], [%1, {%2, %3, %4}], [%5], %6;"
                 :: "r"(dst), "l"(tm), "r"(0), "r"(c1), "r"(c2), "r"(bar), "l"((u64)pol << 32) : "memory");
}
__device__ __forceinline__ void tma3_pf(const CUtensorMap* tm, int c1, int c2, uint32_t pol) {
    asm volatile("cp.async.bulk.prefetch.tensor.3d.L2.global.tile.L2::cache_hint [%0, {%1, %2, %3}], %4;"
                 :: "l"(tm), "r"(0), "r"(c1), "r"(c2), "l"((u64)pol << 32) : "memory");
}
__device__ __forceinline__ void bulk_pf(const void* p, uint32_t bytes, uint32_t pol) {
    asm volatile("cp.async.bulk.prefetch.L2.global.L2::cache_hint [%0], %1, %2;" :: "l"(p), "r"(bytes), "l"((u64)pol << 32) : "memory");
}
__device__ __forceinline__ float warp_max(float v) {
    const int k = __float_as_int(v), m = __reduce_max_sync(~0u, k ^ ((k >> 31) & 0x7fffffff));
    return __int_as_float(m ^ ((m >> 31) & 0x7fffffff));
}
__device__ __forceinline__ u64 ll_pack2(float a, float b, uint32_t tag) { return mk64(__byte_perm(__float_as_uint(a), tag, 0x3214), __float_as_uint(b)); }
__device__ __forceinline__ float lof(u64 w) { return __uint_as_float(lo32(w)); }
__device__ __forceinline__ float hif(u64 w) { return __int_as_float(hi32(w)); }
__device__ __forceinline__ void ll_gather4(const u64* buf, uint32_t tag, u64 (&w)[4]) {
#pragma unroll 1
    for (int it = 0; it < SPIN; it++) {
        if (it) { w[0] = ld_rlx(buf); w[1] = ld_rlx(buf + 256); w[2] = ld_rlx(buf + 512); w[3] = ld_rlx(buf + 768); }
        if (!__any_sync(~0u, (((lo32(w[0]) ^ tag) | (lo32(w[1]) ^ tag)) | ((lo32(w[2]) ^ tag) | (lo32(w[3]) ^ tag))) & 255)) break;
    }
}
__device__ __forceinline__ u64 lds_u64(uint32_t a, int o) { const uint2 v = lds64(a, o); return v.x | (u64)v.y << 32; }
__device__ __forceinline__ float sum8(uint32_t a, int o, int pitch) {
    float s[8];
#pragma unroll
    for (int w = 0; w < 8; w++) s[w] = ldsf(a, o + w * pitch);
    return ((s[0] + s[1]) + (s[2] + s[3])) + ((s[4] + s[5]) + (s[6] + s[7]));
}
__device__ __forceinline__ void ln_final(float& mean, float& rstd, float& msq) {
    float2 v[5];
#pragma unroll
    for (int w = 0; w < 5; w++) v[w] = lds64f(0, SM_STAT + w * 8);
    mean = (((v[0].x + v[1].x) + (v[2].x + v[3].x)) + v[4].x) * (1.f / D_MODEL);
    msq = (((v[0].y + v[1].y) + (v[2].y + v[3].y)) + v[4].y) * (1.f / D_MODEL);
    rstd = rsq(fmaxf(msq - mean * mean, 0.f) + 1e-5f);
}
constexpr float CS = 0.07216878364870322f * 1.4426950408889634f;
constexpr uint32_t ONES = 0x3f803f80u;

__global__ void __launch_bounds__(NTHR, 1) fused_kernel(const __grid_constant__ Params P) {
    extern __shared__ __align__(1024) unsigned char smem[];
    const int warp = __shfl_sync(~0u, threadIdx.x >> 5, 0), bx = blockIdx.x;
    const int cta = (((bx >> 1) & 15) + (bx >> 6) * 16) * 4 + ((bx >> 5) & 1) * 2 + (bx & 1);

    if (bx == NCTA) {
        if ((uint32_t)__cvta_generic_to_shared(smem) != SM_RING) __trap();
        const uint32_t ep = *(volatile unsigned*)&g_epoch;
        if (threadIdx.x == 0) {
#pragma unroll 1
            for (int it = 0; it < SPIN; it++) { if ((lo32(ld_rlx(&g_ll[0][192])) & 255) == ((ep * 8 + 1) & 255)) break; __nanosleep(200); }
            const uint32_t t0 = gtime();
#pragma unroll 1
            for (int it = 0; it < 1024; it++) { if (gtime() - t0 > HZD) break; __nanosleep(100); }
        }
        __syncthreads();
#pragma unroll 1
        for (int i = threadIdx.x; i < 4 * 80 * 8; i += NTHR)
        {
            const u64 v = (i / 640 & 1) && (i & 7) < 2 ? FX2_INIT : 0ull;
            *reinterpret_cast<ulonglong2*>(g_acc + (i >> 3) * ACC_PITCH + (i & 7) * 16) = make_ulonglong2(v, v);
        }
        __threadfence();
        __syncthreads();
        if (threadIdx.x == 0) asm volatile("st.relaxed.gpu.global.u32 [%0], %1;" :: "l"(&g_zflag), "r"(ep + 1) : "memory");
        return;
    }
    const uint32_t barw = SM_BAR + warp * 64;
    if (elect()) {
        if (warp < NI0) sts32(0, SM_T0, gtime());
        if (warp >= 3) {
            mbar_init(barw + 56, 1);
            asm volatile("fence.mbarrier_init.release.cluster;" ::: "memory");
            mbar_expect(barw + 56, HT);
            tma3(SM_WQ - 3 * HT + warp * HT, &P.tm[TM_WQ], (cta >> 2) * 3, (cta & 3) * 160 - 96 + warp * 32, barw + 56, POL_FIRST);
        }
        TS(31);
    }
    int tid = threadIdx.x, lane, g, t, c4;
    uint32_t selA, selB, offV0, offV2;
    auto derive = [&]() {
        lane = tid & 31; g = lane >> 2; t = lane & 3;
        c4 = (tid & 0xe1) + 16 * (t >> 1) + 2 * g;
        selA = (g & 2) ? 0x4444u : (g & 1) ? 0x1044u : 0x4410u;
        selB = (g & 2) ? ((g & 1) ? 0x1044u : 0x4410u) : 0x4444u;
        offV0 = (6 * t) * 128 + ((g ^ ((6 * t) & 7)) << 4);
        offV2 = (6 * t) * 128 + ((g ^ ((6 * t + 2) & 7)) << 4);
    };
    auto refresh = [&]() { tid = pin(tid); derive(); };
    auto refresh_late = [&]() { mbar_wait(SM_BAR + 3 * 64 + 56, 0); refresh(); };
    derive();
    const int j40 = (cta & 3) * 40;
    const bool mlp = (cta & 3) != 3;
    const int hu = ((cta >> 2) * 3 + (cta & 3)) * 16;
    uint2 xp = make_uint2(0, 0);
    if (tid < 160) xp = *reinterpret_cast<const uint2*>(P.x + 4 * c4);
    else if (tid == 192) xp.x = *(volatile unsigned*)&g_epoch;
    else if (tid >= 224 && tid < 240 && mlp) xp.x = reinterpret_cast<const unsigned short*>(P.b1)[hu + lane];
    __syncwarp();
    if (elect()) {
#pragma unroll
        for (int i = 0; i < 7; i++) mbar_init(barw + i * 8, 1);
        if (warp < 4) { mbar_arrive(barw); if (EW1) mbar_arrive(barw + 8); }
        mbar_init(SM_CBAR + warp * 8, 1); mbar_init(SM_CBAR + 64 + warp * 8, 1);
        if (warp == 0) { mbar_init(SM_QBAR, 6); mbar_init(SM_BAR + 56, 8); }
        asm volatile("fence.mbarrier_init.release.cluster;" ::: "memory");
        sts64(warp * 8, SM_CNT, 0, 0);
        sts64(warp * 8, SM_ZQ, 0, 0);
    }
    uint32_t kc[192];
#pragma unroll
    for (int i = 12; i < 192; i++) asm volatile("mov.b32 %0, 0;" : "=r"(kc[i]));
    const int rowc = (cta >> 2) * SK + (SK - WIN) + (cta & 3) * 64;
    const int roww = __shfl_sync(~0u, rowc + warp * 8, 0);
    const CUtensorMap* tmk = reinterpret_cast<const CUtensorMap*>(__shfl_sync(~0u, (u64)&P.tm[0] + (lane >> 5), 0));

    auto wait_due = [&](int i, int extra) {
        const uint32_t due = lds32(0, SM_T0) + PACE0 + extra + i * PACE;
#pragma unroll 1
        for (int it = 0; it < 4096; it++) if ((int)(gtime() - due) >= 0) break;
    };
    auto issue_wo = [&](int k) {
        wait_due(64, k * WOPACE + WOD);
        mbar_expect(SM_CBAR + 32 + k * 8, 4 * WOU);
        asm volatile("cp.async.bulk.tensor.4d.shared::cluster.global.mbarrier::complete_tx::bytes.L2::cache_hint [%0], [%1, {%2, %3, %4, %5}], [%6], %7;"
                     :: "r"(SM_RING + k * 4 * WOU), "l"(tmk + TM_WO4), "r"(0), "r"(5 * (cta & 3)), "r"((k >> 1) * 8), "r"((cta >> 2) * 8 + (k & 1) * 4),
                        "r"(SM_CBAR + 32 + k * 8), "l"((u64)(WOKEEP == 1 && k < 4 ? POL_NORMAL : POL_FIRST) << 32) : "memory");
        if (WOKEEP == 2 && k < 4 && mlp)
            asm volatile("cp.async.bulk.prefetch.tensor.4d.L2.global.tile.L2::cache_hint [%0, {%1, %2, %3, %4}], %5;"
                         :: "l"(tmk + TM_WOP), "r"(0), "r"(5 * (cta & 3)), "r"((k >> 1) * 8), "r"((cta >> 2) * 8 + (k & 1) * 4), "l"((u64)POL_NORMAL << 32) : "memory");
    };
    auto issue_kv = [&](int i, int slot, int bar) {
        const int row = rowc + (i & 30) * 128 + (i & 1) * 32;
        mbar_expect(SM_CBAR + bar * 8, HT);
        tma3(SM_RING + slot * HT, tmk + TM_K + (i >> 5), 0, row, SM_CBAR + bar * 8, POL_FIRST);
        if (i >= KEEP0) tma3_pf(tmk + TM_VP, 0, row, POL_NORMAL);
    };
    __syncwarp();
    if (warp < NI0) { wait_due(warp, 0); if (elect()) issue_kv(warp, warp == 4 ? 0 : warp + 1, warp); }
    if (warp >= 3) mbar_wait(barw + 56, 0);
    if (tid == 192) sts32(0, SM_EPOCH, xp.x);
    if (tid >= 224 && tid < 240) sts32(lane * 4, SM_B1, xp.x << 16);
    __syncthreads();
    TSB(10);
    if (warp >= NI0 && elect()) {
        if (warp < 5) issue_kv(warp, warp == 4 ? 0 : warp + 1, warp);
        else if (warp < 5 + NPF0) tma3_pf(tmk + TM_K, 0, rowc + (warp & 30) * 128 + (warp & 1) * 32, POL_FIRST);
    }
    const uint32_t ep4 = __shfl_sync(~0u, lds32(0, SM_EPOCH) * 4, 0);

    auto load_v3 = [&](uint4* v, uint32_t u, int o, bool odd) {
        if (!odd) { v[0] = lds128(ad(offV0, u), o); v[1] = lds128(ad(offV0 ^ 16, u), o + 128); v[2] = lds128(ad(offV2, u), o + 256); }
        else { v[0] = lds128(ad(offV2 ^ 16, u), o + 384); v[1] = lds128(ad(offV0 ^ 64, u), o + 512); v[2] = lds128(ad(offV0 ^ 80, u), o + 640); }
    };
    auto load_v = [&](uint4 (&v)[6], uint32_t u, int o) { load_v3(v, u, o, false); load_v3(v + 3, u, o, true); };
    const uint32_t wqw = warp * SUB, ksw = warp * HT;
    auto slot_o = [&](int s) { return s < 3 ? SM_WQ + s * 8 * SUB : SM_KS + (s - 3) * SUB; };
    auto slot_u = [&](int s) { return s < 3 ? wqw : ksw; };
    const uint32_t zero = __shfl_sync(~0u, lds32(0, SM_ZQ), 0);
    auto issue2 = [&](auto I, uint32_t dep) {
        constexpr int p = I.value, s = PL.slot[p];
        __syncwarp();
        TR(5, 2 + p);
        if (SKIP >> p & 1) { if (elect()) mbar_arrive(barw + s * 8); }
        else if ((p < 16 || mlp) && elect()) {
            mbar_expect(barw + s * 8, (dep & zero) | (p < 16 ? SUB : 2 * WOU));
            if constexpr (p < 16) tma3(slot_u(s) + slot_o(s), tmk + TM_V8, 0, roww + vunit(p) * 256, barw + s * 8, POL_FIRST);
            else tma3(slot_u(s) + slot_o(s), tmk + TM_WO, 5 * (cta & 3), (cta >> 2) * DH + warp * 24, barw + s * 8, POL_FIRST);
        }
    };
    auto touch2 = [&]() {
        const char* p = reinterpret_cast<const char*>(P.v) + (size_t)(roww + vunit(2) * 256) * (DH * 2) + lane * 32;
#pragma unroll
        for (int i = 0; i < 3; i++) asm volatile("cp.async.ca.shared.global [%0], [%1], 4;" :: "r"(SM_JUNK), "l"(p + i * 1024) : "memory");
    };
    auto issue_help = [&]() {
        if (elect())
            tma3(SM_WQ + (warp == 7 ? 0 : warp == 6 ? 16 * SUB : 4 * SUB), tmk + (warp == 5 ? TM_V8 : TM_V), 0,
                 rowc + (warp == 6 ? vunit(2) * 256 : warp == 5 ? vunit(0) * 256 + 32 : vunit(0) * 256), warp == 5 ? SM_BAR + 4 * 64 : SM_CBAR - 32 + warp * 8, POL_FIRST);
    };
    auto issue_item1 = [&]() {
        if (elect()) {
            const uint32_t bar = EW1 && warp == 7 ? SM_BAR + 4 * 64 + 8 : SM_CBAR - 48 + warp * 8;
            mbar_expect(bar, EW1 && warp == 7 ? SUB : HT);
            tma3(SM_WQ - 4 * HT + warp * HT, tmk + (EW1 && warp == 7 ? TM_V8 : TM_V), 0, rowc - 192 + warp * 32 + vunit(1) * 256, bar, POL_FIRST);
        }
    };
    const uint32_t prow = warp * 768;
    uint4 wq0[6], wqh[3], wq1[6];
    uint32_t xna;
    auto load_wq = [&]() {
        load_v(wq0, wqw, SM_WQ);
        const int r0 = 6 * t + 3 * (warp & 1);
#pragma unroll
        for (int j = 0; j < 3; j++) wqh[j] = lds128(ad(r0 * 128 + ((g ^ ((r0 + j) & 7)) << 4), (warp >> 1) * SUB), SM_WQ + 16 * SUB + j * 128);
        const int r = c4 - j40;
        xna = pin((tid < 160 && r >= 0 && r < 40) ? SM_VEC + r * 8 : 0u);
        selA = pin(selA); selB = pin(selB);
        offV0 = pin(offV0 + wqw); offV2 = pin(offV2 + wqw);
        tid = pin(tid);
    };
    float acc[3][4];
    uint32_t cq;
    auto mma3 = [&](const uint4* v, uint32_t pp, uint32_t hi) {
        const uint32_t b0 = pick(pp, selA | hi), b1 = pick(pp, selB | hi);
        mma(acc[0], v[0], b0, b1); mma(acc[1], v[1], b0, b1); mma(acc[2], v[2], b0, b1);
    };
    auto ln_part = [&]() {
        const float x0 = bf_lo(xp.x), x1 = bf_hi(xp.x), x2 = bf_lo(xp.y), x3 = bf_hi(xp.y);
        const float s1 = (x0 + x1) + (x2 + x3), s2 = (x0 * x0 + x1 * x1) + (x2 * x2 + x3 * x3);
        float ss = ((tid & 16) ? s2 : s1) + shx((tid & 16) ? s1 : s2, 16);
        ss += shx(ss, 8); ss += shx(ss, 4); ss += shx(ss, 2); ss += shx(ss, 1);
        sts32_if((tid & 15) == 0 && tid < 160, tid >> 2, SM_STAT, __float_as_uint(ss));
    };

    auto tick = [&](uint4& v) {
        asm volatile("{\n.reg .pred p;\nsetp.ne.u32 p, %4, 0;\n@p mma.sync.aligned.m16n8k16.row.col.f32.bf16.bf16.f32 {%0,%1,%2,%3}, {%0,%1,%2,%3}, {%0,%1}, {%0,%1,%2,%3};\n}"
                     : "+r"(v.x), "+r"(v.y), "+r"(v.z), "+r"(v.w) : "r"(zero));
    };

    auto q_stage = [&](auto L, auto E) {
        constexpr int layer = L.value;
        if (!E.value) asm volatile("{\n.reg .pred p;\nsetp.ne.u32 p, %0, 0;\n@p st.shared.v2.u32 [%0], {%1,%2};\n}" :: "r"(xna), "r"(xp.x), "r"(xp.y) : "memory");
        if (!E.value) load_v3(wq1, 0, SM_WQ + 8 * SUB, false);
        const uint32_t xra = (tid & 3) * 4;
        bar_sync(0, 256);
        if (layer) TSB(20);
        uint32_t p0 = lds32(ad(xra, warp * 16), SM_VEC), ph = lds32(ad(xra, (warp >> 1) * 16), SM_VEC + 256), p1 = lds32(ad(xra, warp * 16), SM_VEC + 128);
        if (layer == 0 && (tid & 16)) p0 = p1 = ph = ONES;
#pragma unroll
        for (int j = 0; j < 3; j++) zero4(acc[j]);
        mma3(wq0, p0, 0); mma3(wq0 + 3, p0, 0x2222);
        if (!E.value) load_v3(wq1 + 3, 0, SM_WQ + 8 * SUB, true);
        mma3(wqh, ph, (warp & 1) * 0x2222); mma3(wq1, p1, 0); mma3(wq1 + 3, p1, 0x2222);
        if (layer == 1) { lds128(kc + 8, prow + (tid & 31) * 16, SM_PART); lds64(kc + 88, prow + (tid & 31) * 8, SM_PART + 512); __syncwarp(); }
        const uint32_t qpa = ((layer == 0 && (tid & 2)) ? ksw - (SM_PART - SM_KS - 11264) : prow) + (tid & 28) * 8 + (tid & 1) * 16;
#pragma unroll
        for (int j = 0; j < 3; j++) sts128f_if(layer == 0 || !(tid & 2), qpa, SM_PART + j * 256, acc[j][0], acc[j][1], acc[j][2], acc[j][3]);
    };
    auto q_end = [&](auto L) {
        constexpr int layer = L.value;
        u64* dst = &g_ll[cta][tid];
        if (layer) TS(21);
        __syncthreads();
        if (layer) TSB(22);
        if (warp < 6) {
            const float s = sum8(tid * 4, SM_PART, 768);
            st_rlx(dst, layer ? mk64(2 * ep4 + 5, __float_as_uint(s)) : ll_pack2(sum8(tid * 4, SM_KS + 11264, HT), s, 2 * ep4 + 1));
        } else if (layer == 1) { sts32(0, SM_T0, gtime()); if (!I1D) issue_item1(); }
        if (layer) TS(23);
        cq = clk();
        refresh_late();
        if (!LNLATE || !layer) {
            ln_part();
            __syncthreads();
            sts64(prow + lane * 8, SM_PART, xp.x, xp.y);
        }
    };
    auto q_addr = [&]() { return (((tid >> 1) & 1) * 4 + ((tid >> 4) & 3)) * 48 + ((tid >> 6) * 2 + ((tid >> 3) & 1)) * 8 + ((tid >> 2) & 1) * 4 + (tid & 1) * 2; };
    auto score6 = [&](const uint4 (&v)[6], const uint32_t (&qf)[12]) {
        float d[2][4];
#pragma unroll
        for (int i = 0; i < 6; i++) { if (i < 2) zero4(d[i]); mma(d[i & 1], v[i], qf[2 * i], qf[2 * i + 1]); }
        return (d[0][0] + d[0][3]) + (d[1][0] + d[1][3]);
    };
    auto softmax = [&](auto L, const float (&S)[4]) {
        constexpr int layer = L.value;
        DBG(0 + 8 * layer, S[0] + S[1] + S[2] + S[3]);
        const float mrun = warp_max(fmaxf(fmaxf(S[0], S[1]), fmaxf(S[2], S[3])));
        const float p0 = ex2((S[0] - mrun) * CS), p1 = ex2((S[1] - mrun) * CS), p2 = ex2((S[2] - mrun) * CS), p3 = ex2((S[3] - mrun) * CS);
        const uint32_t pa = pack_bf(p0, p1), pb = pack_bf(p2, p3), pw = prow + t * 64 + g * 2;
        sts16(pw, SM_PART + 256, pa); sts16(pw, SM_PART + 272, pa >> 16); sts16(pw, SM_PART + 288, pb); sts16(pw, SM_PART + 304, pb >> 16);
        const uint32_t l = __reduce_add_sync(~0u, __float2uint_rn(((p0 + p1) + (p2 + p3)) * 16777216.f));
        st_rlx(&g_ll[cta][192 + warp], mk64(__byte_perm(l + 128, 2 * ep4 + 1 + 4 * layer, 0x3214), __float_as_uint(mrun)));
        __syncwarp();
#pragma unroll
        for (int j = 0; j < 3; j++) zero4(acc[j]);
    };
    auto pv = [&](const uint4 (&v)[6], uint32_t pp) { mma3(v, pp, 0); mma3(v + 3, pp, 0x2222); };

    auto head_look = [&]() {
        if (lane < 16) asm volatile("cp.async.cg.shared.global [%0], [%1], 16;" :: "r"(SM_PART + 512 + prow + lane * 16), "l"(&g_ll[cta ^ g][192 + 2 * t]) : "memory");
    };
    float fw;
    auto head_weight = [&](auto L) {
        const uint32_t tag = (2 * ep4 + 1 + 4 * L.value) & 255;
        uint32_t l, m;
#pragma unroll 1
        for (int it = 0; it < SPIN; it++) {
            if (it) head_look();
            asm volatile("cp.async.wait_all;" ::: "memory");
            __syncwarp();
            asm volatile("ld.volatile.shared.v2.u32 {%0,%1}, [%2];" : "=r"(l), "=r"(m) : "r"(SM_PART + 512 + prow + lane * 8) : "memory");
            l ^= tag;
            if (!__any_sync(~0u, l & 255)) break;
        }
        const float f = ex2((__uint_as_float(m) - warp_max(__uint_as_float(m))) * CS);
        const uint32_t Lh = __reduce_add_sync(~0u, __float2uint_rn(f * (float)l * 0.03125f));
        fw = __shfl_sync(~0u, f, warp) * rcp((float)Lh) * (ldsf(0, SM_FXS) * 524288.f);
    };

    uint32_t wa[5], ya, oa, selC, selD;
    uint4 z[5];
    unsigned char* ra;
    const u64* lp;
    auto load_u = [&](uint4 (&a)[5], uint32_t u, int o) {
#pragma unroll
        for (int k = 0; k < 5; k++) a[k] = lds128(ad(wa[k], u), o);
    };
    auto tail_prep1 = [&](auto L) {
        xp = lds64(prow + lane * 8, SM_PART);
        ya = pin(prow + (8 * g + 4 * (t & 1)) * 4);
        oa = pin(((tid >> 5) * 12 + min(lane, 11)) * 8);
        lp = pinp(reinterpret_cast<const u64*>(reinterpret_cast<const char*>(&g_ll[cta][0]) + oa));
    };
    auto tail_prep2 = [&](auto L) {
#pragma unroll
        for (int k = 0; k < 5; k++) {
            const int row = (t & 1) + 2 * (t & 2) + 2 * (k < 4 ? k >> 1 : g >> 2), j = k < 4 ? 2 * (k & 1) + (g >> 2) : 4;
            wa[k] = pin(row * 320 + j * 64 + (((g & 3) ^ (((5 * row + j) >> 1) & 3)) << 4));
        }
        selA = pin(selA); selB = pin(selB);
        selC = selA | (g >> 2) * 0x2222; selD = selB | (g >> 2) * 0x2222;
    };
    auto red_addr = [&](auto L) {
        const int word = t * 160 + j40 + (tid >> 2);
        ra = pinp(g_acc + 2 * L.value * ACC_BYTES + (uint32_t)((word >> 3) * ACC_PITCH + (word & 7) * 8));
    };
    uint4 wf[8], w2r[8];
    uint32_t la, w2a, hpa, ha, *op;
    uint2 b2v;
    const unsigned char* ap;
    unsigned char* ap2;
    float inv1;
    auto load_w1 = [&]() {
#pragma unroll
        for (int j = 0; j < 8; j++) wf[j] = ldsm_t(la, SM_RING + j * 256);
    };
    auto load_w2 = [&]() {
#pragma unroll
        for (int i = 0; i < 8; i++) w2r[i] = lds128(w2a ^ ((i & 1) * 16), SM_W2 + (i >> 1) * 5120 + (i & 1) * 128);
    };
    auto load_b2 = [&]() { asm volatile("ld.global.nc.v2.u32 {%0,%1}, [%2];" : "=r"(b2v.x), "=r"(b2v.y) : "l"(P.b2 + 4 * min(c4, 159))); };
    auto mlp_prep = [&](auto L) {
        unsigned char* const accb = g_acc + 2 * L.value * ACC_BYTES;
        la = (tid >> 5) * 4096 + (64 * ((lane >> 2) & 1) + 4 * ((lane >> 1) & 1) + (lane & 1) + 2 * (lane >> 4)) * 32 + ((((lane >> 3) ^ (lane >> 1)) & 1) << 4);
        w2a = pin((10 * t + 2 * (tid >> 5)) * 128 + ((g ^ ((2 * t + 2 * (tid >> 5)) & 7)) << 4));
        hpa = pin((tid >> 5) * 64 + (t * 8 + g) * 4); ha = pin((lane & 15) * 4);
        if (L.value == 0) { selA = pin(selA); selB = pin(selB); tid = pin(tid); }
        ap = accb + (uint32_t)((c4 >> 3) * ACC_PITCH + (c4 & 7) * 8);
        ap2 = accb + ACC_BYTES + pin((c4 >> 2) * ACC_PITCH + (c4 & 3) * 8);
        if (L.value == 1) ap2 = pinp(ap2);
        inv1 = fx_inv(ldsf(0, SM_FXS));
        if (L.value == 1) { ap = pinp(ap); la = pin(la); op = pinp(reinterpret_cast<uint32_t*>(P.out) + 2 * c4); }
    };
    auto tail = [&](auto L) {
        constexpr int layer = L.value;
        auto park = [&]() { const int ln = pin(tid) & 31; sts128(prow + ln * 16, SM_PART, kc[8], kc[9], kc[10], kc[11]); sts64(prow + ln * 8, SM_PART + 512, kc[88], kc[89]); };
        {
#pragma unroll
            for (int j = 0; j < 3; j++) sts128f_if(!(tid & 2), ya, SM_PART + 256 * j, acc[j][0] * fw, acc[j][2] * fw, acc[j][1] * fw, acc[j][3] * fw);
            const uint32_t tag = (2 * ep4 + 3 + 4 * layer) & 255;
            __syncthreads();
            TSB(4 + 10 * layer);
            float2 own;
            {
                float2 s[8];
#pragma unroll
                for (int w = 0; w < 8; w++) s[w] = lds64f(oa, SM_PART + w * 768);
                own.x = ((s[0].x + s[1].x) + (s[2].x + s[3].x)) + ((s[4].x + s[5].x) + (s[6].x + s[7].x));
                own.y = ((s[0].y + s[1].y) + (s[2].y + s[3].y)) + ((s[4].y + s[5].y) + (s[6].y + s[7].y));
                st_rlx(const_cast<u64*>(lp), ll_pack2(own.x, own.y, tag));
            }
            DBG(1 + 8 * layer, own.x + own.y);
            const uint32_t c0 = clk();
            if (layer == 0) refresh_late();
            uint4 v[5], u[5];
            if constexpr (layer == 0) {
                if (warp < 3) { if (elect()) issue_wo(3 + warp); __syncwarp(); }
                if ((TOUCH & 1) && warp >= 4) touch2();
                tail_prep2(L);
                mbar_wait(SM_CBAR + 32 + (warp >> 2) * 8, 0);
                load_u(v, warp * WOU, SM_RING);
                __syncthreads();
            }
            constexpr int YP = layer ? SM_WQ : SM_PART;
            float y[3][4];
#pragma unroll
            for (int j = 0; j < 3; j++) zero4(y[j]);
            const u64 *l1 = reinterpret_cast<const u64*>((u64)lp ^ 4096), *l2 = reinterpret_cast<const u64*>((u64)lp ^ 2048), *l3 = reinterpret_cast<const u64*>((u64)lp ^ 6144);
            if (KA & (layer ? 8 : 4)) tick(layer ? z[0] : v[0]);
            while (clk() - c0 < (layer ? ODELAY2 : ODELAY1));
            const uint32_t w1due = layer ? 0 : lds32(0, SM_T0) + PACE0 + 69 * PACE + W1D + (warp - 3) * W1G;
            u64 w1 = ld_rlx(l1), w2 = ld_rlx(l2), w3 = ld_rlx(l3);
            if constexpr (layer == 1) {
                if (mlp) mbar_wait(barw + 40, IC<PL.par[16]>::value);
                TS(30);
                load_u(v, mlp ? ksw + slot_o(5) : SM_RING + warp * WOU, 0); load_u(u, mlp ? ksw + slot_o(5) + WOU : SM_RING + (8 + warp) * WOU, 0);
            }
            if (layer == 0 && warp >= 3 && mlp) {
#pragma unroll 1
                for (int it = 0; it < 4096; it++) { if (KA & 4) tick(v[0]); if ((int)(gtime() - w1due) >= 0) break; }
                if (elect()) {
                    mbar_expect(SM_CBAR + 56 + warp * 8, 4096);
                    asm volatile("cp.async.bulk.tensor.2d.shared::cluster.global.mbarrier::complete_tx::bytes.L2::cache_hint [%0], [%1, {%2, %3}], [%4], %5;"
                                 :: "r"(SM_RING + (warp - 3) * 4096), "l"(tmk + TM_W1), "r"(hu), "r"(warp * 128 - 384), "r"(SM_CBAR + 56 + warp * 8), "l"((u64)POL_FIRST << 32) : "memory");
                }
                __syncwarp();
            }
#pragma unroll 1
            for (int it = 0; it < SPIN; it++) {
                if (it) { w1 = ld_rlx(l1); w2 = ld_rlx(l2); w3 = ld_rlx(l3); }
                if (!__any_sync(~0u, ((lo32(w1) ^ tag) | (lo32(w2) ^ tag) | (lo32(w3) ^ tag)) & 255)) break;
            }
            TS(5 + 10 * layer);
            const uint32_t od = pack_bf((own.x + __uint_as_float(lo32(w1) ^ tag)) + (__uint_as_float(lo32(w2) ^ tag) + __uint_as_float(lo32(w3) ^ tag)),
                                        (own.y + __int_as_float(hi32(w1))) + (__int_as_float(hi32(w2)) + __int_as_float(hi32(w3))));
            DBG(2 + 8 * layer, bf_lo(od) + bf_hi(od));
            const uint32_t o0 = __shfl_sync(~0u, od, tid & 3), o1 = __shfl_sync(~0u, od, (tid & 3) + 4), o2 = __shfl_sync(~0u, od, (tid & 3) + 8);
            auto narrow = [&](const uint4 (&a)[5], uint32_t o) { mma(y[2], a[4], pick(o, selC), pick(o, selD)); };
            auto wide = [&](const uint4 (&a)[5], uint32_t o) {
                const uint32_t b0 = pick(o, selA), b1 = pick(o, selB), b2 = pick(o, selA | 0x2222), b3 = pick(o, selB | 0x2222);
                mma(y[0], a[0], b0, b1); mma(y[1], a[1], b0, b1); mma(y[0], a[2], b2, b3); mma(y[1], a[3], b2, b3);
            };
            narrow(v, o0); wide(v, o0);
            if constexpr (layer == 0) {
                mbar_wait(SM_CBAR + 48 + (warp >> 2) * 8, 0);
                load_u(u, warp * WOU, SM_RING + 8 * WOU);
                __syncwarp();
                if (mlp && elect() && atoms_inc(SM_CNT + 44, 7) == 7) { mbar_expect(SM_CBAR + 120, 20480); tma3(SM_W2, tmk + TM_W2, 0, hu, SM_CBAR + 120, POL_FIRST); }
                __syncwarp();
                narrow(u, o1); wide(u, o1);
                red_addr(L);
                mbar_wait(SM_CBAR + 64 + (warp >> 2) * 8, 0);
                TS(28);
                load_u(z, warp * WOU, SM_RING + 16 * WOU);
                narrow(z, o2);
            } else { narrow(u, o1); narrow(z, o2); wide(u, o1); }
            wide(z, o2);
#pragma unroll
            for (int k = 0; k < 4; k++) y[2][k] += shx(y[2][k], 18);
            sts128f_if(!(tid & 18), ya, YP + 512, y[2][0], y[2][1], y[2][2], y[2][3]);
            sts128f_if(!(tid & 2), ya, YP, y[0][0], y[0][1], y[0][2], y[0][3]);
            sts128f_if(!(tid & 2), ya, YP + 256, y[1][0], y[1][1], y[1][2], y[1][3]);
            __syncthreads();
            if (warp < 5) {
                const float s = sum8(tid * 4, YP, 768);
                DBG(3 + 8 * layer, s);
                asm volatile("red.relaxed.gpu.global.add.u64 [%0], %1;" :: "l"(ra), "l"(fx_pack(s)) : "memory");
            }
            TS(6 + 10 * layer);
            cq = clk();
            if (layer == 0) refresh_late();
        }
        if (layer == 1 && !mlp) return;
        if (warp < 5) {
            if (layer == 0) { asm volatile("bar.arrive 2, 256;" ::: "memory"); mlp_prep(L); if (mlp) mbar_wait(SM_CBAR + 80 + warp * 8, 0); TS(29); load_w1(); }
            if (layer == 1) { if (PREP3 > 14) load_w1(); if (PREP4 > 14) load_w2(); }
            {
                u64 w[4];
                while (clk() - cq < (layer || mlp ? AR1D : AR1DN));
                if (layer) TS(11);
                fx_poll(ap, w);
                TS(7 + 10 * layer);
                xp = make_uint2(pack_bf(bf_lo(xp.x) + fx_val(w[0]) * inv1, bf_hi(xp.x) + fx_val(w[1]) * inv1),
                                pack_bf(bf_lo(xp.y) + fx_val(w[2]) * inv1, bf_hi(xp.y) + fx_val(w[3]) * inv1));
            }
            DBG(4 + 8 * layer, bf_lo(xp.x) + bf_hi(xp.y));
            {
                const bool ev = layer || !(tid & 4), od = layer || (tid & 4);
                const uint32_t e0 = ev ? xp.x : ONES, e1 = ev ? xp.y : ONES, o0 = od ? xp.x : ONES, o1 = od ? xp.y : ONES;
                float d[8][4];
#pragma unroll
                for (int j = 0; j < 8; j++) { zero4(d[j]); mma(d[j], wf[j], (j & 1) ? o0 : e0, (j & 1) ? o1 : e1); }
                float lo = d[0][0] + d[1][1], hi = d[0][2] + d[1][3];
#pragma unroll
                for (int m = 1; m < 4; m++)
                    asm("{\n.reg .pred p;\nsetp.eq.u32 p, %6, %7;\n@p add.f32 %0, %2, %3;\n@p add.f32 %1, %4, %5;\n}" : "+f"(lo), "+f"(hi)
                        : "f"(d[2 * m][0]), "f"(d[2 * m + 1][1]), "f"(d[2 * m][2]), "f"(d[2 * m + 1][3]), "r"(tid & 3), "r"(m));
                float dd = ((tid & 1) ? hi : lo) + shx((tid & 1) ? lo : hi, 1);
                dd += shx(dd, 2);
                ln_part();
                if (layer == 0) {
                    const float cl = ((d[0][1] + d[1][0]) + (d[2][1] + d[3][0])) + ((d[4][1] + d[5][0]) + (d[6][1] + d[7][0]));
                    const float ch = ((d[0][3] + d[1][2]) + (d[2][3] + d[3][2])) + ((d[4][3] + d[5][2]) + (d[6][3] + d[7][2]));
                    sts32_if(!(tid & 2), hpa, SM_C1, __float_as_uint((tid & 1) ? ch : cl));
                }
                sts32_if(!(tid & 2), hpa, SM_QU, __float_as_uint(dd));
            }
            const float b1v = ldsf(ha, SM_B1);
            float csum = layer ? ldsf(ha, SM_B1 + 64) : 0.f;
            bar_sync(1, layer ? 160 : 192);
            TSB(26 + layer);
            float mean, rstd, msq;
            ln_final(mean, rstd, msq);
            float hp[5];
#pragma unroll
            for (int w = 0; w < 5; w++) hp[w] = ldsf(ha, SM_QU + w * 64);
            if constexpr (layer == 0) {
                float c[5];
#pragma unroll
                for (int w = 0; w < 5; w++) c[w] = ldsf(ha, SM_C1 + w * 64);
                csum = ((c[0] + c[1]) + (c[2] + c[3])) + c[4];
                load_w2();
            }
            float hv = ((((hp[0] + hp[1]) + (hp[2] + hp[3])) + hp[4]) - mean * csum) * rstd + b1v;
            hv = hv * rcp(1.f + ex2(hv * (-2.302208198f - 0.1029432397f * hv * hv)));
            const uint32_t hd = pack_bf(hv, hv);
            DBG(5 + 8 * layer, mlp ? hv : 0.f);
            float yA[4] = {0.f, 0.f, 0.f, 0.f}, yB[4] = {0.f, 0.f, 0.f, 0.f};
            const uint32_t hh[4] = {__shfl_sync(~0u, hd, tid & 3), __shfl_sync(~0u, hd, (tid & 3) + 4), __shfl_sync(~0u, hd, (tid & 3) + 8), __shfl_sync(~0u, hd, (tid & 3) + 12)};
#pragma unroll
            for (int i = 0; i < 4; i++) {
                const uint32_t b0 = pick(hh[i], selA), b1 = pick(hh[i], selB);
                mma(yA, w2r[2 * i], b0, b1); mma(yB, w2r[2 * i + 1], b0, b1);
            }
            const float sc2 = __uint_as_float((uint32_t)(127 + 16 - max(((int)(__float_as_uint(msq) >> 23) - 127) >> 1, -100)) << 23);
            float y[4];
            uint32_t yb[4];
#pragma unroll
            for (int k = 0; k < 4; k++) { y[k] = (tid & 2) ? yB[k] : yA[k]; yb[k] = __float_as_uint(fmaf(y[k], sc2, FX2_MAGIC)); }
            DBG(6 + 8 * layer, mlp ? y[0] + y[1] + y[2] + y[3] : 0.f);
            const uint32_t big = !mlp ? 0 : (((yb[0] ^ 0x4b400000u) | (yb[1] ^ 0x4b400000u)) | ((yb[2] ^ 0x4b400000u) | (yb[3] ^ 0x4b400000u))) & FX2_MASK;
            u64 w[2], old[2];
#pragma unroll
            for (int k = 0; k < 2; k++) {
                w[k] = mk64(big ? 0 : yb[2 * k] * 512 + 0x80000001u, big ? 0 : yb[2 * k + 1] * 16 + 0x4c000000u);
                if (layer == 0) { if (mlp) asm volatile("red.relaxed.gpu.global.add.u64 [%0], %1;" :: "l"(ap2 + k * 40 * ACC_PITCH), "l"(w[k]) : "memory"); }
                else asm volatile("atom.relaxed.gpu.global.add.u64 %0, [%1], %2;" : "=l"(old[k]) : "l"(ap2 + k * 40 * ACC_PITCH), "l"(w[k]) : "memory");
            }
            TS(8 + 10 * layer);
            const uint32_t c0 = clk();
            if (__any_sync(~0u, big)) {
                if (big) {
#pragma unroll
                    for (int k = 0; k < 4; k++)
                        asm volatile("red.relaxed.gpu.global.add.u64 [%0], %1;" :: "l"(ap2 + (k >> 1) * 40 * ACC_PITCH + 64 + (k & 1) * 32), "l"(fx_pack(y[k] * fx_scale(msq))) : "memory");
                    __threadfence();
#pragma unroll
                    for (int k = 0; k < 2; k++) {
                        asm volatile("red.relaxed.gpu.global.and.b64 [%0], %1;" :: "l"(ap2 + k * 40 * ACC_PITCH), "l"(~256ull) : "memory");
                        w[k] = FX2_NONE;
                        asm volatile("atom.relaxed.gpu.global.add.u64 %0, [%1], %2;" : "=l"(old[k]) : "l"(ap2 + k * 40 * ACC_PITCH), "l"(FX2_NONE) : "memory");
                    }
                }
                __syncwarp();
            }
            if (layer == 0) { refresh(); load_b2(); park(); stsf(ha, SM_B1 + 64, csum); }
            stsf(0, SM_FXS, msq);
            const float inv32 = fx_inv(sc2) * 0.03125f;
            float xb[4] = {bf_lo(xp.x) + bf_lo(b2v.x) - 24.f * inv32, bf_hi(xp.x) + bf_hi(b2v.x), bf_lo(xp.y) + bf_lo(b2v.y) - 24.f * inv32, bf_hi(xp.y) + bf_hi(b2v.y)};
            auto add_wide = [&]() {
                __threadfence();
#pragma unroll
                for (int k = 0; k < 4; k++) xb[k] += fx_val(ld_rlx(ap2 + (k >> 1) * 40 * ACC_PITCH + 64 + (k & 1) * 32)) * fx_inv(fx_scale(ldsf(0, SM_FXS)));
            };
            auto sum2 = [&](int k) {
                return pack_bf(xb[2 * k] + (float)(int)__funnelshift_r(lo32(w[k]), hi32(w[k]), 4) * inv32, xb[2 * k + 1] + (float)hi32(w[k]) * (inv32 + inv32));
            };
            if constexpr (layer == 1) {
#pragma unroll
                for (int k = 0; k < 4; k++) xb[k] = pinf(xb[k]);
                mbar_wait(SM_BAR + 3 * 64 + 56, 0);
#pragma unroll
                for (int k = 0; k < 2; k++) {
                    w[k] += old[k];
                    asm volatile("{\n.reg .pred p;\nsetp.eq.u32 p, %2, 0;\n@p st.global.u32 [%0], %1;\n}" :: "l"(op + k), "r"(sum2(k)), "r"(~lo32(w[k]) & 0x180) : "memory");
                }
                TS(19);
                if (((lo32(w[0]) & ~(lo32(w[0]) >> 1)) | (lo32(w[1]) & ~(lo32(w[1]) >> 1))) & 128) {
                    add_wide();
                    if (w[0] & 128) op[0] = sum2(0);
                    if (w[1] & 128) op[1] = sum2(1);
                }
            } else {
                load_wq();
                __syncwarp();
                if (elect()) mbar_arrive(SM_BAR + 56);
#pragma unroll
                for (int k = 0; k < 4; k++) xb[k] = pinf(xb[k]);
                while (clk() - c0 < (mlp ? ARDELAY : ARDN));
                uint32_t want = 0x180;
#pragma unroll 1
                for (int it = 0; it < SPIN; it++) {
                    if (it && !__any_sync(~0u, ~(lo32(w[0]) & lo32(w[1])) & 128)) { add_wide(); want = 128; }
                    w[0] = ld_rlx(ap2); w[1] = ld_rlx(ap2 + 40 * ACC_PITCH);
                    if (!__any_sync(~0u, ~(lo32(w[0]) & lo32(w[1])) & want)) break;
                }
                xp = make_uint2(sum2(0), sum2(1));
                TS(9);
                DBG(7, bf_lo(xp.x) + bf_hi(xp.y));
                q_stage(IC<1>{}, IC<0>{});
            }
        } else if constexpr (layer == 1) {
            if ((KA & 16) && warp == 7) {
                const uint32_t c1 = clk();
                while (clk() - c1 < KAD2) tick(z[0]);
                if (zero) sts32(0, SM_JUNK, z[0].x);
            }
        } else {
            const uint32_t c0 = clk();
            bar_sync(2, 256);
            park();
            load_wq();
            __syncwarp();
            if (elect()) mbar_arrive(SM_BAR + 56);
            if (warp == 5) {
                if (mlp) mbar_wait(SM_CBAR + 120, 0);
                asm volatile("bar.arrive 1, 192;" ::: "memory");
            }
            while (clk() - c0 < S6D + (warp - 5) * S6G) if (KA & 2) tick(wqh[0]);
            issue2(IC<0>{}, wq0[0].x | wq0[1].x | wq0[2].x | wq0[3].x | wq0[4].x | wq0[5].x);
            if (warp == 5) {
#pragma unroll 1
                for (int k = 0; k < NPFC; k++) {
                    while (clk() - c0 < PFD + k * PFG);
                    if (elect()) tma3_pf(tmk + TM_V8, 0, rowc + (k >> 3) * 256 + (k & 7) * 8, PFPOL);
                }
            }
            if (elect()) mbar_expect(warp == 5 ? SM_BAR + 4 * 64 : SM_CBAR - 32 + warp * 8, warp == 5 ? SUB : HT);
#pragma unroll 1
            for (int it = 0; it < SPIN; it++) { if (mbar_test(SM_BAR + 56, 0)) break; if (KA & 2) tick(wqh[0]); }
            const uint32_t c1 = clk();
            while (clk() - c1 < I0D + (7 - warp) * I0G) if (KA & 2) tick(wqh[0]);
            issue_help();
            q_stage(IC<1>{}, IC<EW1>{});
            xp = make_uint2(0, 0);
        }
    };

    load_wq();
    q_stage(IC<0>{}, IC<0>{});
    q_end(IC<0>{});
    TS(1);
    {
        int it = (warp >> 2) + 5, slot = (warp >> 2) + 1, bar = warp >> 2, par = 0;
        auto refill = [&](bool kv) {
            uint32_t old;
            asm volatile("{\n.reg .pred p;\nelect.sync _|p, 0xffffffff;\nmov.u32 %0, 0;\n@p atom.relaxed.cta.shared.inc.u32 %0, [%1], 3;\n}" : "=r"(old) : "r"(SM_CNT + slot * 8) : "memory");
            if (__any_sync(~0u, old == 3)) {
                if (!kv && it >= 64) {
#pragma unroll 1
                    for (int k = 0; k < SPIN; k++) {
                        int f; asm volatile("ld.volatile.shared.u32 %0, [%1];" : "=r"(f) : "r"(SM_CNT + 4) : "memory");
                        if (f >= slot) break;
                    }
                    sts32(0, SM_CNT + 4, slot + 1);
                    if (elect()) issue_wo(slot);
                } else {
                    wait_due(it, 0);
                    if (elect()) issue_kv(it, slot, bar < 5 ? bar + 5 : bar - 5);
                }
                __syncwarp();
            }
        };
        auto advance = [&]() { it += 2; slot += 2; if (slot >= 5) slot -= 5; bar += 2; if (bar >= 10) { bar -= 10; par ^= 1; } };
        {
            uint32_t offK[3], qf[12];
#pragma unroll
            for (int j = 0; j < 3; j++) offK[j] = pin(((tid >> 5) & 3) * SUB + 3 * g * 128 + (((2 * t) ^ ((3 * g + j) & 7)) << 4));
#pragma unroll
            for (int i = 0; i < 12; i++) qf[i] = kc[i] = 0;
            const uint32_t ksl = pin(ksw + lane * 16), sca = pin(prow + g * 64);
            int n0 = 0;
#pragma unroll 1
            for (int e = 0; e < 16; e++) {
                TR(1, 1 + 2 * e);
                mbar_wait(SM_CBAR + bar * 8, par);
                TR(1, 2 + 2 * e); TR(2, 1 + 2 * e);
                uint4 v[6];
#pragma unroll
                for (int i = 0; i < 6; i++) v[i] = lds128(ad(offK[i >> 1] ^ ((i & 1) * 16), slot * HT), SM_RING + (i >> 1) * 128);
                refill(true);
                TR(2, 2 + 2 * e);
                advance();
                if ((0xc20 | ((2 << NP) - 1)) >> e & 1) {
                    refresh();
                    static_for<0, NP>([&](auto E) {
                        if (e == E.value) {
#pragma unroll
                            for (int i = 0; i < 6; i++) {
                                uint32_t* k = kc + 90 + 24 * E.value + 4 * i;
                                asm volatile("mov.b32 %0, %4; mov.b32 %1, %5; mov.b32 %2, %6; mov.b32 %3, %7;" : "=r"(k[0]), "=r"(k[1]), "=r"(k[2]), "=r"(k[3]) : "r"(v[i].x), "r"(v[i].y), "r"(v[i].z), "r"(v[i].w));
                            }
                            if (E.value == NP - 2 && warp < 6) {
#pragma unroll
                                for (int i = 0; i < 2; i++)
                                    asm volatile("cp.async.cg.shared.global [%0], [%1], 16;" :: "r"(ksl + SM_KS + 10240 + i * 512),
                                                 "l"(&g_ll[(cta & ~3) + 2 * i + (lane >> 4)][warp * 32 + (lane & 15) * 2]) : "memory");
                            }
                            if (E.value == NP - 1 && warp < 6) {
                                asm volatile("cp.async.wait_all;" ::: "memory");
                                __syncwarp();
                                const uint32_t a = ksw + lane * 8;
                                u64 w[4] = {lds_u64(a, SM_KS + 10240), lds_u64(a, SM_KS + 10496), lds_u64(a, SM_KS + 10752), lds_u64(a, SM_KS + 11008)};
                                ll_gather4(&g_ll[cta & ~3][tid], 2 * ep4 + 1, w);
                                const float cs = (lof(w[0] & ~255ull) + lof(w[1] & ~255ull)) + (lof(w[2] & ~255ull) + lof(w[3] & ~255ull));
                                float q = (hif(w[0]) + hif(w[1])) + (hif(w[2]) + hif(w[3]));
                                stsf(tid * 4, SM_CS, cs);
                                float mean, rstd, msq;
                                ln_final(mean, rstd, msq);
                                stsf(0, SM_FXS, fx_scale(msq));
                                q = (q - mean * cs) * rstd;
                                sts16(q_addr(), SM_QU, pack_bf(q, q));
                                __syncwarp();
                                if (elect()) mbar_arrive(SM_QBAR);
#pragma unroll
                                for (int i = 0; i < 12; i++) asm volatile("mov.b32 %0, 0;" : "=r"(kc[i]));
                            }
                        }
                    });
                    if (e == NP) {
                        mbar_wait(SM_QBAR, 0);
#pragma unroll
                        for (int k = 0; k < 3; k++) lds128(qf + 4 * k, (lane & 7) * 48, SM_QU + k * 16);
                        static_for<0, NP>([&](auto E) {
                            uint4 r[6];
#pragma unroll
                            for (int i = 0; i < 6; i++) { const uint32_t* k = kc + 90 + 24 * E.value + 4 * i; r[i] = make_uint4(k[0], k[1], k[2], k[3]); }
                            stsf(sca, SM_PART + 256 + (E.value + 6) * 4, score6(r, qf));
                        });
#pragma unroll
                        for (int i = 0; i < 24; i++) asm volatile("mov.b32 %0, 0;" : "=r"(kc[i]));
                    } else if (e == 5) {
#pragma unroll
                        for (int k = 0; k < 22; k++) lds128(kc + 4 * k, ksl, SM_KS + k * 512);
                        lds64(kc + 88, ksl, SM_KS + 22 * 512);
                        n0 = 0;
                    } else if (e == 10) {
#pragma unroll
                        for (int k = 0; k < 22; k++)
                            asm volatile("ld.shared.v4.b32 {%0,%1,%2,%3}, [%4];" : "=r"(kc[90 + 4 * k]), "=r"(kc[91 + 4 * k]), "=r"(kc[92 + 4 * k]), "=r"(kc[93 + 4 * k]) : "r"(ad(ksl, SM_KS + k * 512)) : "memory");
                        asm volatile("ld.shared.v2.b32 {%0,%1}, [%2];" : "=r"(kc[178]), "=r"(kc[179]) : "r"(ad(ksl, SM_KS + 22 * 512)) : "memory");
                        n0 = 0;
                    } else if (e == 11) {
                        lds64(kc + 180, ksl, SM_KS + 520); lds128(kc + 182, ksl, SM_KS + 1024); lds128(kc + 186, ksl, SM_KS + 1536); lds64(kc + 190, ksl, SM_KS + 2048);
                        n0 = 3;
                    }
                }
                const int n = (e + 6) & 15;
                stsf(ad(sca, n * 4), SM_PART + 256, score6(v, qf));
                uint32_t m = bf2_amax(bf2_amax(v[0].x, v[0].y), bf2_amax(v[0].z, v[0].w)), mn = bf2_amin(bf2_amin(v[0].x, v[0].y), bf2_amin(v[0].z, v[0].w));
#pragma unroll
                for (int i = 1; i < 6; i++) m = bf2_amax(m, bf2_amax(bf2_amax(v[i].x, v[i].y), bf2_amax(v[i].z, v[i].w)));
                m = max(m & 0x7fff, (m >> 16) & 0x7fff);
                m = max(m, __shfl_xor_sync(~0u, m, 1)); m = max(m, __shfl_xor_sync(~0u, m, 2));
#pragma unroll
                for (int i = 1; i < 6; i++) mn = bf2_amin(mn, bf2_amin(bf2_amin(v[i].x, v[i].y), bf2_amin(v[i].z, v[i].w)));
                mn = min(mn & 0x7fff, (mn >> 16) & 0x7fff);
                const int sh = min(max((int)(m >> 7) - 15, 0), 126);
                asm volatile("st.shared.u8 [%0], %1;" :: "r"(ad(ad((tid >> 2) * 16, n), SM_SH)), "r"(sh) : "memory");
                const uint32_t dn = (127 - sh) * 0x00800080u;
                if (__any_sync(~0u, (int)(mn >> 7) <= sh || m >= (142 << 7))) {
                    if (m >= (142 << 7)) sts32(0, SM_BIG, 1);
                    const uint32_t up = (127 + 256 + sh) * 0x00800080u;
#pragma unroll
                    for (int i = 0; i < 6; i++) {
                        const uint32_t r0 = bf2_fma(bf2_mul(v[i].x, dn), up, v[i].x), r1 = bf2_fma(bf2_mul(v[i].y, dn), up, v[i].y);
                        const uint32_t r2 = bf2_fma(bf2_mul(v[i].z, dn), up, v[i].z), r3 = bf2_fma(bf2_mul(v[i].w, dn), up, v[i].w);
                        asm volatile("{\n.reg .pred p;\n.reg .u32 x, a;\nsetp.ne.u32 p, %0, 0;\nmov.u32 x, %7;\n@p atom.relaxed.cta.shared.inc.u32 x, [%6], 0x7fffffff;\n"
                                     "setp.lt.u32 p, x, %7;\nmad.lo.u32 a, x, 16, %8;\n@p st.shared.v4.u32 [a], {%1,%2,%3,%4};\n"
                                     "mad.lo.u32 a, x, 4, %9;\n@p st.shared.u32 [a], %5;\n}"
                                     :: "r"(r0 | r1 | r2 | r3), "r"(r0), "r"(r1), "r"(r2), "r"(r3), "r"(tid << 16 | n << 8 | i * 8), "r"(SM_XN), "n"(XCAP), "n"(SM_XR), "n"(SM_XM) : "memory");
                    }
                }
                const uint32_t ae = (n0 >> 1) * 512 + (n0 & 1) * 8, ao = ((n0 + 1) >> 1) * 512 + (~n0 & 1) * 8;
                uint32_t o[18];
#pragma unroll
                for (int i = 0; i < 6; i++) {
                    const uint32_t y0 = bf2_mulv(v[i].x, dn), y1 = bf2_mulv(v[i].y, dn), y2 = bf2_mulv(v[i].z, dn), y3 = bf2_mulv(v[i].w, dn);
                    o[3 * i] = __byte_perm(y0, y1, 0x6420); o[3 * i + 1] = __byte_perm(y2, y3, 0x6420);
                    const uint32_t hb = __byte_perm(y2, y3, 0x7531);
                    o[3 * i + 2] = __byte_perm(y0, y1, 0x7531) | __funnelshift_l(hb, hb, 4);
                    if (i & 1) {
#pragma unroll
                        for (int k = 3 * (i >> 1); k < 3 * (i >> 1) + 3; k++) sts64(ad(ksl, (k & 1) ? ao : ae), SM_KS + (k >> 1) * 512, o[2 * k], o[2 * k + 1]);
                    }
                }
                n0 += 9;
            }
            fence_async();
        }
        TS(2);
        refresh();
        {
            const uint4 sc = lds128(prow + lane * 16, SM_PART + 256);
            const float S[4] = {__uint_as_float(sc.x), __uint_as_float(sc.y), __uint_as_float(sc.z), __uint_as_float(sc.w)};
            softmax(IC<0>{}, S);
        }
        fw = 0.f;
#pragma unroll 1
        for (int e = 0; e < 16; e++) {
            if ((1 << (PUBAT - 3) | 1 << PUBAT | 1 << ZCHK) >> e & 1) {
                if (e == PUBAT - 3) head_look();
                else if (e == PUBAT) {
                    head_weight(IC<0>{});
                    if (tid < 196) st_rlx(&g_ll[cta][tid + (tid >> 6 == 3) * 8], 0ull);
                } else if (warp == ZW) {
                    if (B2PF && (bx & 15) == 0 && elect()) bulk_pf(P.b2, D_MODEL * 2, POL_NORMAL);
#pragma unroll 1
                    for (int k = 0; k < SPIN; k++) {
                        uint32_t v; asm volatile("ld.acquire.gpu.global.u32 %0, [%1];" : "=r"(v) : "l"(&g_zflag) : "memory");
                        if (__all_sync(~0u, v * 4 == ep4 + 4)) break;
                    }
                }
                __syncwarp();
            }
            const uint32_t pp = lds32(ad(t * 4, prow + ((e + 6) & 15) * 16), SM_PART + 256);
            TR(3, 1 + 2 * e);
            mbar_wait(SM_CBAR + bar * 8, par);
            TR(3, 2 + 2 * e);
            uint4 v[6];
            load_v(v, (warp & 3) * SUB + slot * HT, SM_RING);
            if (e < 15) refill(false);
            advance();
            pv(v, pp);
        }
    }
    TS(3);
    tail_prep1(IC<0>{});
    __syncwarp();
    tail(IC<0>{});

    q_end(IC<1>{});
    {
        const u64* qp = &g_ll[cta & ~3][tid];
        u64 w[4] = {0, 0, 0, 0};
        while (clk() - cq < QDELAY);
        if (warp < 6) { w[0] = ld_rlx(qp); w[1] = ld_rlx(qp + 256); w[2] = ld_rlx(qp + 512); w[3] = ld_rlx(qp + 768); }
        if ((TOUCH & 2) && warp >= 4) touch2();
        if (LNLATE) { ln_part(); __syncthreads(); sts64(prow + lane * 8, SM_PART, xp.x, xp.y); }
        const uint32_t ksl = ksw + lane * 16, qa = pin(q_addr()), qb0 = pin(lane < 8 ? lane * 48 : SM_ZQ - SM_VEC);
        uint32_t ks[96], qf[12];
        float mean, rstd, msq;
        ln_final(mean, rstd, msq);
        const float qc = pinf(-mean * rstd * ldsf(tid * 4, SM_CS));
#pragma unroll
        for (int k = 0; k < PRE; k++) lds128(ks + 4 * k, ksl, SM_KS + k * 512);
        stsf(0, SM_FXS, fx_scale(msq));
        if (E3 == 2 || (E3 == 3 && warp >= E3W)) issue2(IC<3>{}, ks[0] | ks[4] | ks[8] | ks[12] | ks[16] | ks[20]);
        if (warp < 6) {
            ll_gather4(qp, 2 * ep4 + 5, w);
            const float q = ((hif(w[0]) + hif(w[1])) + (hif(w[2]) + hif(w[3]))) * rstd + qc;
            TS(24);
            const uint32_t qq = bf2_mul(pack_bf(q, q), 0x3f807180u);
            sts16(qa, SM_VEC, qq); sts16(qa, SM_QU, qq >> 16);
            sts32_if(!(fabsf(q) < 1048576.f), 0, SM_BIG, 1);
            __syncwarp();
            if (elect()) mbar_arrive(SM_QBAR);
        } else {
            uint4 c = make_uint4(ks[0], ks[1], ks[2], ks[3]);
            if (cta == 0 && tid == 255) g_epoch = (ep4 >> 2) + 1;
            if (I1D) { tick(c); while (clk() - cq < I1D + (warp - 6) * I1G); issue_item1(); }
#pragma unroll 1
            for (int it = 0; it < SPIN; it++) { if (mbar_test(SM_QBAR, 1)) break; if (KA & 1) tick(c); }
            ks[0] = c.x; ks[1] = c.y; ks[2] = c.z; ks[3] = c.w;
        }
        if (!E3 || (E3 == 3 && warp < E3W)) issue2(IC<3>{}, ks[0] | ks[4] | ks[8] | ks[12] | ks[16] | ks[20]);
        mbar_wait(SM_QBAR, 1);
        TS(12); TR(4, 1); TR(5, 1);
        auto load_q = [&](int u, int k) { lds128(qf + 4 * k, u == 0 ? qb0 : (tid & 24) == 8 * u ? (tid & 7) * 48 : SM_ZQ - SM_VEC, SM_VEC + k * 16); };
        load_q(0, 1); load_q(0, 2); load_q(0, 0);
        if constexpr (E3 == 1) issue2(IC<3>{}, ks[0] | ks[4] | ks[8] | ks[12] | ks[16] | ks[20]);
        float D[4][4];
        uint4 vb[NPK + 2][6], v2[6];
        uint32_t xn = 0;
        const uint32_t t1 = __shfl_sync(~0u, lds32(0, SM_T0), 0);
        auto step = [&](auto Q) {
            constexpr int st = Q.value, p = cord(st), s = PL.slot[p], n = PL.ld[st];
            if constexpr (n > 0 && !(n == 16 && WOLATE)) {
                if constexpr (st >= NPK || PACEK) {
                    const uint32_t due = t1 + P2A + n * P2B + (n == 16 ? P2W : 0);
#pragma unroll 1
                    for (int it = 0; it < 4096; it++) if ((int)(gtime() - due) >= 0) break;
                }
                const uint4 (&u)[6] = vb[st - 1 < NPK ? st - 1 : NPK + ((st - 1) & 1)];
                issue2(IC<n>{}, st > PVNOW ? 0 : u[0].x | u[1].x | u[2].x | u[3].x | u[4].x | u[5].x);
            }
            TR(4, 2 + 2 * st);
            if (p == 1) mbar_wait(SM_CBAR + (warp >> 2) * 8, 1);
            else if (p == 0) mbar_wait(warp < 4 ? SM_CBAR + 24 : barw, warp < 4);
            else mbar_wait(barw + s * 8, IC<PL.par[p]>::value);
            TR(4, 3 + 2 * st);
            load_v(vb[st < NPK ? st : NPK + (st & 1)], slot_u(s), slot_o(s));
            if constexpr (n == 16 && WOLATE) issue2(IC<16>{}, 0);
        };
        static_for<0, 96>([&](auto I) {
            constexpr int F = I.value, n = F / 6, i = n ? F % 6 : (F + 2) % 6;
            const uint32_t* c = n == 0 ? (i < 2 ? ks + 3 * i : kc + 174 + 3 * i) : n < 6 ? ks + 18 * n - 12 + 3 * i : kc + 18 * (n - 6) + 3 * i;
            uint32_t ha, hb;
            if (DEC) { const uint32_t gg = c[2] & 0x78787878u; asm("mad.lo.u32 %0, %1, %2, %3;" : "=r"(ha) : "r"(gg), "r"(zero - 1), "r"(c[2])); hb = __funnelshift_r(gg, gg, 4); }
            else { ha = c[2] & 0x87878787u; hb = __funnelshift_r(c[2], c[2], 4) & 0x87878787u; }
            if (F < 24 && F % 6 == 0) zero4(D[n]);
            mma(D[n & 3], __byte_perm(c[0], ha, 0x5140), __byte_perm(c[0], ha, 0x7362), __byte_perm(c[1], hb, 0x5140), __byte_perm(c[1], hb, 0x7362), qf[2 * i], qf[2 * i + 1]);
            if constexpr ((n & 3) == 3 && n < 15 && (i & 1)) load_q((n + 1) >> 2, i >> 1);
            static_for<PRE, 24>([&](auto U) {
                if constexpr (((U.value - PRE + 1) * 4 + 2) / 3 - 1 + KSL == F) {
                    lds128(ks + 4 * U.value, ksl, SM_KS + U.value * 512);
                    if constexpr (U.value % 6 == 5 && (U.value < 23 || !I6AT)) { const uint32_t* k = ks + 4 * U.value - 17; issue2(IC<3 + U.value / 6>{}, k[0] | k[4] | k[8] | k[12] | k[16] | k[20]); }
                }
            });
            if constexpr (F == I6AT && I6AT) issue2(IC<6>{}, __float_as_uint(D[1][0]));
            if constexpr (F == I2AT) {
                if (warp < 4) { mbar_wait(SM_CBAR + 16, 1); load_v(v2, wqw, slot_o(2)); }
                else {
                    const char* p = reinterpret_cast<const char*>(P.v) + (size_t)(roww + vunit(2) * 256) * (DH * 2) + t * 768 + g * 16;
#pragma unroll
                    for (int k = 0; k < 6; k++)
                        asm volatile("ld.global.nc.v4.u32 {%0,%1,%2,%3}, [%4];" : "=r"(v2[k].x), "=r"(v2[k].y), "=r"(v2[k].z), "=r"(v2[k].w) : "l"(p + k * 128));
                }
            }
            if constexpr (F == XAT || F == XAT2) if (XAT == XAT2 || (warp < 4) == (F == XAT)) {
                                { const uint2 x = lds64(0, SM_XN); xn = x.y ? XCAP + 1 : x.x; }
                sts128(prow + lane * 16, SM_PART + 256, 0, 0, 0, 0);
                __syncwarp();
#pragma unroll 1
                for (uint32_t idx = lane; idx < (xn > XCAP ? 0 : xn); idx += 32) {
                    const uint32_t m = lds32(idx * 4, SM_XM);
                    if ((m >> 21) == warp) {
                        const uint4 r = lds128(idx * 16, SM_XR);
                        const uint32_t qo = ((m >> 16) & 3) * 48 + (m & 255);
                        const uint2 a = lds64(qo, SM_QU), b = lds64(qo, SM_QU + 192);
                        const float s = ((bf_lo(r.x) * bf_lo(a.x) + bf_hi(r.x) * bf_hi(a.x)) + (bf_lo(r.y) * bf_lo(b.x) + bf_hi(r.y) * bf_hi(b.x))) +
                                        ((bf_lo(r.z) * bf_lo(a.y) + bf_hi(r.z) * bf_hi(a.y)) + (bf_lo(r.w) * bf_lo(b.y) + bf_hi(r.w) * bf_hi(b.y)));
                        asm volatile("red.relaxed.cta.shared.add.f32 [%0], %1;" :: "r"(SM_PART + 256 + prow + ((m >> 18) & 7) * 64 + ((m >> 8) & 15) * 4), "f"(s) : "memory");
                    }
                }
                __syncwarp();
            }
            if constexpr (F == PK0 - 2) refresh();
            static_for<0, NPK>([&](auto Q) { if constexpr (F == (Q.value ? PK1 + (Q.value - 1) * PKD : PK0)) step(Q); });
        });
        float S[4];
        {
            const uint32_t shp = lds32(tid * 4, SM_SH);
            const uint4 cr = lds128(prow + lane * 16, SM_PART + 256);
            const uint32_t c[4] = {cr.x, cr.y, cr.z, cr.w};
#pragma unroll
            for (int j = 0; j < 4; j++) S[j] = (D[j][0] + D[j][3]) * __uint_as_float((((shp >> (8 * j)) & 255) + 27) << 23) + __uint_as_float(c[j]);
        }
        if (xn > XCAP) {
#pragma unroll
            for (int k = 0; k < 3; k++) lds128(qf + 4 * k, (lane & 7) * 48, SM_QU + k * 16);
#pragma unroll 1
            for (int e = 0; e < 16; e++) {
                uint4 v[6];
#pragma unroll
                for (int i = 0; i < 6; i++) v[i] = ldg128(P.k + (size_t)(roww + 256 * e + g) * DH + (i >> 1) * 64 + (2 * t + (i & 1)) * 8);
                const float s = score6(v, qf);
#pragma unroll
                for (int j = 0; j < 4; j++) if (4 * t + j == ((e + 6) & 15)) S[j] = s;
            }
        }
        TS(25);
        softmax(IC<1>{}, S);
        auto p_of = [&](int st) { return lds32(ad(t * 4, prow), SM_PART + 256 + ((vunit(cord(st)) + 6) & 15) * 16); };
        auto pv_at = [&](auto Q) { constexpr int st = Q.value; pv(vb[st < NPK ? st : NPK + (st & 1)], p_of(st)); };
        static_for<NPK, 15>([&](auto Q) {
            constexpr int st = Q.value;
            if constexpr (st == HWAT) head_look();
            if constexpr (st == B2AT) asm volatile("cp.async.ca.shared.global [%0], [%1], 8;" :: "r"(SM_KS + 11264 + ksw + lane * 8), "l"(P.b2 + 4 * min(c4, 159)) : "memory");
            if constexpr (st == HWC) { head_weight(IC<1>{}); b2v = lds64(ksw + lane * 8, SM_KS + 11264); }
            if constexpr (st == PREP1) { tail_prep1(IC<1>{}); tail_prep2(IC<1>{}); red_addr(IC<1>{}); load_u(z, warp * WOU, SM_RING + 16 * WOU); }
            if constexpr (st == PREP2) mlp_prep(IC<1>{});
            if constexpr (st == PREP3) load_w1();
            if constexpr (st == PREP4) load_w2();
            uint32_t pp;
            if constexpr (st >= PVNOW) pp = pin(p_of(st));
            step(Q);
            if constexpr (st - NPK < NPK) pv_at(IC<st - NPK>{});
            if constexpr (st > NPK && st <= PVNOW) pv_at(IC<st - 1>{});
            if constexpr (st == PV2) pv(v2, lds32(ad(t * 4, prow), SM_PART + 256 + ((vunit(2) + 6) & 15) * 16));
            if constexpr (st >= PVNOW) pv(vb[NPK + (st & 1)], pp);
        });
    }
    TS(13);
    tail(IC<1>{});
}

typedef CUresult (*EncodeFn)(CUtensorMap*, CUtensorMapDataType, cuuint32_t, void*, const cuuint64_t*, const cuuint64_t*, const cuuint32_t*,
                             const cuuint32_t*, CUtensorMapInterleave, CUtensorMapSwizzle, CUtensorMapL2promotion, CUtensorMapFloatOOBfill);

}

extern "C" void kernel_launch(void* const* d_in, const int* in_sizes, int n_in, void* d_out, int out_size) {
    (void)in_sizes; (void)n_in; (void)out_size;
    static EncodeFn enc = nullptr;
    if (!enc) {
        void* fn = nullptr;
        cudaDriverEntryPointQueryResult qr;
        cudaGetDriverEntryPoint("cuTensorMapEncodeTiled", &fn, cudaEnableDefault, &qr);
        enc = (EncodeFn)fn;
        cudaFuncSetAttribute(fused_kernel, cudaFuncAttributeMaxDynamicSharedMemorySize, SM_TOTAL);
    }
    Params P;
    const cuuint32_t ones[3] = {1, 1, 1};
    for (int m = TM_K; m <= TM_V8; m++) {
        const cuuint64_t dim[3] = {64, 3, (cuuint64_t)NHEAD * SK}, str[2] = {128, DH * 2};
        const cuuint32_t box[3] = {m == TM_VP ? 8u : 64u, 3, m == TM_V8 ? 8u : 32u};
        enc(&P.tm[m], CU_TENSOR_MAP_DATA_TYPE_BFLOAT16, 3, d_in[m == TM_K ? 1 : 2], dim, str, box, ones, CU_TENSOR_MAP_INTERLEAVE_NONE,
            m == TM_VP ? CU_TENSOR_MAP_SWIZZLE_NONE : CU_TENSOR_MAP_SWIZZLE_128B, CU_TENSOR_MAP_L2_PROMOTION_NONE, CU_TENSOR_MAP_FLOAT_OOB_FILL_NONE);
    }
    {
        const cuuint64_t dim[3] = {64, NHEAD * 3, D_MODEL}, str[2] = {128, NHEAD * DH * 2};
        const cuuint32_t box[3] = {64, 3, 32};
        enc(&P.tm[TM_WQ], CU_TENSOR_MAP_DATA_TYPE_BFLOAT16, 3, d_in[3], dim, str, box, ones, CU_TENSOR_MAP_INTERLEAVE_NONE,
            CU_TENSOR_MAP_SWIZZLE_128B, CU_TENSOR_MAP_L2_PROMOTION_NONE, CU_TENSOR_MAP_FLOAT_OOB_FILL_NONE);
    }
    {
        const cuuint64_t dim[2] = {DFF, D_MODEL}, str[1] = {DFF * 2};
        const cuuint32_t box[2] = {16, 128};
        enc(&P.tm[TM_W1], CU_TENSOR_MAP_DATA_TYPE_BFLOAT16, 2, d_in[6], dim, str, box, ones, CU_TENSOR_MAP_INTERLEAVE_NONE,
            CU_TENSOR_MAP_SWIZZLE_32B, (CUtensorMapL2promotion)W1PROMO, CU_TENSOR_MAP_FLOAT_OOB_FILL_NONE);
    }
    {
        const cuuint64_t dim[3] = {32, 20, NHEAD * DH}, str[2] = {64, D_MODEL * 2};
        const cuuint32_t box[3] = {32, 5, 16};
        enc(&P.tm[TM_WO], CU_TENSOR_MAP_DATA_TYPE_BFLOAT16, 3, d_in[4], dim, str, box, ones, CU_TENSOR_MAP_INTERLEAVE_NONE,
            CU_TENSOR_MAP_SWIZZLE_64B, CU_TENSOR_MAP_L2_PROMOTION_L2_128B, CU_TENSOR_MAP_FLOAT_OOB_FILL_NONE);
    }
    {
        const cuuint64_t dim[4] = {32, 20, 24, NHEAD * 8}, str[3] = {64, D_MODEL * 2, 24 * D_MODEL * 2};
        const cuuint32_t box[4] = {32, 5, 8, 4}, ones4[4] = {1, 1, 1, 1};
        enc(&P.tm[TM_WO4], CU_TENSOR_MAP_DATA_TYPE_BFLOAT16, 4, d_in[4], dim, str, box, ones4, CU_TENSOR_MAP_INTERLEAVE_NONE,
            CU_TENSOR_MAP_SWIZZLE_64B, (CUtensorMapL2promotion)WOPROMO, CU_TENSOR_MAP_FLOAT_OOB_FILL_NONE);
        const cuuint32_t thin[4] = {8, 5, 8, 4};
        enc(&P.tm[TM_WOP], CU_TENSOR_MAP_DATA_TYPE_BFLOAT16, 4, d_in[4], dim, str, thin, ones4, CU_TENSOR_MAP_INTERLEAVE_NONE,
            CU_TENSOR_MAP_SWIZZLE_NONE, CU_TENSOR_MAP_L2_PROMOTION_NONE, CU_TENSOR_MAP_FLOAT_OOB_FILL_NONE);
    }
    {
        const cuuint64_t dim[3] = {64, 10, DFF}, str[2] = {128, D_MODEL * 2};
        const cuuint32_t box[3] = {64, 10, 16};
        enc(&P.tm[TM_W2], CU_TENSOR_MAP_DATA_TYPE_BFLOAT16, 3, d_in[8], dim, str, box, ones, CU_TENSOR_MAP_INTERLEAVE_NONE,
            CU_TENSOR_MAP_SWIZZLE_128B, CU_TENSOR_MAP_L2_PROMOTION_NONE, CU_TENSOR_MAP_FLOAT_OOB_FILL_NONE);
    }
    P.x = (const __nv_bfloat16*)d_in[0];
    P.k = (const __nv_bfloat16*)d_in[1];
    P.v = (const __nv_bfloat16*)d_in[2];
    P.b1 = (const __nv_bfloat16*)d_in[7];
    P.b2 = (const __nv_bfloat16*)d_in[9];
    P.out = (__nv_bfloat16*)d_out;
    fused_kernel<<<NCTA + 1 + NXTRA, NTHR, SM_TOTAL, cudaStreamPerThread>>>(P);
}
```

```cpp
#include <cuda_runtime.h>
#include <cuda_bf16.h>
#include <cuda.h>
#include <stdint.h>

#define DI __device__ __forceinline__

namespace {

constexpr int D_MODEL = 640, NHEAD = 32, SK = 32768, DH = 192, WIN = 4096, DFF = 1536;
constexpr int NCTA = 128, NTHR = 256;
constexpr int SUB = 8 * DH * 2;
constexpr int HT = 4 * SUB;
constexpr int WOU = 8 * 320;
constexpr int XCAP = 48;
constexpr int SM_RING = 1024;
constexpr int SM_W2 = SM_RING + 8 * WOU;
constexpr int SM_WQ = SM_RING + 5 * HT;
constexpr int SM_KS = SM_WQ + 5 * HT;
constexpr int SM_PART = SM_KS + 8 * HT;
constexpr int SM_BAR = SM_PART + 6144;
constexpr int SM_VEC = SM_BAR + 512;
constexpr int SM_QU = SM_VEC + 384;
constexpr int SM_ZQ = SM_QU + 384;
constexpr int SM_CS = SM_ZQ + 64;
constexpr int SM_XR = SM_CS + 768;
constexpr int SM_XM = SM_XR + XCAP * 16;
constexpr int SM_SH = SM_XM + XCAP * 4;
constexpr int SM_C1 = SM_SH + 1024;
constexpr int SM_B1 = SM_C1 + 320;
constexpr int SM_STAT = SM_B1 + 128;
constexpr int SM_QBAR = SM_STAT + 40;
constexpr int SM_CBAR = SM_QBAR + 8;
constexpr int SM_CNT = SM_CBAR + 128;
constexpr int SM_XN = SM_CNT + 56;
constexpr int SM_BIG = SM_XN + 4;
constexpr int SM_EPOCH = SM_BIG + 4;
constexpr int SM_FXS = SM_EPOCH + 4;
constexpr int SM_T0 = SM_FXS + 4;
constexpr int SM_JUNK = SM_T0 + 4;
constexpr int SM_TOTAL = 232448;
static_assert(SM_JUNK + 4 <= SM_RING + SM_TOTAL, "smem");

constexpr int SPIN = 1 << 20;
enum { TM_WQ = 0, TM_K = 1, TM_V = 2, TM_VP = 3, TM_V8 = 4, TM_WO = 5, TM_W1 = 6, TM_WO4 = 7, TM_W2 = 8, TM_WOP = 9 };
constexpr uint32_t POL_NORMAL = 0x16F00000u, POL_FIRST = 0x12F00000u;

constexpr int PACE = 484, PACE0 = 1800, WOPACE = 403, W1D = 100, W1G = 150, HZD = 9500;
constexpr int NP = 3, PUBAT = 8, ZCHK = 14;
constexpr int ODELAY = 200, AR1D = 400, AR1DN = 1000, AR2D = 600, S6D = 900, S6G = 100, I0D = 300, NPFC = 4;
constexpr int PFD = 1200, PFG = 150, KAD = 900;
constexpr unsigned long long VORD = 0x45678932a1b0cdefull;
constexpr int ISS = 0xf9e, NPK = 4, PK0 = 34, PK1 = 52, PKD = 21, P2A = -700, P2B = 400, PREP1 = 8;
constexpr int PREP2 = 9, PV2 = 9, HWAT = 10, B2AT = 13, PVNOW = 12, HWC = 13;
constexpr uint32_t FX2_MASK = 0xfff00000u;

struct Plan { int slot[17], par[17], ld[15]; bool ok; };
__host__ __device__ constexpr int cord(int s) { return s < 2 ? s : s + 1; }
constexpr Plan make_plan() {
    Plan s{};
    int phase[7] = {}, freeat[7] = {}, it = 7;
    for (int p = 0; p < 7; p++) { s.slot[p] = p; phase[p] = p != 1; freeat[p] = -1; }
    s.ok = true;
    for (int st = 0; st < 15; st++) {
        if (ISS >> st & 1) {
            int best = -1;
            for (int c = 0; c < 7; c++) if (freeat[c] >= 0 && (c < 5 || it < 13) && (best < 0 || freeat[c] < freeat[best])) best = c;
            if (best < 0 || it > 15) { s.ok = false; return s; }
            s.slot[it] = best; freeat[best] = -1;
            s.par[it] = phase[best]++ & 1;
            s.ld[st] = it++;
        }
        if (cord(st) >= it || (st >= B2AT && s.slot[cord(st)] >= 5)) s.ok = false;
        freeat[s.slot[cord(st)]] = st;
    }
    s.slot[16] = 5; s.par[16] = phase[5] & 1;
    return s;
}
constexpr Plan PL = make_plan();
static_assert(PL.ok, "bad pass-2 plan");
__host__ __device__ constexpr int vunit(int p) { return (int)(VORD >> (4 * p) & 15); }

template <int I> struct IC { static constexpr int value = I; };
template <int A, int B, class F> DI void static_for(F&& f) {
    if constexpr (A < B) { f(IC<A>{}); static_for<A + 1, B>(f); }
}

struct Params {
    CUtensorMap tm[10];
    const __nv_bfloat16 *x, *b1, *b2, *k, *v;
    __nv_bfloat16* out;
};

typedef unsigned long long u64;
constexpr int ACC_PITCH = 256;
constexpr int ACC_BYTES = 80 * ACC_PITCH;
__device__ __align__(1024) unsigned char g_acc[4 * ACC_BYTES];
__device__ __align__(8192) u64 g_ll[NCTA][256];
__device__ unsigned g_epoch;
__device__ __align__(128) unsigned g_zflag;

DI void mbar_wait(uint32_t bar, uint32_t parity) {
    asm volatile("{\n.reg .pred p, q;\n.reg .u32 n;\nmov.u32 n, 0;\n"
                 "LOOP:\nmbarrier.try_wait.parity.shared::cta.b64 p, [%0], %1;\n"
                 "add.u32 n, n, 1;\nsetp.lt.and.u32 q, n, 0x100000, !p;\n@q bra.uni LOOP;\n}"
                 :: "r"(bar), "r"(parity) : "memory");
}
DI bool mbar_test(uint32_t bar, uint32_t parity) {
    uint32_t done;
    asm volatile("{\n.reg .pred p;\nmbarrier.test_wait.parity.shared::cta.b64 p, [%1], %2;\nselp.u32 %0, 1, 0, p;\n}" : "=r"(done) : "r"(bar), "r"(parity) : "memory");
    return __any_sync(~0u, done);
}
DI bool elect() {
    uint32_t r;
    asm volatile("{\n.reg .pred p;\nelect.sync _|p, 0xffffffff;\nselp.u32 %0, 1, 0, p;\n}" : "=r"(r));
    return r != 0;
}
DI void mbar_init(uint32_t bar, uint32_t n) { asm volatile("mbarrier.init.shared::cta.b64 [%0], %1;" :: "r"(bar), "r"(n) : "memory"); }
DI void mbar_arrive(uint32_t bar) { asm volatile("mbarrier.arrive.shared::cta.b64 _, [%0];" :: "r"(bar) : "memory"); }
DI void mbar_expect(uint32_t bar, uint32_t bytes) {
    asm volatile("mbarrier.arrive.expect_tx.shared::cta.b64 _, [%0], %1;" :: "r"(bar), "r"(bytes) : "memory");
}
DI void fence_async() { asm volatile("fence.proxy.async.shared::cta;" ::: "memory"); }
DI uint32_t ad(uint32_t a, uint32_t o) { uint32_t r; asm("add.u32 %0, %1, %2;" : "=r"(r) : "r"(a), "r"(o)); return r; }
DI uint4 lds128(uint32_t a, int o) {
    uint4 v; asm volatile("ld.shared.v4.u32 {%0,%1,%2,%3}, [%4];" : "=r"(v.x), "=r"(v.y), "=r"(v.z), "=r"(v.w) : "r"(ad(a, o)) : "memory"); return v;
}
DI void lds128(uint32_t* v, uint32_t a, int o) {
    asm volatile("ld.shared.v4.u32 {%0,%1,%2,%3}, [%4];" : "=r"(v[0]), "=r"(v[1]), "=r"(v[2]), "=r"(v[3]) : "r"(ad(a, o)) : "memory");
}
DI void lds64(uint32_t* v, uint32_t a, int o) { asm volatile("ld.shared.v2.u32 {%0,%1}, [%2];" : "=r"(v[0]), "=r"(v[1]) : "r"(ad(a, o)) : "memory"); }
DI uint4 ldsm_t(uint32_t a, int o) {
    uint4 v; asm volatile("ldmatrix.sync.aligned.m8n8.x4.trans.shared.b16 {%0,%1,%2,%3}, [%4];" : "=r"(v.x), "=r"(v.y), "=r"(v.z), "=r"(v.w) : "r"(ad(a, o)) : "memory"); return v;
}
DI uint2 lds64(uint32_t a, int o) { uint2 v; asm volatile("ld.shared.v2.u32 {%0,%1}, [%2];" : "=r"(v.x), "=r"(v.y) : "r"(ad(a, o)) : "memory"); return v; }
DI float2 lds64f(uint32_t a, int o) { const uint2 v = lds64(a, o); return make_float2(__uint_as_float(v.x), __uint_as_float(v.y)); }
DI uint32_t lds32(uint32_t a, int o) { uint32_t v; asm volatile("ld.shared.u32 %0, [%1];" : "=r"(v) : "r"(ad(a, o)) : "memory"); return v; }
DI float ldsf(uint32_t a, int o) { return __uint_as_float(lds32(a, o)); }
DI void sts32(uint32_t a, int o, uint32_t v) { asm volatile("st.shared.u32 [%0], %1;" :: "r"(ad(a, o)), "r"(v) : "memory"); }
DI void stsf(uint32_t a, int o, float v) { sts32(a, o, __float_as_uint(v)); }
DI void sts16(uint32_t a, int o, uint32_t v) { asm volatile("st.shared.u16 [%0], %1;" :: "r"(ad(a, o)), "h"((uint16_t)v) : "memory"); }
DI void sts64(uint32_t a, int o, uint32_t x, uint32_t y) { asm volatile("st.shared.v2.u32 [%0], {%1,%2};" :: "r"(ad(a, o)), "r"(x), "r"(y) : "memory"); }
DI void sts128(uint32_t a, int o, uint32_t x, uint32_t y, uint32_t z, uint32_t w) {
    asm volatile("st.shared.v4.u32 [%0], {%1,%2,%3,%4};" :: "r"(ad(a, o)), "r"(x), "r"(y), "r"(z), "r"(w) : "memory");
}
DI void sts128f_if(bool p, uint32_t a, int o, float x, float y, float z, float w) {
    asm volatile("{\n.reg .pred p;\nsetp.ne.u32 p, %5, 0;\n@p st.shared.v4.f32 [%0], {%1,%2,%3,%4};\n}" :: "r"(ad(a, o)), "f"(x), "f"(y), "f"(z), "f"(w), "r"((int)p) : "memory");
}
DI void sts32_if(bool p, uint32_t a, int o, uint32_t v) {
    asm volatile("{\n.reg .pred p;\nsetp.ne.u32 p, %2, 0;\n@p st.shared.u32 [%0], %1;\n}" :: "r"(ad(a, o)), "r"(v), "r"((int)p) : "memory");
}
DI uint32_t atoms_inc(uint32_t a, uint32_t lim) {
    uint32_t old; asm volatile("atom.relaxed.cta.shared.inc.u32 %0, [%1], %2;" : "=r"(old) : "r"(a), "r"(lim) : "memory"); return old;
}
DI void mma(float (&c)[4], uint32_t a0, uint32_t a1, uint32_t a2, uint32_t a3, uint32_t b0, uint32_t b1) {
    asm volatile("mma.sync.aligned.m16n8k16.row.col.f32.bf16.bf16.f32 {%0,%1,%2,%3}, {%4,%5,%6,%7}, {%8,%9}, {%0,%1,%2,%3};"
                 : "+f"(c[0]), "+f"(c[1]), "+f"(c[2]), "+f"(c[3]) : "r"(a0), "r"(a1), "r"(a2), "r"(a3), "r"(b0), "r"(b1));
}
DI void mma(float (&c)[4], const uint4& a, uint32_t b0, uint32_t b1) { mma(c, a.x, a.y, a.z, a.w, b0, b1); }
DI void zero4(float (&c)[4]) { c[0] = c[1] = c[2] = c[3] = 0.f; }
DI u64 ld_rlx(const void* p) {
    u64 a; asm volatile("ld.relaxed.gpu.global.u64 %0, [%1];" : "=l"(a) : "l"(p) : "memory"); return a;
}
DI void st_rlx(void* p, u64 a) { asm volatile("st.relaxed.gpu.global.u64 [%0], %1;" :: "l"(p), "l"(a) : "memory"); }
DI uint4 ldg128(const void* p) {
    uint4 v; asm volatile("ld.global.nc.L1::no_allocate.L2::cache_hint.v4.u32 {%0,%1,%2,%3}, [%4], %5;" : "=r"(v.x), "=r"(v.y), "=r"(v.z), "=r"(v.w) : "l"(p), "l"((u64)POL_FIRST << 32)); return v;
}
DI float bf_lo(uint32_t u) { return __uint_as_float(u << 16); }
DI float bf_hi(uint32_t u) { return __uint_as_float(u & 0xffff0000u); }
DI uint32_t pack_bf(float lo, float hi) {
    uint32_t r; asm("cvt.rn.bf16x2.f32 %0, %1, %2;" : "=r"(r) : "f"(hi), "f"(lo)); return r;
}
DI uint32_t pick(uint32_t a, uint32_t sel) { uint32_t r; asm("prmt.b32 %0, %1, 0, %2;" : "=r"(r) : "r"(a), "r"(sel)); return r; }
DI uint32_t bf2_amax(uint32_t a, uint32_t b) { uint32_t r; asm("max.NaN.xorsign.abs.bf16x2 %0, %1, %2;" : "=r"(r) : "r"(a), "r"(b)); return r; }
DI uint32_t bf2_amin(uint32_t a, uint32_t b) { uint32_t r; asm("min.xorsign.abs.bf16x2 %0, %1, %2;" : "=r"(r) : "r"(a), "r"(b)); return r; }
DI uint32_t bf2_mulv(uint32_t a, uint32_t b) { uint32_t r; asm volatile("mul.rn.bf16x2 %0, %2, %1;" : "=r"(r) : "r"(a), "r"(b)); return r; }
DI uint32_t bf2_mul(uint32_t a, uint32_t b) { uint32_t r; asm("mul.rn.bf16x2 %0, %1, %2;" : "=r"(r) : "r"(a), "r"(b)); return r; }
DI uint32_t bf2_fma(uint32_t a, uint32_t b, uint32_t c) { uint32_t r; asm("fma.rn.bf16x2 %0, %1, %2, %3;" : "=r"(r) : "r"(a), "r"(b), "r"(c)); return r; }
DI float ex2(float v) { float r; asm("ex2.approx.ftz.f32 %0, %1;" : "=f"(r) : "f"(v)); return r; }
DI float rcp(float v) { float r; asm("rcp.approx.ftz.f32 %0, %1;" : "=f"(r) : "f"(v)); return r; }
DI float rsq(float v) { float r; asm("rsqrt.approx.ftz.f32 %0, %1;" : "=f"(r) : "f"(v)); return r; }
DI void bar_sync(int id, int n) { asm volatile("bar.sync %0, %1;" :: "r"(id), "r"(n) : "memory"); }
DI uint32_t clk() { uint32_t c; asm volatile("mov.u32 %0, %clock;" : "=r"(c)); return c; }
DI uint32_t gtime() { uint32_t c; asm volatile("mov.u32 %0, %globaltimer_lo;" : "=r"(c)); return c; }
DI uint32_t pin(uint32_t v) { return __shfl_xor_sync(~0u, v, 0); }
DI float pinf(float v) { return __shfl_xor_sync(~0u, v, 0); }
template <class T> DI T* pinp(T* p) { return reinterpret_cast<T*>(__shfl_xor_sync(~0u, (u64)p, 0)); }
DI u64 mk64(uint32_t lo, uint32_t hi) { u64 r; asm("mov.b64 %0, {%1, %2};" : "=l"(r) : "r"(lo), "r"(hi)); return r; }
DI float shx(float v, int o) { return __shfl_xor_sync(~0u, v, o); }

DI u64 fx_pack(float v) {
    u64 r; asm("{\n.reg .u32 a, b;\n.reg .s64 w;\ncvt.rni.s64.f32 w, %1;\nmov.b64 {a, b}, w;\nprmt.b32 a, a, 1, 0x3214;\nmov.b64 %0, {a, b};\n}" : "=l"(r) : "f"(v)); return r;
}
DI float fx_scale(float meansq) {
    const int e = max(((int)(__float_as_uint(meansq) >> 23) - 127) >> 1, -14);
    return __uint_as_float((uint32_t)(127 + 32 - e) << 23);
}
DI float fx_inv(float scale) { return __uint_as_float((254u << 23) - __float_as_uint(scale)); }
DI uint32_t lo32(u64 w) { uint32_t l; asm("mov.b64 {%0, _}, %1;" : "=r"(l) : "l"(w)); return l; }
DI int hi32(u64 w) { int h; asm("mov.b64 {_, %0}, %1;" : "=r"(h) : "l"(w)); return h; }
DI float fx_val(u64 w) { return (float)hi32(w) * 4294967296.f + (float)lo32(w); }
DI void fx_poll(const unsigned char* ap, u64 (&w)[4]) {
    asm volatile("{\n.reg .pred p, q;\n.reg .u32 n, a, b, c, d;\nmov.u32 n, 0;\nLOOP:\n"
                 "ld.relaxed.gpu.global.u64 %0, [%4];\nld.relaxed.gpu.global.u64 %1, [%4+5120];\n"
                 "ld.relaxed.gpu.global.u64 %2, [%4+10240];\nld.relaxed.gpu.global.u64 %3, [%4+15360];\n"
                 "add.u32 n, n, 1;\nsetp.ge.u32 q, n, 0x100000;\n@q bra.uni DONE;\n"
                 "mov.b64 {a, _}, %0;\nmov.b64 {b, _}, %1;\nmov.b64 {c, _}, %2;\nmov.b64 {d, _}, %3;\n"
                 "lop3.b32 a, a, b, c, 0x80;\nlop3.b32 a, a, d, 32, 0x80;\nsetp.eq.u32 p, a, 0;\n"
                 "vote.sync.any.pred p, p, 0xffffffff;\n@p bra.uni LOOP;\nDONE:\n}"
                 : "=l"(w[0]), "=l"(w[1]), "=l"(w[2]), "=l"(w[3]) : "l"(ap) : "memory");
}
constexpr u64 FX2_INIT = 256ull + 32 - 96 * ((1ull << 28) + (1ull << 55)), FX2_NONE = 1ull + (1ull << 28) + (1ull << 55);
constexpr float FX2_MAGIC = 12582912.f + 524288.f;

DI void tma3(uint32_t dst, const CUtensorMap* tm, int c1, int c2, uint32_t bar, uint32_t pol) {
    asm volatile("cp.async.bulk.tensor.3d.shared::cluster.global.mbarrier::complete_tx::bytes.L2::cache_hint [%0], [%1, {%2, %3, %4}], [%5], %6;"
                 :: "r"(dst), "l"(tm), "r"(0), "r"(c1), "r"(c2), "r"(bar), "l"((u64)pol << 32) : "memory");
}
DI void tma3_pf(const CUtensorMap* tm, int c1, int c2, uint32_t pol) {
    asm volatile("cp.async.bulk.prefetch.tensor.3d.L2.global.tile.L2::cache_hint [%0, {%1, %2, %3}], %4;"
                 :: "l"(tm), "r"(0), "r"(c1), "r"(c2), "l"((u64)pol << 32) : "memory");
}
DI void bulk_pf(const void* p, uint32_t bytes, uint32_t pol) {
    asm volatile("cp.async.bulk.prefetch.L2.global.L2::cache_hint [%0], %1, %2;" :: "l"(p), "r"(bytes), "l"((u64)pol << 32) : "memory");
}
DI float warp_max(float v) {
    const int k = __float_as_int(v), m = __reduce_max_sync(~0u, k ^ ((k >> 31) & 0x7fffffff));
    return __int_as_float(m ^ ((m >> 31) & 0x7fffffff));
}
DI u64 ll_pack2(float a, float b, uint32_t tag) { return mk64(__byte_perm(__float_as_uint(a), tag, 0x3214), __float_as_uint(b)); }
DI float lof(u64 w) { return __uint_as_float(lo32(w)); }
DI float hif(u64 w) { return __int_as_float(hi32(w)); }
DI void ll_gather4(const u64* buf, uint32_t tag, u64 (&w)[4]) {
#pragma unroll 1
    for (int it = 0; it < SPIN; it++) {
        if (it) { w[0] = ld_rlx(buf); w[1] = ld_rlx(buf + 256); w[2] = ld_rlx(buf + 512); w[3] = ld_rlx(buf + 768); }
        if (!__any_sync(~0u, (((lo32(w[0]) ^ tag) | (lo32(w[1]) ^ tag)) | ((lo32(w[2]) ^ tag) | (lo32(w[3]) ^ tag))) & 255)) break;
    }
}
DI u64 lds_u64(uint32_t a, int o) { const uint2 v = lds64(a, o); return v.x | (u64)v.y << 32; }
DI float sum8(uint32_t a, int o, int pitch) {
    float s[8];
#pragma unroll
    for (int w = 0; w < 8; w++) s[w] = ldsf(a, o + w * pitch);
    return ((s[0] + s[1]) + (s[2] + s[3])) + ((s[4] + s[5]) + (s[6] + s[7]));
}
DI void ln_final(float& mean, float& rstd, float& msq) {
    float2 v[5];
#pragma unroll
    for (int w = 0; w < 5; w++) v[w] = lds64f(0, SM_STAT + w * 8);
    mean = (((v[0].x + v[1].x) + (v[2].x + v[3].x)) + v[4].x) * (1.f / D_MODEL);
    msq = (((v[0].y + v[1].y) + (v[2].y + v[3].y)) + v[4].y) * (1.f / D_MODEL);
    rstd = rsq(fmaxf(msq - mean * mean, 0.f) + 1e-5f);
}
constexpr float CS = 0.07216878364870322f * 1.4426950408889634f;
constexpr uint32_t ONES = 0x3f803f80u;

__global__ void __launch_bounds__(NTHR, 1) fused_kernel(const __grid_constant__ Params P) {
    extern __shared__ __align__(1024) unsigned char smem[];
    const int warp = __shfl_sync(~0u, threadIdx.x >> 5, 0), bx = blockIdx.x;
    const int cta = (((bx >> 1) & 15) + (bx >> 6) * 16) * 4 + ((bx >> 5) & 1) * 2 + (bx & 1);

    if (bx == NCTA) {
        if ((uint32_t)__cvta_generic_to_shared(smem) != SM_RING) __trap();
        const uint32_t ep = *(volatile unsigned*)&g_epoch;
        if (threadIdx.x == 0) {
#pragma unroll 1
            for (int it = 0; it < SPIN; it++) { if ((lo32(ld_rlx(&g_ll[0][192])) & 255) == ((ep * 8 + 1) & 255)) break; __nanosleep(200); }
            const uint32_t t0 = gtime();
#pragma unroll 1
            for (int it = 0; it < 1024; it++) { if (gtime() - t0 > HZD) break; __nanosleep(100); }
        }
        __syncthreads();
#pragma unroll 1
        for (int i = threadIdx.x; i < 4 * 80 * 8; i += NTHR)
        {
            const u64 v = (i / 640 & 1) && (i & 7) < 2 ? FX2_INIT : 0ull;
            *reinterpret_cast<ulonglong2*>(g_acc + (i >> 3) * ACC_PITCH + (i & 7) * 16) = make_ulonglong2(v, v);
        }
        __threadfence();
        __syncthreads();
        if (threadIdx.x == 0) asm volatile("st.relaxed.gpu.global.u32 [%0], %1;" :: "l"(&g_zflag), "r"(ep + 1) : "memory");
        return;
    }
    const uint32_t barw = SM_BAR + warp * 64;
    if (elect()) {
        if (warp < 3) sts32(0, SM_T0, gtime());
        else {
            mbar_init(barw + 56, 1);
            asm volatile("fence.mbarrier_init.release.cluster;" ::: "memory");
            mbar_expect(barw + 56, HT);
            tma3(SM_WQ - 3 * HT + warp * HT, &P.tm[TM_WQ], (cta >> 2) * 3, (cta & 3) * 160 - 96 + warp * 32, barw + 56, POL_FIRST);
        }
    }
    int tid = threadIdx.x, lane, g, t, c4;
    uint32_t selA, selB, offV0, offV2;
    auto derive = [&]() {
        lane = tid & 31; g = lane >> 2; t = lane & 3;
        c4 = (tid & 0xe1) + 16 * (t >> 1) + 2 * g;
        selA = (g & 2) ? 0x4444u : (g & 1) ? 0x1044u : 0x4410u;
        selB = (g & 2) ? ((g & 1) ? 0x1044u : 0x4410u) : 0x4444u;
        offV0 = (6 * t) * 128 + ((g ^ ((6 * t) & 7)) << 4);
        offV2 = (6 * t) * 128 + ((g ^ ((6 * t + 2) & 7)) << 4);
    };
    auto refresh = [&]() { tid = pin(tid); derive(); };
    auto refresh_late = [&]() { mbar_wait(SM_BAR + 3 * 64 + 56, 0); refresh(); };
    derive();
    const int j40 = (cta & 3) * 40;
    const bool mlp = (cta & 3) != 3;
    const int hu = ((cta >> 2) * 3 + (cta & 3)) * 16;
    uint2 xp = make_uint2(0, 0);
    if (tid < 160) xp = *reinterpret_cast<const uint2*>(P.x + 4 * c4);
    else if (tid == 192) xp.x = *(volatile unsigned*)&g_epoch;
    else if (tid >= 224 && tid < 240 && mlp) xp.x = reinterpret_cast<const unsigned short*>(P.b1)[hu + lane];
    __syncwarp();
    if (elect()) {
#pragma unroll
        for (int i = 0; i < 7; i++) mbar_init(barw + i * 8, 1);
        if (warp < 4) mbar_arrive(barw);
        mbar_init(SM_CBAR + warp * 8, 1); mbar_init(SM_CBAR + 64 + warp * 8, 1);
        if (warp == 0) { mbar_init(SM_QBAR, 6); mbar_init(SM_BAR + 56, 8); }
        asm volatile("fence.mbarrier_init.release.cluster;" ::: "memory");
        sts64(warp * 8, SM_CNT, 0, 0);
        sts64(warp * 8, SM_ZQ, 0, 0);
    }
    uint32_t kc[192];
#pragma unroll
    for (int i = 12; i < 192; i++) asm volatile("mov.b32 %0, 0;" : "=r"(kc[i]));
    const int rowc = (cta >> 2) * SK + (SK - WIN) + (cta & 3) * 64;
    const int roww = __shfl_sync(~0u, rowc + warp * 8, 0);
    const CUtensorMap* tmk = reinterpret_cast<const CUtensorMap*>(__shfl_sync(~0u, (u64)&P.tm[0] + (lane >> 5), 0));

    auto wait_due = [&](int i, int extra) {
        const uint32_t due = lds32(0, SM_T0) + PACE0 + extra + i * PACE;
#pragma unroll 1
        for (int it = 0; it < 4096; it++) if ((int)(gtime() - due) >= 0) break;
    };
    auto issue_wo = [&](int k) {
        wait_due(64, k * WOPACE);
        mbar_expect(SM_CBAR + 32 + k * 8, 4 * WOU);
        asm volatile("cp.async.bulk.tensor.4d.shared::cluster.global.mbarrier::complete_tx::bytes.L2::cache_hint [%0], [%1, {%2, %3, %4, %5}], [%6], %7;"
                     :: "r"(SM_RING + k * 4 * WOU), "l"(tmk + TM_WO4), "r"(0), "r"(5 * (cta & 3)), "r"((k >> 1) * 8), "r"((cta >> 2) * 8 + (k & 1) * 4),
                        "r"(SM_CBAR + 32 + k * 8), "l"((u64)POL_FIRST << 32) : "memory");
        if (k < 4 && mlp)
            asm volatile("cp.async.bulk.prefetch.tensor.4d.L2.global.tile.L2::cache_hint [%0, {%1, %2, %3, %4}], %5;"
                         :: "l"(tmk + TM_WOP), "r"(0), "r"(5 * (cta & 3)), "r"((k >> 1) * 8), "r"((cta >> 2) * 8 + (k & 1) * 4), "l"((u64)POL_NORMAL << 32) : "memory");
    };
    auto issue_kv = [&](int i, int slot, int bar) {
        const int row = rowc + (i & 30) * 128 + (i & 1) * 32;
        mbar_expect(SM_CBAR + bar * 8, HT);
        tma3(SM_RING + slot * HT, tmk + TM_K + (i >> 5), 0, row, SM_CBAR + bar * 8, POL_FIRST);
        if (i >= 32) tma3_pf(tmk + TM_VP, 0, row, POL_NORMAL);
    };
    __syncwarp();
    if (warp < 3) { wait_due(warp, 0); if (elect()) issue_kv(warp, warp + 1, warp); }
    else mbar_wait(barw + 56, 0);
    if (tid == 192) sts32(0, SM_EPOCH, xp.x);
    if (tid >= 224 && tid < 240) sts32(lane * 4, SM_B1, xp.x << 16);
    __syncthreads();
    if ((warp == 3 || warp == 4) && elect()) issue_kv(warp, warp == 4 ? 0 : 4, warp);
    const uint32_t ep4 = __shfl_sync(~0u, lds32(0, SM_EPOCH) * 4, 0);

    auto load_v3 = [&](uint4* v, uint32_t u, int o, bool odd) {
        if (!odd) { v[0] = lds128(ad(offV0, u), o); v[1] = lds128(ad(offV0 ^ 16, u), o + 128); v[2] = lds128(ad(offV2, u), o + 256); }
        else { v[0] = lds128(ad(offV2 ^ 16, u), o + 384); v[1] = lds128(ad(offV0 ^ 64, u), o + 512); v[2] = lds128(ad(offV0 ^ 80, u), o + 640); }
    };
    auto load_v = [&](uint4 (&v)[6], uint32_t u, int o) { load_v3(v, u, o, false); load_v3(v + 3, u, o, true); };
    const uint32_t wqw = warp * SUB, ksw = warp * HT;
    auto slot_o = [&](int s) { return s < 3 ? SM_WQ + s * 8 * SUB : SM_KS + (s - 3) * SUB; };
    auto slot_u = [&](int s) { return s < 3 ? wqw : ksw; };
    const uint32_t zero = __shfl_sync(~0u, lds32(0, SM_ZQ), 0);
    auto issue2 = [&](auto I, uint32_t dep) {
        constexpr int p = I.value, s = PL.slot[p];
        __syncwarp();
        if ((p < 16 || mlp) && elect()) {
            mbar_expect(barw + s * 8, (dep & zero) | (p < 16 ? SUB : 2 * WOU));
            if constexpr (p < 16) tma3(slot_u(s) + slot_o(s), tmk + TM_V8, 0, roww + vunit(p) * 256, barw + s * 8, POL_FIRST);
            else tma3(slot_u(s) + slot_o(s), tmk + TM_WO, 5 * (cta & 3), (cta >> 2) * DH + warp * 24, barw + s * 8, POL_FIRST);
        }
    };
    auto touch2 = [&]() {
        const char* p = reinterpret_cast<const char*>(P.v) + (size_t)(roww + vunit(2) * 256) * (DH * 2) + lane * 32;
#pragma unroll
        for (int i = 0; i < 3; i++) asm volatile("cp.async.ca.shared.global [%0], [%1], 4;" :: "r"(SM_JUNK), "l"(p + i * 1024) : "memory");
    };
    auto issue_help = [&]() {
        if (elect())
            tma3(SM_WQ + (warp == 7 ? 0 : warp == 6 ? 16 * SUB : 4 * SUB), tmk + (warp == 5 ? TM_V8 : TM_V), 0,
                 rowc + (warp == 6 ? vunit(2) * 256 : warp == 5 ? vunit(0) * 256 + 32 : vunit(0) * 256), warp == 5 ? SM_BAR + 4 * 64 : SM_CBAR - 32 + warp * 8, POL_FIRST);
    };
    auto issue_item1 = [&]() {
        if (elect()) {
            mbar_expect(SM_CBAR - 48 + warp * 8, HT);
            tma3(SM_WQ - 4 * HT + warp * HT, tmk + TM_V, 0, rowc - 192 + warp * 32 + vunit(1) * 256, SM_CBAR - 48 + warp * 8, POL_FIRST);
        }
    };
    const uint32_t prow = warp * 768;
    uint4 wq0[6], wqh[3];
    uint32_t xna;
    auto load_wq = [&]() {
        load_v(wq0, wqw, SM_WQ);
        const int r0 = 6 * t + 3 * (warp & 1);
#pragma unroll
        for (int j = 0; j < 3; j++) wqh[j] = lds128(ad(r0 * 128 + ((g ^ ((r0 + j) & 7)) << 4), (warp >> 1) * SUB), SM_WQ + 16 * SUB + j * 128);
        const int r = c4 - j40;
        xna = pin((tid < 160 && r >= 0 && r < 40) ? SM_VEC + r * 8 : 0u);
        selA = pin(selA); selB = pin(selB);
        offV0 = pin(offV0 + wqw); offV2 = pin(offV2 + wqw);
        tid = pin(tid);
    };
    float acc[3][4];
    auto mma3 = [&](const uint4* v, uint32_t pp, uint32_t hi) {
        const uint32_t b0 = pick(pp, selA | hi), b1 = pick(pp, selB | hi);
        mma(acc[0], v[0], b0, b1); mma(acc[1], v[1], b0, b1); mma(acc[2], v[2], b0, b1);
    };
    auto ln_part = [&]() {
        const float x0 = bf_lo(xp.x), x1 = bf_hi(xp.x), x2 = bf_lo(xp.y), x3 = bf_hi(xp.y);
        const float s1 = (x0 + x1) + (x2 + x3), s2 = (x0 * x0 + x1 * x1) + (x2 * x2 + x3 * x3);
        float ss = ((tid & 16) ? s2 : s1) + shx((tid & 16) ? s1 : s2, 16);
        ss += shx(ss, 8); ss += shx(ss, 4); ss += shx(ss, 2); ss += shx(ss, 1);
        sts32_if((tid & 15) == 0 && tid < 160, tid >> 2, SM_STAT, __float_as_uint(ss));
    };

    auto tick = [&](uint4& v) {
        asm volatile("{\n.reg .pred p;\nsetp.ne.u32 p, %4, 0;\n@p mma.sync.aligned.m16n8k16.row.col.f32.bf16.bf16.f32 {%0,%1,%2,%3}, {%0,%1,%2,%3}, {%0,%1}, {%0,%1,%2,%3};\n}"
                     : "+r"(v.x), "+r"(v.y), "+r"(v.z), "+r"(v.w) : "r"(zero));
    };

    auto q_stage = [&](auto L) {
        constexpr int layer = L.value;
        asm volatile("{\n.reg .pred p;\nsetp.ne.u32 p, %0, 0;\n@p st.shared.v2.u32 [%0], {%1,%2};\n}" :: "r"(xna), "r"(xp.x), "r"(xp.y) : "memory");
        uint4 wq1[6];
        load_v3(wq1, 0, SM_WQ + 8 * SUB, false);
        const uint32_t xra = (tid & 3) * 4;
        __syncthreads();
        uint32_t p0 = lds32(ad(xra, warp * 16), SM_VEC), ph = lds32(ad(xra, (warp >> 1) * 16), SM_VEC + 256), p1 = lds32(ad(xra, warp * 16), SM_VEC + 128);
        if (layer == 0 && (tid & 16)) p0 = p1 = ph = ONES;
#pragma unroll
        for (int j = 0; j < 3; j++) zero4(acc[j]);
        mma3(wq0, p0, 0); mma3(wq0 + 3, p0, 0x2222);
        load_v3(wq1 + 3, 0, SM_WQ + 8 * SUB, true);
        mma3(wqh, ph, (warp & 1) * 0x2222); mma3(wq1, p1, 0); mma3(wq1 + 3, p1, 0x2222);
        if (layer == 1) { lds128(kc + 8, prow + (tid & 31) * 16, SM_PART); lds64(kc + 88, prow + (tid & 31) * 8, SM_PART + 512); __syncwarp(); }
        const uint32_t qpa = ((layer == 0 && (tid & 2)) ? ksw - (SM_PART - SM_KS - 11264) : prow) + (tid & 28) * 8 + (tid & 1) * 16;
#pragma unroll
        for (int j = 0; j < 3; j++) sts128f_if(layer == 0 || !(tid & 2), qpa, SM_PART + j * 256, acc[j][0], acc[j][1], acc[j][2], acc[j][3]);
        u64* dst = &g_ll[cta][tid];
        __syncthreads();
        if (warp < 6) {
            const float s = sum8(tid * 4, SM_PART, 768);
            st_rlx(dst, layer ? mk64(2 * ep4 + 5, __float_as_uint(s)) : ll_pack2(__uint_as_float(__float_as_uint(sum8(tid * 4, SM_KS + 11264, HT)) + 128), s, 2 * ep4 + 1));
        } else if (layer == 1) { sts32(0, SM_T0, gtime()); issue_item1(); }
        refresh_late();
        ln_part();
        __syncthreads();
        sts64(prow + lane * 8, SM_PART, xp.x, xp.y);
    };
    auto q_addr = [&]() { return (((tid >> 1) & 1) * 4 + ((tid >> 4) & 3)) * 48 + ((tid >> 6) * 2 + ((tid >> 3) & 1)) * 8 + ((tid >> 2) & 1) * 4 + (tid & 1) * 2; };
    auto score6 = [&](const uint4 (&v)[6], const uint32_t (&qf)[12]) {
        float d[2][4];
#pragma unroll
        for (int i = 0; i < 6; i++) { if (i < 2) zero4(d[i]); mma(d[i & 1], v[i], qf[2 * i], qf[2 * i + 1]); }
        return (d[0][0] + d[0][3]) + (d[1][0] + d[1][3]);
    };
    auto softmax = [&](auto L, const float (&S)[4]) {
        constexpr int layer = L.value;
        const float mrun = warp_max(fmaxf(fmaxf(S[0], S[1]), fmaxf(S[2], S[3])));
        const float p0 = ex2((S[0] - mrun) * CS), p1 = ex2((S[1] - mrun) * CS), p2 = ex2((S[2] - mrun) * CS), p3 = ex2((S[3] - mrun) * CS);
        const uint32_t pa = pack_bf(p0, p1), pb = pack_bf(p2, p3), pw = prow + t * 64 + g * 2;
        sts16(pw, SM_PART + 256, pa); sts16(pw, SM_PART + 272, pa >> 16); sts16(pw, SM_PART + 288, pb); sts16(pw, SM_PART + 304, pb >> 16);
        const uint32_t l = __reduce_add_sync(~0u, __float2uint_rn(((p0 + p1) + (p2 + p3)) * 16777216.f));
        st_rlx(&g_ll[cta][192 + warp], mk64(__byte_perm(l + 128, 2 * ep4 + 1 + 4 * layer, 0x3214), __float_as_uint(mrun)));
        __syncwarp();
#pragma unroll
        for (int j = 0; j < 3; j++) zero4(acc[j]);
    };
    auto pv = [&](const uint4 (&v)[6], uint32_t pp) { mma3(v, pp, 0); mma3(v + 3, pp, 0x2222); };

    auto head_look = [&]() {
        if (lane < 16) asm volatile("cp.async.cg.shared.global [%0], [%1], 16;" :: "r"(SM_PART + 512 + prow + lane * 16), "l"(&g_ll[cta ^ g][192 + 2 * t]) : "memory");
    };
    float fw;
    auto head_weight = [&](auto L) {
        const uint32_t tag = (2 * ep4 + 1 + 4 * L.value) & 255;
        uint32_t l, m;
#pragma unroll 1
        for (int it = 0; it < SPIN; it++) {
            if (it) head_look();
            asm volatile("cp.async.wait_all;" ::: "memory");
            __syncwarp();
            asm volatile("ld.volatile.shared.v2.u32 {%0,%1}, [%2];" : "=r"(l), "=r"(m) : "r"(SM_PART + 512 + prow + lane * 8) : "memory");
            l ^= tag;
            if (!__any_sync(~0u, l & 255)) break;
        }
        const float f = ex2((__uint_as_float(m) - warp_max(__uint_as_float(m))) * CS);
        const uint32_t Lh = __reduce_add_sync(~0u, __float2uint_rn(f * (float)l * 0.03125f));
        fw = __shfl_sync(~0u, f, warp) * rcp((float)Lh) * (ldsf(0, SM_FXS) * 524288.f);
    };

    uint32_t wa[5], ya, oa, selC, selD;
    uint4 z[5];
    unsigned char* ra;
    const u64* lp;
    auto load_u = [&](uint4 (&a)[5], uint32_t u, int o) {
#pragma unroll
        for (int k = 0; k < 5; k++) a[k] = lds128(ad(wa[k], u), o);
    };
    auto tail_prep1 = [&](auto L) {
        xp = lds64(prow + lane * 8, SM_PART);
        ya = pin(prow + (8 * g + 4 * (t & 1)) * 4);
        oa = pin(((tid >> 5) * 12 + min(lane, 11)) * 8);
        lp = pinp(reinterpret_cast<const u64*>(reinterpret_cast<const char*>(&g_ll[cta][0]) + oa));
    };
    auto tail_prep2 = [&](auto L) {
#pragma unroll
        for (int k = 0; k < 5; k++) {
            const int row = (t & 1) + 2 * (t & 2) + 2 * (k < 4 ? k >> 1 : g >> 2), j = k < 4 ? 2 * (k & 1) + (g >> 2) : 4;
            wa[k] = pin(row * 320 + j * 64 + (((g & 3) ^ (((5 * row + j) >> 1) & 3)) << 4));
        }
        selA = pin(selA); selB = pin(selB);
        selC = selA | (g >> 2) * 0x2222; selD = selB | (g >> 2) * 0x2222;
    };
    auto red_addr = [&](auto L) {
        const int word = t * 160 + j40 + (tid >> 2);
        ra = pinp(g_acc + 2 * L.value * ACC_BYTES + (uint32_t)((word >> 3) * ACC_PITCH + (word & 7) * 8));
    };
    uint4 wf[8], w2r[8];
    uint32_t la, w2a, hpa, ha, *op;
    uint2 b2v;
    const unsigned char* ap;
    unsigned char* ap2;
    float inv1;
    auto load_w1 = [&]() {
#pragma unroll
        for (int j = 0; j < 8; j++) wf[j] = ldsm_t(la, SM_RING + j * 256);
    };
    auto load_w2 = [&]() {
#pragma unroll
        for (int i = 0; i < 8; i++) w2r[i] = lds128(w2a ^ ((i & 1) * 16), SM_W2 + (i >> 1) * 5120 + (i & 1) * 128);
    };
    auto load_b2 = [&]() { asm volatile("ld.global.nc.v2.u32 {%0,%1}, [%2];" : "=r"(b2v.x), "=r"(b2v.y) : "l"(P.b2 + 4 * min(c4, 159))); };
    auto mlp_prep = [&](auto L) {
        unsigned char* const accb = g_acc + 2 * L.value * ACC_BYTES;
        la = (tid >> 5) * 4096 + (64 * ((lane >> 2) & 1) + 4 * ((lane >> 1) & 1) + (lane & 1) + 2 * (lane >> 4)) * 32 + ((((lane >> 3) ^ (lane >> 1)) & 1) << 4);
        w2a = pin((10 * t + 2 * (tid >> 5)) * 128 + ((g ^ ((2 * t + 2 * (tid >> 5)) & 7)) << 4));
        hpa = pin((tid >> 5) * 64 + (t * 8 + g) * 4); ha = pin((lane & 15) * 4);
        if (L.value == 0) { selA = pin(selA); selB = pin(selB); tid = pin(tid); }
        ap = accb + (uint32_t)((c4 >> 3) * ACC_PITCH + (c4 & 7) * 8);
        ap2 = accb + ACC_BYTES + pin((c4 >> 2) * ACC_PITCH + (c4 & 3) * 8);
        if (L.value == 1) ap2 = pinp(ap2);
        inv1 = fx_inv(ldsf(0, SM_FXS));
        if (L.value == 1) { ap = pinp(ap); la = pin(la); op = pinp(reinterpret_cast<uint32_t*>(P.out) + 2 * c4); }
    };
    auto tail = [&](auto L) {
        constexpr int layer = L.value;
        uint32_t cq;
        auto park = [&]() { const int ln = pin(tid) & 31; sts128(prow + ln * 16, SM_PART, kc[8], kc[9], kc[10], kc[11]); sts64(prow + ln * 8, SM_PART + 512, kc[88], kc[89]); };
        {
#pragma unroll
            for (int j = 0; j < 3; j++) sts128f_if(!(tid & 2), ya, SM_PART + 256 * j, acc[j][0] * fw, acc[j][2] * fw, acc[j][1] * fw, acc[j][3] * fw);
            const uint32_t tag = (2 * ep4 + 3 + 4 * layer) & 255;
            __syncthreads();
            float2 own;
            {
                float2 s[8];
#pragma unroll
                for (int w = 0; w < 8; w++) s[w] = lds64f(oa, SM_PART + w * 768);
                own.x = ((s[0].x + s[1].x) + (s[2].x + s[3].x)) + ((s[4].x + s[5].x) + (s[6].x + s[7].x));
                own.y = ((s[0].y + s[1].y) + (s[2].y + s[3].y)) + ((s[4].y + s[5].y) + (s[6].y + s[7].y));
                st_rlx(const_cast<u64*>(lp), ll_pack2(own.x, own.y, tag));
            }
            const uint32_t c0 = clk();
            if (layer == 0) refresh_late();
            uint4 v[5], u[5];
            if constexpr (layer == 0) {
                if (warp < 3) { if (elect()) issue_wo(3 + warp); __syncwarp(); }
                if (warp >= 4) touch2();
                tail_prep2(L);
                mbar_wait(SM_CBAR + 32 + (warp >> 2) * 8, 0);
                load_u(v, warp * WOU, SM_RING);
                __syncthreads();
            }
            constexpr int YP = layer ? SM_WQ : SM_PART;
            float y[3][4];
#pragma unroll
            for (int j = 0; j < 3; j++) zero4(y[j]);
            const u64 *l1 = reinterpret_cast<const u64*>((u64)lp ^ 4096), *l2 = reinterpret_cast<const u64*>((u64)lp ^ 2048), *l3 = reinterpret_cast<const u64*>((u64)lp ^ 6144);
            tick(layer ? z[0] : v[0]);
            if (layer) while (clk() - c0 < ODELAY);
            const uint32_t w1due = layer ? 0 : lds32(0, SM_T0) + PACE0 + 69 * PACE + W1D + (warp - 3) * W1G;
            u64 w1 = ld_rlx(l1), w2 = ld_rlx(l2), w3 = ld_rlx(l3);
            if constexpr (layer == 1) {
                if (mlp) mbar_wait(barw + 40, IC<PL.par[16]>::value);
                load_u(v, mlp ? ksw + slot_o(5) : SM_RING + warp * WOU, 0); load_u(u, mlp ? ksw + slot_o(5) + WOU : SM_RING + (8 + warp) * WOU, 0);
            }
            if (layer == 0 && warp >= 3 && mlp) {
#pragma unroll 1
                for (int it = 0; it < 4096; it++) { tick(v[0]); if ((int)(gtime() - w1due) >= 0) break; }
                if (elect()) {
                    mbar_expect(SM_CBAR + 56 + warp * 8, 4096);
                    asm volatile("cp.async.bulk.tensor.2d.shared::cluster.global.mbarrier::complete_tx::bytes.L2::cache_hint [%0], [%1, {%2, %3}], [%4], %5;"
                                 :: "r"(SM_RING + (warp - 3) * 4096), "l"(tmk + TM_W1), "r"(hu), "r"(warp * 128 - 384), "r"(SM_CBAR + 56 + warp * 8), "l"((u64)POL_FIRST << 32) : "memory");
                }
                __syncwarp();
            }
#pragma unroll 1
            for (int it = 0; it < SPIN; it++) {
                if (it) { w1 = ld_rlx(l1); w2 = ld_rlx(l2); w3 = ld_rlx(l3); }
                if (!__any_sync(~0u, ((lo32(w1) ^ tag) | (lo32(w2) ^ tag) | (lo32(w3) ^ tag)) & 255)) break;
            }
            const uint32_t od = pack_bf((own.x + __uint_as_float(lo32(w1) ^ tag)) + (__uint_as_float(lo32(w2) ^ tag) + __uint_as_float(lo32(w3) ^ tag)),
                                        (own.y + __int_as_float(hi32(w1))) + (__int_as_float(hi32(w2)) + __int_as_float(hi32(w3))));
            const uint32_t o0 = __shfl_sync(~0u, od, tid & 3), o1 = __shfl_sync(~0u, od, (tid & 3) + 4), o2 = __shfl_sync(~0u, od, (tid & 3) + 8);
            auto narrow = [&](const uint4 (&a)[5], uint32_t o) { mma(y[2], a[4], pick(o, selC), pick(o, selD)); };
            auto wide = [&](const uint4 (&a)[5], uint32_t o) {
                const uint32_t b0 = pick(o, selA), b1 = pick(o, selB), b2 = pick(o, selA | 0x2222), b3 = pick(o, selB | 0x2222);
                mma(y[0], a[0], b0, b1); mma(y[1], a[1], b0, b1); mma(y[0], a[2], b2, b3); mma(y[1], a[3], b2, b3);
            };
            narrow(v, o0); wide(v, o0);
            if constexpr (layer == 0) {
                mbar_wait(SM_CBAR + 48 + (warp >> 2) * 8, 0);
                load_u(u, warp * WOU, SM_RING + 8 * WOU);
                __syncwarp();
                if (mlp && elect() && atoms_inc(SM_CNT + 44, 7) == 7) { mbar_expect(SM_CBAR + 120, 20480); tma3(SM_W2, tmk + TM_W2, 0, hu, SM_CBAR + 120, POL_FIRST); }
                __syncwarp();
                narrow(u, o1); wide(u, o1);
                red_addr(L);
                mbar_wait(SM_CBAR + 64 + (warp >> 2) * 8, 0);
                load_u(z, warp * WOU, SM_RING + 16 * WOU);
                narrow(z, o2);
            } else { narrow(u, o1); narrow(z, o2); wide(u, o1); }
            wide(z, o2);
#pragma unroll
            for (int k = 0; k < 4; k++) y[2][k] += shx(y[2][k], 18);
            sts128f_if(!(tid & 18), ya, YP + 512, y[2][0], y[2][1], y[2][2], y[2][3]);
            sts128f_if(!(tid & 2), ya, YP, y[0][0], y[0][1], y[0][2], y[0][3]);
            sts128f_if(!(tid & 2), ya, YP + 256, y[1][0], y[1][1], y[1][2], y[1][3]);
            __syncthreads();
            if (warp < 5) {
                const float s = sum8(tid * 4, YP, 768);
                asm volatile("red.relaxed.gpu.global.add.u64 [%0], %1;" :: "l"(ra), "l"(fx_pack(s)) : "memory");
            }
            cq = clk();
            if (layer == 0) refresh_late();
        }
        if (layer == 1 && !mlp) return;
        if (warp < 5) {
            if (layer == 0) { mlp_prep(L); if (mlp) mbar_wait(SM_CBAR + 80 + warp * 8, 0); }
            load_w1();
            if (layer == 1) { load_w2(); asm volatile("cp.async.wait_all;" ::: "memory"); b2v = lds64(ksw + (tid & 31) * 8, SM_KS + 11264); }
            {
                u64 w[4];
                while (clk() - cq < (layer || mlp ? AR1D : AR1DN));
                fx_poll(ap, w);
                xp = make_uint2(pack_bf(bf_lo(xp.x) + fx_val(w[0]) * inv1, bf_hi(xp.x) + fx_val(w[1]) * inv1),
                                pack_bf(bf_lo(xp.y) + fx_val(w[2]) * inv1, bf_hi(xp.y) + fx_val(w[3]) * inv1));
            }
            {
                const bool ev = layer || !(tid & 4), od = layer || (tid & 4);
                const uint32_t e0 = ev ? xp.x : ONES, e1 = ev ? xp.y : ONES, o0 = od ? xp.x : ONES, o1 = od ? xp.y : ONES;
                float d[8][4];
#pragma unroll
                for (int j = 0; j < 8; j++) { zero4(d[j]); mma(d[j], wf[j], (j & 1) ? o0 : e0, (j & 1) ? o1 : e1); }
                float lo = d[0][0] + d[1][1], hi = d[0][2] + d[1][3];
#pragma unroll
                for (int m = 1; m < 4; m++)
                    asm("{\n.reg .pred p;\nsetp.eq.u32 p, %6, %7;\n@p add.f32 %0, %2, %3;\n@p add.f32 %1, %4, %5;\n}" : "+f"(lo), "+f"(hi)
                        : "f"(d[2 * m][0]), "f"(d[2 * m + 1][1]), "f"(d[2 * m][2]), "f"(d[2 * m + 1][3]), "r"(tid & 3), "r"(m));
                float dd = ((tid & 1) ? hi : lo) + shx((tid & 1) ? lo : hi, 1);
                dd += shx(dd, 2);
                ln_part();
                if (layer == 0) {
                    const float cl = ((d[0][1] + d[1][0]) + (d[2][1] + d[3][0])) + ((d[4][1] + d[5][0]) + (d[6][1] + d[7][0]));
                    const float ch = ((d[0][3] + d[1][2]) + (d[2][3] + d[3][2])) + ((d[4][3] + d[5][2]) + (d[6][3] + d[7][2]));
                    sts32_if(!(tid & 2), hpa, SM_C1, __float_as_uint((tid & 1) ? ch : cl));
                }
                sts32_if(!(tid & 2), hpa, SM_QU, __float_as_uint(dd));
            }
            const float b1v = ldsf(ha, SM_B1);
            float csum = layer ? ldsf(ha, SM_B1 + 64) : 0.f;
            bar_sync(1, layer ? 160 : 192);
            float mean, rstd, msq;
            ln_final(mean, rstd, msq);
            float hp[5];
#pragma unroll
            for (int w = 0; w < 5; w++) hp[w] = ldsf(ha, SM_QU + w * 64);
            if constexpr (layer == 0) {
                float c[5];
#pragma unroll
                for (int w = 0; w < 5; w++) c[w] = ldsf(ha, SM_C1 + w * 64);
                csum = ((c[0] + c[1]) + (c[2] + c[3])) + c[4];
                load_w2();
            }
            float hv = ((((hp[0] + hp[1]) + (hp[2] + hp[3])) + hp[4]) - mean * csum) * rstd + b1v;
            hv = hv * rcp(1.f + ex2(hv * (-2.302208198f - 0.1029432397f * hv * hv)));
            const uint32_t hd = pack_bf(hv, hv);
            float ym[4][4];
            const uint32_t hh[4] = {__shfl_sync(~0u, hd, tid & 3), __shfl_sync(~0u, hd, (tid & 3) + 4), __shfl_sync(~0u, hd, (tid & 3) + 8), __shfl_sync(~0u, hd, (tid & 3) + 12)};
#pragma unroll
            for (int i = 0; i < 4; i++) {
                const uint32_t b0 = pick(hh[i], selA), b1 = pick(hh[i], selB);
                if (i < 2) { zero4(ym[2 * i]); zero4(ym[2 * i + 1]); }
                mma(ym[2 * (i & 1)], w2r[2 * i], b0, b1); mma(ym[2 * (i & 1) + 1], w2r[2 * i + 1], b0, b1);
            }
            const float sc2 = __uint_as_float((uint32_t)(127 + 16 - max(((int)(__float_as_uint(msq) >> 23) - 127) >> 1, -100)) << 23);
            float y[4];
            uint32_t yb[4];
#pragma unroll
            for (int k = 0; k < 4; k++) { y[k] = ((tid & 2) ? ym[1][k] : ym[0][k]) + ((tid & 2) ? ym[3][k] : ym[2][k]); yb[k] = __float_as_uint(fmaf(y[k], sc2, FX2_MAGIC)); }
            const uint32_t big = !mlp ? 0 : (((yb[0] ^ 0x4b400000u) | (yb[1] ^ 0x4b400000u)) | ((yb[2] ^ 0x4b400000u) | (yb[3] ^ 0x4b400000u))) & FX2_MASK;
            u64 w[2], old[2];
#pragma unroll
            for (int k = 0; k < 2; k++) {
                w[k] = mk64(big ? 0 : yb[2 * k] * 512 + 0x80000001u, big ? 0 : yb[2 * k + 1] * 16 + 0x4c000000u);
                if (layer == 0) { if (mlp) asm volatile("red.relaxed.gpu.global.add.u64 [%0], %1;" :: "l"(ap2 + k * 40 * ACC_PITCH), "l"(w[k]) : "memory"); }
                else asm volatile("atom.relaxed.gpu.global.add.u64 %0, [%1], %2;" : "=l"(old[k]) : "l"(ap2 + k * 40 * ACC_PITCH), "l"(w[k]) : "memory");
            }
            const uint32_t c0 = clk();
            if (__any_sync(~0u, big)) {
                if (big) {
#pragma unroll
                    for (int k = 0; k < 4; k++)
                        asm volatile("red.relaxed.gpu.global.add.u64 [%0], %1;" :: "l"(ap2 + (k >> 1) * 40 * ACC_PITCH + 64 + (k & 1) * 32), "l"(fx_pack(y[k] * fx_scale(msq))) : "memory");
                    __threadfence();
#pragma unroll
                    for (int k = 0; k < 2; k++) {
                        asm volatile("red.relaxed.gpu.global.and.b64 [%0], %1;" :: "l"(ap2 + k * 40 * ACC_PITCH), "l"(~256ull) : "memory");
                        w[k] = FX2_NONE;
                        asm volatile("atom.relaxed.gpu.global.add.u64 %0, [%1], %2;" : "=l"(old[k]) : "l"(ap2 + k * 40 * ACC_PITCH), "l"(FX2_NONE) : "memory");
                    }
                }
                __syncwarp();
            }
            if (layer == 0) { refresh(); load_b2(); park(); stsf(ha, SM_B1 + 64, csum); }
            stsf(0, SM_FXS, msq);
            const float inv32 = fx_inv(sc2) * 0.03125f;
            float xb[4] = {bf_lo(xp.x) + bf_lo(b2v.x) - 24.f * inv32, bf_hi(xp.x) + bf_hi(b2v.x), bf_lo(xp.y) + bf_lo(b2v.y) - 24.f * inv32, bf_hi(xp.y) + bf_hi(b2v.y)};
            auto add_wide = [&]() {
                __threadfence();
#pragma unroll
                for (int k = 0; k < 4; k++) xb[k] += fx_val(ld_rlx(ap2 + (k >> 1) * 40 * ACC_PITCH + 64 + (k & 1) * 32)) * fx_inv(fx_scale(ldsf(0, SM_FXS)));
            };
            auto sum2 = [&](int k) {
                return pack_bf(xb[2 * k] + (float)(int)__funnelshift_r(lo32(w[k]), hi32(w[k]), 4) * inv32, xb[2 * k + 1] + (float)hi32(w[k]) * (inv32 + inv32));
            };
            if constexpr (layer == 1) {
#pragma unroll
                for (int k = 0; k < 4; k++) xb[k] = pinf(xb[k]);
                mbar_wait(SM_BAR + 3 * 64 + 56, 0);
#pragma unroll
                for (int k = 0; k < 2; k++) {
                    w[k] += old[k];
                    asm volatile("{\n.reg .pred p;\nsetp.eq.u32 p, %2, 0;\n@p st.global.u32 [%0], %1;\n}" :: "l"(op + k), "r"(sum2(k)), "r"(~lo32(w[k]) & 0x180) : "memory");
                }
                if (((lo32(w[0]) & ~(lo32(w[0]) >> 1)) | (lo32(w[1]) & ~(lo32(w[1]) >> 1))) & 128) {
                    add_wide();
                    if (w[0] & 128) op[0] = sum2(0);
                    if (w[1] & 128) op[1] = sum2(1);
                }
            } else {
                load_wq();
                __syncwarp();
                if (elect()) mbar_arrive(SM_BAR + 56);
#pragma unroll
                for (int k = 0; k < 4; k++) xb[k] = pinf(xb[k]);
                while (clk() - c0 < AR2D);
                uint32_t want = 0x180;
#pragma unroll 1
                for (int it = 0; it < SPIN; it++) {
                    if (it && !__any_sync(~0u, ~(lo32(w[0]) & lo32(w[1])) & 128)) { add_wide(); want = 128; }
                    w[0] = ld_rlx(ap2); w[1] = ld_rlx(ap2 + 40 * ACC_PITCH);
                    if (!__any_sync(~0u, ~(lo32(w[0]) & lo32(w[1])) & want)) break;
                }
                xp = make_uint2(sum2(0), sum2(1));
            }
        } else if constexpr (layer == 1) {
            if (warp == 7) {
                const uint32_t c1 = clk();
                while (clk() - c1 < KAD) tick(z[0]);
                if (zero) sts32(0, SM_JUNK, z[0].x);
            }
        } else {
            const uint32_t c0 = clk();
            load_wq();
            __syncwarp();
            if (elect()) mbar_arrive(SM_BAR + 56);
            if (warp == 5) {
                if (mlp) mbar_wait(SM_CBAR + 120, 0);
                asm volatile("bar.arrive 1, 192;" ::: "memory");
            }
            while (clk() - c0 < S6D + (warp - 5) * S6G) tick(wqh[0]);
            issue2(IC<0>{}, wq0[0].x | wq0[1].x | wq0[2].x | wq0[3].x | wq0[4].x | wq0[5].x);
            if (warp == 5) {
#pragma unroll 1
                for (int k = 0; k < NPFC; k++) {
                    while (clk() - c0 < PFD + k * PFG);
                    if (elect()) tma3_pf(tmk + TM_V8, 0, rowc + (k >> 3) * 256 + (k & 7) * 8, POL_NORMAL);
                }
            }
            if (elect()) mbar_expect(warp == 5 ? SM_BAR + 4 * 64 : SM_CBAR - 32 + warp * 8, warp == 5 ? SUB : HT);
#pragma unroll 1
            for (int it = 0; it < SPIN; it++) { if (mbar_test(SM_BAR + 56, 0)) break; tick(wqh[0]); }
            const uint32_t c1 = clk();
            park();
            while (clk() - c1 < I0D) tick(wqh[0]);
            issue_help();
        }
    };

    load_wq();
    q_stage(IC<0>{});
    {
        int it = (warp >> 2) + 5, slot = (warp >> 2) + 1, bar = warp >> 2, par = 0;
        auto refill = [&](bool kv) {
            uint32_t old;
            asm volatile("{\n.reg .pred p;\nelect.sync _|p, 0xffffffff;\nmov.u32 %0, 0;\n@p atom.relaxed.cta.shared.inc.u32 %0, [%1], 3;\n}" : "=r"(old) : "r"(SM_CNT + slot * 8) : "memory");
            if (__any_sync(~0u, old == 3)) {
                if (!kv && it >= 64) {
#pragma unroll 1
                    for (int k = 0; k < SPIN; k++) {
                        int f; asm volatile("ld.volatile.shared.u32 %0, [%1];" : "=r"(f) : "r"(SM_CNT + 4) : "memory");
                        if (f >= slot) break;
                    }
                    sts32(0, SM_CNT + 4, slot + 1);
                    if (elect()) issue_wo(slot);
                } else {
                    wait_due(it, 0);
                    if (elect()) issue_kv(it, slot, bar < 5 ? bar + 5 : bar - 5);
                }
                __syncwarp();
            }
        };
        auto advance = [&]() { it += 2; slot += 2; if (slot >= 5) slot -= 5; bar += 2; if (bar >= 10) { bar -= 10; par ^= 1; } };
        {
            uint32_t offK[3], qf[12];
#pragma unroll
            for (int j = 0; j < 3; j++) offK[j] = pin(((tid >> 5) & 3) * SUB + 3 * g * 128 + (((2 * t) ^ ((3 * g + j) & 7)) << 4));
#pragma unroll
            for (int i = 0; i < 12; i++) qf[i] = kc[i] = 0;
            const uint32_t ksl = pin(ksw + lane * 16), sca = pin(prow + g * 64);
            int n0 = 0;
#pragma unroll 1
            for (int e = 0; e < 16; e++) {
                mbar_wait(SM_CBAR + bar * 8, par);
                uint4 v[6];
#pragma unroll
                for (int i = 0; i < 6; i++) v[i] = lds128(ad(offK[i >> 1] ^ ((i & 1) * 16), slot * HT), SM_RING + (i >> 1) * 128);
                refill(true);
                advance();
                if ((0xc20 | ((2 << NP) - 1)) >> e & 1) {
                    refresh();
                    static_for<0, NP>([&](auto E) {
                        if (e == E.value) {
#pragma unroll
                            for (int i = 0; i < 6; i++) {
                                uint32_t* k = kc + 90 + 24 * E.value + 4 * i;
                                asm volatile("mov.b32 %0, %4; mov.b32 %1, %5; mov.b32 %2, %6; mov.b32 %3, %7;" : "=r"(k[0]), "=r"(k[1]), "=r"(k[2]), "=r"(k[3]) : "r"(v[i].x), "r"(v[i].y), "r"(v[i].z), "r"(v[i].w));
                            }
                            if (E.value == NP - 2 && warp < 6) {
#pragma unroll
                                for (int i = 0; i < 2; i++)
                                    asm volatile("cp.async.cg.shared.global [%0], [%1], 16;" :: "r"(ksl + SM_KS + 10240 + i * 512),
                                                 "l"(&g_ll[(cta & ~3) + 2 * i + (lane >> 4)][warp * 32 + (lane & 15) * 2]) : "memory");
                            }
                            if (E.value == NP - 1 && warp < 6) {
                                asm volatile("cp.async.wait_all;" ::: "memory");
                                __syncwarp();
                                const uint32_t a = ksw + lane * 8;
                                u64 w[4] = {lds_u64(a, SM_KS + 10240), lds_u64(a, SM_KS + 10496), lds_u64(a, SM_KS + 10752), lds_u64(a, SM_KS + 11008)};
                                ll_gather4(&g_ll[cta & ~3][tid], 2 * ep4 + 1, w);
                                const float cs = (lof(w[0] & ~255ull) + lof(w[1] & ~255ull)) + (lof(w[2] & ~255ull) + lof(w[3] & ~255ull));
                                float q = (hif(w[0]) + hif(w[1])) + (hif(w[2]) + hif(w[3]));
                                stsf(tid * 4, SM_CS, cs);
                                float mean, rstd, msq;
                                ln_final(mean, rstd, msq);
                                stsf(0, SM_FXS, fx_scale(msq));
                                q = (q - mean * cs) * rstd;
                                sts16(q_addr(), SM_QU, pack_bf(q, q));
                                __syncwarp();
                                if (elect()) mbar_arrive(SM_QBAR);
#pragma unroll
                                for (int i = 0; i < 12; i++) asm volatile("mov.b32 %0, 0;" : "=r"(kc[i]));
                            }
                        }
                    });
                    if (e == NP) {
                        mbar_wait(SM_QBAR, 0);
#pragma unroll
                        for (int k = 0; k < 3; k++) lds128(qf + 4 * k, (lane & 7) * 48, SM_QU + k * 16);
                        static_for<0, NP>([&](auto E) {
                            uint4 r[6];
#pragma unroll
                            for (int i = 0; i < 6; i++) { const uint32_t* k = kc + 90 + 24 * E.value + 4 * i; r[i] = make_uint4(k[0], k[1], k[2], k[3]); }
                            stsf(sca, SM_PART + 256 + (E.value + 6) * 4, score6(r, qf));
                        });
#pragma unroll
                        for (int i = 0; i < 24; i++) asm volatile("mov.b32 %0, 0;" : "=r"(kc[i]));
                    } else if (e == 5) {
#pragma unroll
                        for (int k = 0; k < 22; k++) lds128(kc + 4 * k, ksl, SM_KS + k * 512);
                        lds64(kc + 88, ksl, SM_KS + 22 * 512);
                        n0 = 0;
                    } else if (e == 10) {
#pragma unroll
                        for (int k = 0; k < 22; k++)
                            asm volatile("ld.shared.v4.b32 {%0,%1,%2,%3}, [%4];" : "=r"(kc[90 + 4 * k]), "=r"(kc[91 + 4 * k]), "=r"(kc[92 + 4 * k]), "=r"(kc[93 + 4 * k]) : "r"(ad(ksl, SM_KS + k * 512)) : "memory");
                        asm volatile("ld.shared.v2.b32 {%0,%1}, [%2];" : "=r"(kc[178]), "=r"(kc[179]) : "r"(ad(ksl, SM_KS + 22 * 512)) : "memory");
                        n0 = 0;
                    } else if (e == 11) {
                        lds64(kc + 180, ksl, SM_KS + 520); lds128(kc + 182, ksl, SM_KS + 1024); lds128(kc + 186, ksl, SM_KS + 1536); lds64(kc + 190, ksl, SM_KS + 2048);
                        n0 = 3;
                    }
                }
                const int n = (e + 6) & 15;
                stsf(ad(sca, n * 4), SM_PART + 256, score6(v, qf));
                uint32_t m = bf2_amax(bf2_amax(v[0].x, v[0].y), bf2_amax(v[0].z, v[0].w)), mn = bf2_amin(bf2_amin(v[0].x, v[0].y), bf2_amin(v[0].z, v[0].w));
#pragma unroll
                for (int i = 1; i < 6; i++) m = bf2_amax(m, bf2_amax(bf2_amax(v[i].x, v[i].y), bf2_amax(v[i].z, v[i].w)));
                m = max(m & 0x7fff, (m >> 16) & 0x7fff);
                m = max(m, __shfl_xor_sync(~0u, m, 1)); m = max(m, __shfl_xor_sync(~0u, m, 2));
#pragma unroll
                for (int i = 1; i < 6; i++) mn = bf2_amin(mn, bf2_amin(bf2_amin(v[i].x, v[i].y), bf2_amin(v[i].z, v[i].w)));
                mn = min(mn & 0x7fff, (mn >> 16) & 0x7fff);
                const int sh = min(max((int)(m >> 7) - 15, 0), 126);
                asm volatile("st.shared.u8 [%0], %1;" :: "r"(ad(ad((tid >> 2) * 16, n), SM_SH)), "r"(sh) : "memory");
                const uint32_t dn = (127 - sh) * 0x00800080u;
                if (__any_sync(~0u, (int)(mn >> 7) <= sh || m >= (142 << 7))) {
                    if (m >= (142 << 7)) sts32(0, SM_BIG, 1);
                    const uint32_t up = (127 + 256 + sh) * 0x00800080u;
#pragma unroll
                    for (int i = 0; i < 6; i++) {
                        const uint32_t r0 = bf2_fma(bf2_mul(v[i].x, dn), up, v[i].x), r1 = bf2_fma(bf2_mul(v[i].y, dn), up, v[i].y);
                        const uint32_t r2 = bf2_fma(bf2_mul(v[i].z, dn), up, v[i].z), r3 = bf2_fma(bf2_mul(v[i].w, dn), up, v[i].w);
                        asm volatile("{\n.reg .pred p;\n.reg .u32 x, a;\nsetp.ne.u32 p, %0, 0;\nmov.u32 x, %7;\n@p atom.relaxed.cta.shared.inc.u32 x, [%6], 0x7fffffff;\n"
                                     "setp.lt.u32 p, x, %7;\nmad.lo.u32 a, x, 16, %8;\n@p st.shared.v4.u32 [a], {%1,%2,%3,%4};\n"
                                     "mad.lo.u32 a, x, 4, %9;\n@p st.shared.u32 [a], %5;\n}"
                                     :: "r"(r0 | r1 | r2 | r3), "r"(r0), "r"(r1), "r"(r2), "r"(r3), "r"(tid << 16 | n << 8 | i * 8), "r"(SM_XN), "n"(XCAP), "n"(SM_XR), "n"(SM_XM) : "memory");
                    }
                }
                const uint32_t ae = (n0 >> 1) * 512 + (n0 & 1) * 8, ao = ((n0 + 1) >> 1) * 512 + (~n0 & 1) * 8;
                uint32_t o[18];
#pragma unroll
                for (int i = 0; i < 6; i++) {
                    const uint32_t y0 = bf2_mulv(v[i].x, dn), y1 = bf2_mulv(v[i].y, dn), y2 = bf2_mulv(v[i].z, dn), y3 = bf2_mulv(v[i].w, dn);
                    o[3 * i] = __byte_perm(y0, y1, 0x6420); o[3 * i + 1] = __byte_perm(y2, y3, 0x6420);
                    const uint32_t hb = __byte_perm(y2, y3, 0x7531);
                    o[3 * i + 2] = __byte_perm(y0, y1, 0x7531) | __funnelshift_l(hb, hb, 4);
                    if (i & 1) {
#pragma unroll
                        for (int k = 3 * (i >> 1); k < 3 * (i >> 1) + 3; k++) sts64(ad(ksl, (k & 1) ? ao : ae), SM_KS + (k >> 1) * 512, o[2 * k], o[2 * k + 1]);
                    }
                }
                n0 += 9;
            }
            fence_async();
        }
        refresh();
        {
            const uint4 sc = lds128(prow + lane * 16, SM_PART + 256);
            const float S[4] = {__uint_as_float(sc.x), __uint_as_float(sc.y), __uint_as_float(sc.z), __uint_as_float(sc.w)};
            softmax(IC<0>{}, S);
        }
        fw = 0.f;
#pragma unroll 1
        for (int e = 0; e < 16; e++) {
            if ((1 << (PUBAT - 3) | 1 << PUBAT | 1 << ZCHK) >> e & 1) {
                if (e == PUBAT - 3) head_look();
                else if (e == PUBAT) {
                    head_weight(IC<0>{});
                    if (tid < 196) st_rlx(&g_ll[cta][tid + (tid >> 6 == 3) * 8], 0ull);
                } else if (warp == 7) {
                    if ((bx & 15) == 0 && elect()) bulk_pf(P.b2, D_MODEL * 2, POL_NORMAL);
#pragma unroll 1
                    for (int k = 0; k < SPIN; k++) {
                        uint32_t v; asm volatile("ld.acquire.gpu.global.u32 %0, [%1];" : "=r"(v) : "l"(&g_zflag) : "memory");
                        if (__all_sync(~0u, v * 4 == ep4 + 4)) break;
                    }
                }
                __syncwarp();
            }
            const uint32_t pp = lds32(ad(t * 4, prow + ((e + 6) & 15) * 16), SM_PART + 256);
            mbar_wait(SM_CBAR + bar * 8, par);
            uint4 v[6];
            load_v(v, (warp & 3) * SUB + slot * HT, SM_RING);
            if (e < 15) refill(false);
            advance();
            pv(v, pp);
        }
    }
    tail_prep1(IC<0>{});
    __syncwarp();
    tail(IC<0>{});

    q_stage(IC<1>{});
    {
        const u64* qp = &g_ll[cta & ~3][tid];
        u64 w[4] = {0, 0, 0, 0};
        if (warp < 6) { w[0] = ld_rlx(qp); w[1] = ld_rlx(qp + 256); w[2] = ld_rlx(qp + 512); w[3] = ld_rlx(qp + 768); }
        mbar_wait(SM_BAR + 3 * 64 + 56, 0);
        const uint32_t ksl = ksw + lane * 16, qa = pin(q_addr()), qb0 = pin(lane < 8 ? lane * 48 : SM_ZQ - SM_VEC);
        uint32_t ks[96], qf[12];
        float mean, rstd, msq;
        ln_final(mean, rstd, msq);
        const float qc = pinf(-mean * rstd * ldsf(tid * 4, SM_CS));
#pragma unroll
        for (int k = 0; k < 6; k++) lds128(ks + 4 * k, ksl, SM_KS + k * 512);
        stsf(0, SM_FXS, fx_scale(msq));
        if (warp < 6) {
            ll_gather4(qp, 2 * ep4 + 5, w);
            const float q = ((hif(w[0]) + hif(w[1])) + (hif(w[2]) + hif(w[3]))) * rstd + qc;
            const uint32_t qq = bf2_mul(pack_bf(q, q), 0x3f807180u);
            sts16(qa, SM_VEC, qq); sts16(qa, SM_QU, qq >> 16);
            sts32_if(!(fabsf(q) < 1048576.f), 0, SM_BIG, 1);
            __syncwarp();
            if (elect()) mbar_arrive(SM_QBAR);
        } else {
            uint4 c = make_uint4(ks[0], ks[1], ks[2], ks[3]);
            if (cta == 0 && tid == 255) g_epoch = (ep4 >> 2) + 1;
#pragma unroll 1
            for (int it = 0; it < SPIN; it++) { if (mbar_test(SM_QBAR, 1)) break; tick(c); }
            ks[0] = c.x; ks[1] = c.y; ks[2] = c.z; ks[3] = c.w;
        }
        issue2(IC<3>{}, ks[0] | ks[4] | ks[8] | ks[12] | ks[16] | ks[20]);
        mbar_wait(SM_QBAR, 1);
        auto load_q = [&](int u, int k) { lds128(qf + 4 * k, u == 0 ? qb0 : (tid & 24) == 8 * u ? (tid & 7) * 48 : SM_ZQ - SM_VEC, SM_VEC + k * 16); };
        load_q(0, 1); load_q(0, 2); load_q(0, 0);
        float D[4][4];
        uint4 vb[NPK + 2][6], v2[6];
        uint32_t xn = 0;
        const uint32_t t1 = __shfl_sync(~0u, lds32(0, SM_T0), 0);
        auto step = [&](auto Q) {
            constexpr int st = Q.value, p = cord(st), s = PL.slot[p], n = PL.ld[st];
            if constexpr (n > 0) {
                if constexpr (st >= NPK) {
                    const uint32_t due = t1 + P2A + n * P2B;
#pragma unroll 1
                    for (int it = 0; it < 4096; it++) if ((int)(gtime() - due) >= 0) break;
                }
                const uint4 (&u)[6] = vb[st - 1 < NPK ? st - 1 : NPK + ((st - 1) & 1)];
                issue2(IC<n>{}, st > PVNOW ? 0 : u[0].x | u[1].x | u[2].x | u[3].x | u[4].x | u[5].x);
            }
            if (p == 1) mbar_wait(SM_CBAR + (warp >> 2) * 8, 1);
            else if (p == 0) mbar_wait(warp < 4 ? SM_CBAR + 24 : barw, warp < 4);
            else mbar_wait(barw + s * 8, IC<PL.par[p]>::value);
            load_v(vb[st < NPK ? st : NPK + (st & 1)], slot_u(s), slot_o(s));
            if constexpr (st == 14) issue2(IC<16>{}, 0);
        };
        static_for<0, 96>([&](auto I) {
            constexpr int F = I.value, n = F / 6, i = n ? F % 6 : (F + 2) % 6;
            const uint32_t* c = n == 0 ? (i < 2 ? ks + 3 * i : kc + 174 + 3 * i) : n < 6 ? ks + 18 * n - 12 + 3 * i : kc + 18 * (n - 6) + 3 * i;
            const uint32_t hx = c[2] & 0x78787878u, ha = hx * (zero - 1) + c[2], hb = __funnelshift_r(hx, hx, 4);
            if (F < 24 && F % 6 == 0) zero4(D[n]);
            mma(D[n & 3], __byte_perm(c[0], ha, 0x5140), __byte_perm(c[0], ha, 0x7362), __byte_perm(c[1], hb, 0x5140), __byte_perm(c[1], hb, 0x7362), qf[2 * i], qf[2 * i + 1]);
            if constexpr ((n & 3) == 3 && n < 15 && (i & 1)) load_q((n + 1) >> 2, i >> 1);
            static_for<6, 24>([&](auto U) {
                if constexpr (((U.value - 5) * 4 + 2) / 3 - 1 == F) {
                    lds128(ks + 4 * U.value, ksl, SM_KS + U.value * 512);
                    if constexpr (U.value % 6 == 5) { const uint32_t* k = ks + 4 * U.value - 17; issue2(IC<3 + U.value / 6>{}, k[0] | k[4] | k[8] | k[12] | k[16] | k[20]); }
                }
            });
            if constexpr (F == 94) {
                if (warp < 4) { mbar_wait(SM_CBAR + 16, 1); load_v(v2, wqw, slot_o(2)); }
                else {
                    const char* p = reinterpret_cast<const char*>(P.v) + (size_t)(roww + vunit(2) * 256) * (DH * 2) + t * 768 + g * 16;
#pragma unroll
                    for (int k = 0; k < 6; k++)
                        asm volatile("ld.global.nc.v4.u32 {%0,%1,%2,%3}, [%4];" : "=r"(v2[k].x), "=r"(v2[k].y), "=r"(v2[k].z), "=r"(v2[k].w) : "l"(p + k * 128));
                }
                const uint2 x = lds64(0, SM_XN);
                xn = x.y ? XCAP + 1 : x.x;
                sts128(prow + lane * 16, SM_PART + 256, 0, 0, 0, 0);
                __syncwarp();
#pragma unroll 1
                for (uint32_t idx = lane; idx < (xn > XCAP ? 0 : xn); idx += 32) {
                    const uint32_t m = lds32(idx * 4, SM_XM);
                    if ((m >> 21) == warp) {
                        const uint4 r = lds128(idx * 16, SM_XR);
                        const uint32_t qo = ((m >> 16) & 3) * 48 + (m & 255);
                        const uint2 a = lds64(qo, SM_QU), b = lds64(qo, SM_QU + 192);
                        const float s = ((bf_lo(r.x) * bf_lo(a.x) + bf_hi(r.x) * bf_hi(a.x)) + (bf_lo(r.y) * bf_lo(b.x) + bf_hi(r.y) * bf_hi(b.x))) +
                                        ((bf_lo(r.z) * bf_lo(a.y) + bf_hi(r.z) * bf_hi(a.y)) + (bf_lo(r.w) * bf_lo(b.y) + bf_hi(r.w) * bf_hi(b.y)));
                        asm volatile("red.relaxed.cta.shared.add.f32 [%0], %1;" :: "r"(SM_PART + 256 + prow + ((m >> 18) & 7) * 64 + ((m >> 8) & 15) * 4), "f"(s) : "memory");
                    }
                }
                __syncwarp();
            }
            if constexpr (F == PK0 - 2) refresh();
            static_for<0, NPK>([&](auto Q) { if constexpr (F == (Q.value ? PK1 + (Q.value - 1) * PKD : PK0)) step(Q); });
        });
        float S[4];
        {
            const uint32_t shp = lds32(tid * 4, SM_SH);
            const uint4 cr = lds128(prow + lane * 16, SM_PART + 256);
            const uint32_t c[4] = {cr.x, cr.y, cr.z, cr.w};
#pragma unroll
            for (int j = 0; j < 4; j++) S[j] = (D[j][0] + D[j][3]) * __uint_as_float((((shp >> (8 * j)) & 255) + 27) << 23) + __uint_as_float(c[j]);
        }
        if (xn > XCAP) {
#pragma unroll
            for (int k = 0; k < 3; k++) lds128(qf + 4 * k, (lane & 7) * 48, SM_QU + k * 16);
#pragma unroll 1
            for (int e = 0; e < 16; e++) {
                uint4 v[6];
#pragma unroll
                for (int i = 0; i < 6; i++) v[i] = ldg128(P.k + (size_t)(roww + 256 * e + g) * DH + (i >> 1) * 64 + (2 * t + (i & 1)) * 8);
                const float s = score6(v, qf);
#pragma unroll
                for (int j = 0; j < 4; j++) if (4 * t + j == ((e + 6) & 15)) S[j] = s;
            }
        }
        softmax(IC<1>{}, S);
        auto p_of = [&](int st) { return lds32(ad(t * 4, prow), SM_PART + 256 + ((vunit(cord(st)) + 6) & 15) * 16); };
        auto pv_at = [&](auto Q) { constexpr int st = Q.value; pv(vb[st < NPK ? st : NPK + (st & 1)], p_of(st)); };
        static_for<NPK, 15>([&](auto Q) {
            constexpr int st = Q.value;
            if constexpr (st == HWAT) head_look();
            if constexpr (st == HWC) head_weight(IC<1>{});
            if constexpr (st == B2AT) asm volatile("cp.async.ca.shared.global [%0], [%1], 8;" :: "r"(SM_KS + 11264 + ksw + lane * 8), "l"(P.b2 + 4 * min(c4, 159)) : "memory");
            if constexpr (st == PREP1) { tail_prep1(IC<1>{}); tail_prep2(IC<1>{}); red_addr(IC<1>{}); load_u(z, warp * WOU, SM_RING + 16 * WOU); }
            if constexpr (st == PREP2) mlp_prep(IC<1>{});
            uint32_t pp;
            if constexpr (st >= PVNOW) pp = pin(p_of(st));
            step(Q);
            if constexpr (st - NPK < NPK) pv_at(IC<st - NPK>{});
            if constexpr (st > NPK && st <= PVNOW) pv_at(IC<st - 1>{});
            if constexpr (st == PV2) pv(v2, lds32(ad(t * 4, prow), SM_PART + 256 + ((vunit(2) + 6) & 15) * 16));
            if constexpr (st >= PVNOW) pv(vb[NPK + (st & 1)], pp);
        });
    }
    tail(IC<1>{});
}

typedef CUresult (*EncodeFn)(CUtensorMap*, CUtensorMapDataType, cuuint32_t, void*, const cuuint64_t*, const cuuint64_t*, const cuuint32_t*,
                             const cuuint32_t*, CUtensorMapInterleave, CUtensorMapSwizzle, CUtensorMapL2promotion, CUtensorMapFloatOOBfill);

}

extern "C" void kernel_launch(void* const* d_in, const int* in_sizes, int n_in, void* d_out, int out_size) {
    (void)in_sizes; (void)n_in; (void)out_size;
    static EncodeFn enc = nullptr;
    if (!enc) {
        void* fn = nullptr;
        cudaDriverEntryPointQueryResult qr;
        cudaGetDriverEntryPoint("cuTensorMapEncodeTiled", &fn, cudaEnableDefault, &qr);
        enc = (EncodeFn)fn;
        cudaFuncSetAttribute(fused_kernel, cudaFuncAttributeMaxDynamicSharedMemorySize, SM_TOTAL);
    }
    Params P;
    const cuuint32_t ones[3] = {1, 1, 1};
    for (int m = TM_K; m <= TM_V8; m++) {
        const cuuint64_t dim[3] = {64, 3, (cuuint64_t)NHEAD * SK}, str[2] = {128, DH * 2};
        const cuuint32_t box[3] = {m == TM_VP ? 8u : 64u, 3, m == TM_V8 ? 8u : 32u};
        enc(&P.tm[m], CU_TENSOR_MAP_DATA_TYPE_BFLOAT16, 3, d_in[m == TM_K ? 1 : 2], dim, str, box, ones, CU_TENSOR_MAP_INTERLEAVE_NONE,
            m == TM_VP ? CU_TENSOR_MAP_SWIZZLE_NONE : CU_TENSOR_MAP_SWIZZLE_128B, CU_TENSOR_MAP_L2_PROMOTION_NONE, CU_TENSOR_MAP_FLOAT_OOB_FILL_NONE);
    }
    {
        const cuuint64_t dim[3] = {64, NHEAD * 3, D_MODEL}, str[2] = {128, NHEAD * DH * 2};
        const cuuint32_t box[3] = {64, 3, 32};
        enc(&P.tm[TM_WQ], CU_TENSOR_MAP_DATA_TYPE_BFLOAT16, 3, d_in[3], dim, str, box, ones, CU_TENSOR_MAP_INTERLEAVE_NONE,
            CU_TENSOR_MAP_SWIZZLE_128B, CU_TENSOR_MAP_L2_PROMOTION_NONE, CU_TENSOR_MAP_FLOAT_OOB_FILL_NONE);
    }
    {
        const cuuint64_t dim[2] = {DFF, D_MODEL}, str[1] = {DFF * 2};
        const cuuint32_t box[2] = {16, 128};
        enc(&P.tm[TM_W1], CU_TENSOR_MAP_DATA_TYPE_BFLOAT16, 2, d_in[6], dim, str, box, ones, CU_TENSOR_MAP_INTERLEAVE_NONE,
            CU_TENSOR_MAP_SWIZZLE_32B, CU_TENSOR_MAP_L2_PROMOTION_L2_128B, CU_TENSOR_MAP_FLOAT_OOB_FILL_NONE);
    }
    {
        const cuuint64_t dim[3] = {32, 20, NHEAD * DH}, str[2] = {64, D_MODEL * 2};
        const cuuint32_t box[3] = {32, 5, 16};
        enc(&P.tm[TM_WO], CU_TENSOR_MAP_DATA_TYPE_BFLOAT16, 3, d_in[4], dim, str, box, ones, CU_TENSOR_MAP_INTERLEAVE_NONE,
            CU_TENSOR_MAP_SWIZZLE_64B, CU_TENSOR_MAP_L2_PROMOTION_L2_128B, CU_TENSOR_MAP_FLOAT_OOB_FILL_NONE);
    }
    {
        const cuuint64_t dim[4] = {32, 20, 24, NHEAD * 8}, str[3] = {64, D_MODEL * 2, 24 * D_MODEL * 2};
        const cuuint32_t box[4] = {32, 5, 8, 4}, ones4[4] = {1, 1, 1, 1};
        enc(&P.tm[TM_WO4], CU_TENSOR_MAP_DATA_TYPE_BFLOAT16, 4, d_in[4], dim, str, box, ones4, CU_TENSOR_MAP_INTERLEAVE_NONE,
            CU_TENSOR_MAP_SWIZZLE_64B, CU_TENSOR_MAP_L2_PROMOTION_L2_128B, CU_TENSOR_MAP_FLOAT_OOB_FILL_NONE);
        const cuuint32_t thin[4] = {8, 5, 8, 4};
        enc(&P.tm[TM_WOP], CU_TENSOR_MAP_DATA_TYPE_BFLOAT16, 4, d_in[4], dim, str, thin, ones4, CU_TENSOR_MAP_INTERLEAVE_NONE,
            CU_TENSOR_MAP_SWIZZLE_NONE, CU_TENSOR_MAP_L2_PROMOTION_NONE, CU_TENSOR_MAP_FLOAT_OOB_FILL_NONE);
    }
    {
        const cuuint64_t dim[3] = {64, 10, DFF}, str[2] = {128, D_MODEL * 2};
        const cuuint32_t box[3] = {64, 10, 16};
        enc(&P.tm[TM_W2], CU_TENSOR_MAP_DATA_TYPE_BFLOAT16, 3, d_in[8], dim, str, box, ones, CU_TENSOR_MAP_INTERLEAVE_NONE,
            CU_TENSOR_MAP_SWIZZLE_128B, CU_TENSOR_MAP_L2_PROMOTION_NONE, CU_TENSOR_MAP_FLOAT_OOB_FILL_NONE);
    }
    P.x = (const __nv_bfloat16*)d_in[0];
    P.k = (const __nv_bfloat16*)d_in[1];
    P.v = (const __nv_bfloat16*)d_in[2];
    P.b1 = (const __nv_bfloat16*)d_in[7];
    P.b2 = (const __nv_bfloat16*)d_in[9];
    P.out = (__nv_bfloat16*)d_out;
    fused_kernel<<<NCTA + 1, NTHR, SM_TOTAL, cudaStreamPerThread>>>(P);
}
```

```cpp
#include <cuda_runtime.h>
#include <cuda_bf16.h>
#include <cuda.h>
#include <stdint.h>

#define DI __device__ __forceinline__

namespace {

constexpr int D_MODEL = 640, NHEAD = 32, SK = 32768, DH = 192, WIN = 4096, DFF = 1536;
constexpr int NCTA = 128, NTHR = 256;
constexpr int SUB = 8 * DH * 2;
constexpr int HT = 4 * SUB;
constexpr int WOU = 8 * 320;
constexpr int XCAP = 48;
constexpr int SM_RING = 1024;
constexpr int SM_W2 = SM_RING + 8 * WOU;
constexpr int SM_WQ = SM_RING + 5 * HT;
constexpr int SM_KS = SM_WQ + 5 * HT;
constexpr int SM_PART = SM_KS + 8 * HT;
constexpr int SM_BAR = SM_PART + 6144;
constexpr int SM_VEC = SM_BAR + 512;
constexpr int SM_QU = SM_VEC + 384;
constexpr int SM_ZQ = SM_QU + 384;
constexpr int SM_CS = SM_ZQ + 64;
constexpr int SM_XR = SM_CS + 768;
constexpr int SM_XM = SM_XR + XCAP * 16;
constexpr int SM_SH = SM_XM + XCAP * 4;
constexpr int SM_C1 = SM_SH + 1024;
constexpr int SM_B1 = SM_C1 + 320;
constexpr int SM_STAT = SM_B1 + 128;
constexpr int SM_QBAR = SM_STAT + 40;
constexpr int SM_CBAR = SM_QBAR + 8;
constexpr int SM_CNT = SM_CBAR + 128;
constexpr int SM_XN = SM_CNT + 56;
constexpr int SM_BIG = SM_XN + 4;
constexpr int SM_EPOCH = SM_BIG + 4;
constexpr int SM_FXS = SM_EPOCH + 4;
constexpr int SM_T0 = SM_FXS + 4;
constexpr int SM_JUNK = SM_T0 + 4;
constexpr int SM_TOTAL = 232448;
static_assert(SM_JUNK + 4 <= SM_RING + SM_TOTAL, "smem");

constexpr int SPIN = 1 << 20;
enum { TM_WQ = 0, TM_K = 1, TM_V = 2, TM_VP = 3, TM_V8 = 4, TM_WO = 5, TM_W1 = 6, TM_WO4 = 7, TM_W2 = 8, TM_WOP = 9 };
constexpr uint32_t POL_NORMAL = 0x16F00000u, POL_FIRST = 0x12F00000u;

constexpr int PACE = 484, PACE0 = 1800, WOPACE = 403, W1D = 100, W1G = 150, HZD = 9500;
constexpr int NP = 3, PUBAT = 8, ZCHK = 14;
constexpr int ODELAY = 250, AR1D = 500, AR1DN = 1000, AR2D = 600, S6D = 900, S6G = 100, I0D = 300, NPFC = 4;
constexpr int PFD = 1200, PFG = 150, KAD = 900;
constexpr unsigned long long VORD = 0x56784932a1b0cdefull;
constexpr int ISS = 0xf9e, NPK = 4, PK0 = 34, PK1 = 52, PKD = 21, P2A = -700, P2B = 400, P2W = 5700;
constexpr int PREP1 = 8, PREP2 = 9, PV2 = 7, HWAT = 8, PVNOW = 12, HWC = 11;
constexpr uint32_t FX2_MASK = 0xfff00000u;

struct Plan { int slot[17], par[17], ld[15]; bool ok; };
__host__ __device__ constexpr int cord(int s) { return s < 2 ? s : s + 1; }
constexpr Plan make_plan() {
    Plan s{};
    int phase[7] = {}, freeat[7] = {}, it = 7;
    for (int p = 0; p < 7; p++) { s.slot[p] = p; phase[p] = p != 1; freeat[p] = -1; }
    s.ok = true;
    for (int st = 0; st < 15; st++) {
        if (ISS >> st & 1) {
            int best = -1;
            for (int c = 0; c < 7; c++) if (freeat[c] >= 0 && (c < 5 || it < 13) && (best < 0 || freeat[c] < freeat[best])) best = c;
            if (best < 0 || it > 15) { s.ok = false; return s; }
            s.slot[it] = best; freeat[best] = -1;
            s.par[it] = phase[best]++ & 1;
            s.ld[st] = it++;
        }
        if (cord(st) >= it || (st >= 12 && s.slot[cord(st)] >= 5)) s.ok = false;
        freeat[s.slot[cord(st)]] = st;
    }
    s.slot[16] = 5; s.par[16] = phase[5] & 1;
    return s;
}
constexpr Plan PL = make_plan();
static_assert(PL.ok, "bad pass-2 plan");
__host__ __device__ constexpr int vunit(int p) { return (int)(VORD >> (4 * p) & 15); }

template <int I> struct IC { static constexpr int value = I; };
template <int A, int B, class F> DI void static_for(F&& f) {
    if constexpr (A < B) { f(IC<A>{}); static_for<A + 1, B>(f); }
}

struct Params {
    CUtensorMap tm[10];
    const __nv_bfloat16 *x, *b1, *b2, *k, *v;
    __nv_bfloat16* out;
};

typedef unsigned long long u64;
constexpr int ACC_PITCH = 256;
constexpr int ACC_BYTES = 80 * ACC_PITCH;
__device__ __align__(1024) unsigned char g_acc[4 * ACC_BYTES];
__device__ __align__(8192) u64 g_ll[NCTA][256];
__device__ unsigned g_epoch;
__device__ __align__(128) unsigned g_zflag;

DI void mbar_wait(uint32_t bar, uint32_t parity) {
    asm volatile("{\n.reg .pred p, q;\n.reg .u32 n;\nmov.u32 n, 0;\n"
                 "LOOP:\nmbarrier.try_wait.parity.shared::cta.b64 p, [%0], %1;\n"
                 "add.u32 n, n, 1;\nsetp.lt.and.u32 q, n, 0x100000, !p;\n@q bra.uni LOOP;\n}"
                 :: "r"(bar), "r"(parity) : "memory");
}
DI bool mbar_test(uint32_t bar, uint32_t parity) {
    uint32_t done;
    asm volatile("{\n.reg .pred p;\nmbarrier.test_wait.parity.shared::cta.b64 p, [%1], %2;\nselp.u32 %0, 1, 0, p;\n}" : "=r"(done) : "r"(bar), "r"(parity) : "memory");
    return __any_sync(~0u, done);
}
DI bool elect() {
    uint32_t r;
    asm volatile("{\n.reg .pred p;\nelect.sync _|p, 0xffffffff;\nselp.u32 %0, 1, 0, p;\n}" : "=r"(r));
    return r != 0;
}
DI void mbar_init(uint32_t bar, uint32_t n) { asm volatile("mbarrier.init.shared::cta.b64 [%0], %1;" :: "r"(bar), "r"(n) : "memory"); }
DI void mbar_arrive(uint32_t bar) { asm volatile("mbarrier.arrive.shared::cta.b64 _, [%0];" :: "r"(bar) : "memory"); }
DI void mbar_expect(uint32_t bar, uint32_t bytes) {
    asm volatile("mbarrier.arrive.expect_tx.shared::cta.b64 _, [%0], %1;" :: "r"(bar), "r"(bytes) : "memory");
}
DI void fence_async() { asm volatile("fence.proxy.async.shared::cta;" ::: "memory"); }
DI uint32_t ad(uint32_t a, uint32_t o) { uint32_t r; asm("add.u32 %0, %1, %2;" : "=r"(r) : "r"(a), "r"(o)); return r; }
DI uint4 lds128(uint32_t a, int o) {
    uint4 v; asm volatile("ld.shared.v4.u32 {%0,%1,%2,%3}, [%4];" : "=r"(v.x), "=r"(v.y), "=r"(v.z), "=r"(v.w) : "r"(ad(a, o)) : "memory"); return v;
}
DI void lds128(uint32_t* v, uint32_t a, int o) {
    asm volatile("ld.shared.v4.u32 {%0,%1,%2,%3}, [%4];" : "=r"(v[0]), "=r"(v[1]), "=r"(v[2]), "=r"(v[3]) : "r"(ad(a, o)) : "memory");
}
DI void lds64(uint32_t* v, uint32_t a, int o) { asm volatile("ld.shared.v2.u32 {%0,%1}, [%2];" : "=r"(v[0]), "=r"(v[1]) : "r"(ad(a, o)) : "memory"); }
DI uint4 ldsm_t(uint32_t a, int o) {
    uint4 v; asm volatile("ldmatrix.sync.aligned.m8n8.x4.trans.shared.b16 {%0,%1,%2,%3}, [%4];" : "=r"(v.x), "=r"(v.y), "=r"(v.z), "=r"(v.w) : "r"(ad(a, o)) : "memory"); return v;
}
DI uint2 lds64(uint32_t a, int o) { uint2 v; asm volatile("ld.shared.v2.u32 {%0,%1}, [%2];" : "=r"(v.x), "=r"(v.y) : "r"(ad(a, o)) : "memory"); return v; }
DI float2 lds64f(uint32_t a, int o) { const uint2 v = lds64(a, o); return make_float2(__uint_as_float(v.x), __uint_as_float(v.y)); }
DI uint32_t lds32(uint32_t a, int o) { uint32_t v; asm volatile("ld.shared.u32 %0, [%1];" : "=r"(v) : "r"(ad(a, o)) : "memory"); return v; }
DI float ldsf(uint32_t a, int o) { return __uint_as_float(lds32(a, o)); }
DI void sts32(uint32_t a, int o, uint32_t v) { asm volatile("st.shared.u32 [%0], %1;" :: "r"(ad(a, o)), "r"(v) : "memory"); }
DI void stsf(uint32_t a, int o, float v) { sts32(a, o, __float_as_uint(v)); }
DI void sts16(uint32_t a, int o, uint32_t v) { asm volatile("st.shared.u16 [%0], %1;" :: "r"(ad(a, o)), "h"((uint16_t)v) : "memory"); }
DI void sts64(uint32_t a, int o, uint32_t x, uint32_t y) { asm volatile("st.shared.v2.u32 [%0], {%1,%2};" :: "r"(ad(a, o)), "r"(x), "r"(y) : "memory"); }
DI void sts128(uint32_t a, int o, uint32_t x, uint32_t y, uint32_t z, uint32_t w) {
    asm volatile("st.shared.v4.u32 [%0], {%1,%2,%3,%4};" :: "r"(ad(a, o)), "r"(x), "r"(y), "r"(z), "r"(w) : "memory");
}
DI void sts128f_if(bool p, uint32_t a, int o, float x, float y, float z, float w) {
    asm volatile("{\n.reg .pred p;\nsetp.ne.u32 p, %5, 0;\n@p st.shared.v4.f32 [%0], {%1,%2,%3,%4};\n}" :: "r"(ad(a, o)), "f"(x), "f"(y), "f"(z), "f"(w), "r"((int)p) : "memory");
}
DI void sts32_if(bool p, uint32_t a, int o, uint32_t v) {
    asm volatile("{\n.reg .pred p;\nsetp.ne.u32 p, %2, 0;\n@p st.shared.u32 [%0], %1;\n}" :: "r"(ad(a, o)), "r"(v), "r"((int)p) : "memory");
}
DI uint32_t atoms_inc(uint32_t a, uint32_t lim) {
    uint32_t old; asm volatile("atom.relaxed.cta.shared.inc.u32 %0, [%1], %2;" : "=r"(old) : "r"(a), "r"(lim) : "memory"); return old;
}
DI void mma(float (&c)[4], uint32_t a0, uint32_t a1, uint32_t a2, uint32_t a3, uint32_t b0, uint32_t b1) {
    asm volatile("mma.sync.aligned.m16n8k16.row.col.f32.bf16.bf16.f32 {%0,%1,%2,%3}, {%4,%5,%6,%7}, {%8,%9}, {%0,%1,%2,%3};"
                 : "+f"(c[0]), "+f"(c[1]), "+f"(c[2]), "+f"(c[3]) : "r"(a0), "r"(a1), "r"(a2), "r"(a3), "r"(b0), "r"(b1));
}
DI void mma(float (&c)[4], const uint4& a, uint32_t b0, uint32_t b1) { mma(c, a.x, a.y, a.z, a.w, b0, b1); }
DI void zero4(float (&c)[4]) { c[0] = c[1] = c[2] = c[3] = 0.f; }
DI u64 ld_rlx(const void* p) {
    u64 a; asm volatile("ld.relaxed.gpu.global.u64 %0, [%1];" : "=l"(a) : "l"(p) : "memory"); return a;
}
DI void st_rlx(void* p, u64 a) { asm volatile("st.relaxed.gpu.global.u64 [%0], %1;" :: "l"(p), "l"(a) : "memory"); }
DI uint4 ldg128(const void* p) {
    uint4 v; asm volatile("ld.global.nc.L1::no_allocate.L2::cache_hint.v4.u32 {%0,%1,%2,%3}, [%4], %5;" : "=r"(v.x), "=r"(v.y), "=r"(v.z), "=r"(v.w) : "l"(p), "l"((u64)POL_FIRST << 32)); return v;
}
DI float bf_lo(uint32_t u) { return __uint_as_float(u << 16); }
DI float bf_hi(uint32_t u) { return __uint_as_float(u & 0xffff0000u); }
DI uint32_t pack_bf(float lo, float hi) {
    uint32_t r; asm("cvt.rn.bf16x2.f32 %0, %1, %2;" : "=r"(r) : "f"(hi), "f"(lo)); return r;
}
DI uint32_t pick(uint32_t a, uint32_t sel) { uint32_t r; asm("prmt.b32 %0, %1, 0, %2;" : "=r"(r) : "r"(a), "r"(sel)); return r; }
DI uint32_t bf2_amax(uint32_t a, uint32_t b) { uint32_t r; asm("max.NaN.xorsign.abs.bf16x2 %0, %1, %2;" : "=r"(r) : "r"(a), "r"(b)); return r; }
DI uint32_t bf2_amin(uint32_t a, uint32_t b) { uint32_t r; asm("min.xorsign.abs.bf16x2 %0, %1, %2;" : "=r"(r) : "r"(a), "r"(b)); return r; }
DI uint32_t bf2_mulv(uint32_t a, uint32_t b) { uint32_t r; asm volatile("mul.rn.bf16x2 %0, %2, %1;" : "=r"(r) : "r"(a), "r"(b)); return r; }
DI uint32_t bf2_mul(uint32_t a, uint32_t b) { uint32_t r; asm("mul.rn.bf16x2 %0, %1, %2;" : "=r"(r) : "r"(a), "r"(b)); return r; }
DI uint32_t bf2_fma(uint32_t a, uint32_t b, uint32_t c) { uint32_t r; asm("fma.rn.bf16x2 %0, %1, %2, %3;" : "=r"(r) : "r"(a), "r"(b), "r"(c)); return r; }
DI float ex2(float v) { float r; asm("ex2.approx.ftz.f32 %0, %1;" : "=f"(r) : "f"(v)); return r; }
DI float rcp(float v) { float r; asm("rcp.approx.ftz.f32 %0, %1;" : "=f"(r) : "f"(v)); return r; }
DI float rsq(float v) { float r; asm("rsqrt.approx.ftz.f32 %0, %1;" : "=f"(r) : "f"(v)); return r; }
DI void bar_sync(int id, int n) { asm volatile("bar.sync %0, %1;" :: "r"(id), "r"(n) : "memory"); }
DI uint32_t clk() { uint32_t c; asm volatile("mov.u32 %0, %clock;" : "=r"(c)); return c; }
DI uint32_t gtime() { uint32_t c; asm volatile("mov.u32 %0, %globaltimer_lo;" : "=r"(c)); return c; }
DI uint32_t pin(uint32_t v) { return __shfl_xor_sync(~0u, v, 0); }
DI float pinf(float v) { return __shfl_xor_sync(~0u, v, 0); }
template <class T> DI T* pinp(T* p) { return reinterpret_cast<T*>(__shfl_xor_sync(~0u, (u64)p, 0)); }
DI u64 mk64(uint32_t lo, uint32_t hi) { u64 r; asm("mov.b64 %0, {%1, %2};" : "=l"(r) : "r"(lo), "r"(hi)); return r; }
DI float shx(float v, int o) { return __shfl_xor_sync(~0u, v, o); }

DI u64 fx_pack(float v) {
    u64 r; asm("{\n.reg .u32 a, b;\n.reg .s64 w;\ncvt.rni.s64.f32 w, %1;\nmov.b64 {a, b}, w;\nprmt.b32 a, a, 1, 0x3214;\nmov.b64 %0, {a, b};\n}" : "=l"(r) : "f"(v)); return r;
}
DI float fx_scale(float meansq) {
    const int e = max(((int)(__float_as_uint(meansq) >> 23) - 127) >> 1, -14);
    return __uint_as_float((uint32_t)(127 + 32 - e) << 23);
}
DI float fx_inv(float scale) { return __uint_as_float((254u << 23) - __float_as_uint(scale)); }
DI uint32_t lo32(u64 w) { uint32_t l; asm("mov.b64 {%0, _}, %1;" : "=r"(l) : "l"(w)); return l; }
DI int hi32(u64 w) { int h; asm("mov.b64 {_, %0}, %1;" : "=r"(h) : "l"(w)); return h; }
DI float fx_val(u64 w) { return (float)hi32(w) * 4294967296.f + (float)lo32(w); }
DI void fx_poll(const unsigned char* ap, u64 (&w)[4]) {
    asm volatile("{\n.reg .pred p, q;\n.reg .u32 n, a, b, c, d;\nmov.u32 n, 0;\nLOOP:\n"
                 "ld.relaxed.gpu.global.u64 %0, [%4];\nld.relaxed.gpu.global.u64 %1, [%4+5120];\n"
                 "ld.relaxed.gpu.global.u64 %2, [%4+10240];\nld.relaxed.gpu.global.u64 %3, [%4+15360];\n"
                 "add.u32 n, n, 1;\nsetp.ge.u32 q, n, 0x100000;\n@q bra.uni DONE;\n"
                 "mov.b64 {a, _}, %0;\nmov.b64 {b, _}, %1;\nmov.b64 {c, _}, %2;\nmov.b64 {d, _}, %3;\n"
                 "lop3.b32 a, a, b, c, 0x80;\nlop3.b32 a, a, d, 32, 0x80;\nsetp.eq.u32 p, a, 0;\n"
                 "vote.sync.any.pred p, p, 0xffffffff;\n@p bra.uni LOOP;\nDONE:\n}"
                 : "=l"(w[0]), "=l"(w[1]), "=l"(w[2]), "=l"(w[3]) : "l"(ap) : "memory");
}
constexpr u64 FX2_INIT = 256ull + 32 - 96 * ((1ull << 28) + (1ull << 55)), FX2_NONE = 1ull + (1ull << 28) + (1ull << 55);
constexpr float FX2_MAGIC = 12582912.f + 524288.f;

DI void tma3(uint32_t dst, const CUtensorMap* tm, int c1, int c2, uint32_t bar, uint32_t pol) {
    asm volatile("cp.async.bulk.tensor.3d.shared::cluster.global.mbarrier::complete_tx::bytes.L2::cache_hint [%0], [%1, {%2, %3, %4}], [%5], %6;"
                 :: "r"(dst), "l"(tm), "r"(0), "r"(c1), "r"(c2), "r"(bar), "l"((u64)pol << 32) : "memory");
}
DI void tma3_pf(const CUtensorMap* tm, int c1, int c2, uint32_t pol) {
    asm volatile("cp.async.bulk.prefetch.tensor.3d.L2.global.tile.L2::cache_hint [%0, {%1, %2, %3}], %4;"
                 :: "l"(tm), "r"(0), "r"(c1), "r"(c2), "l"((u64)pol << 32) : "memory");
}
DI void bulk_pf(const void* p, uint32_t bytes, uint32_t pol) {
    asm volatile("cp.async.bulk.prefetch.L2.global.L2::cache_hint [%0], %1, %2;" :: "l"(p), "r"(bytes), "l"((u64)pol << 32) : "memory");
}
DI float warp_max(float v) {
    const int k = __float_as_int(v), m = __reduce_max_sync(~0u, k ^ ((k >> 31) & 0x7fffffff));
    return __int_as_float(m ^ ((m >> 31) & 0x7fffffff));
}
DI u64 ll_pack2(float a, float b, uint32_t tag) { return mk64(__byte_perm(__float_as_uint(a), tag, 0x3214), __float_as_uint(b)); }
DI float lof(u64 w) { return __uint_as_float(lo32(w)); }
DI float hif(u64 w) { return __int_as_float(hi32(w)); }
DI void ll_gather4(const u64* buf, uint32_t tag, u64 (&w)[4]) {
#pragma unroll 1
    for (int it = 0; it < SPIN; it++) {
        if (it) { w[0] = ld_rlx(buf); w[1] = ld_rlx(buf + 256); w[2] = ld_rlx(buf + 512); w[3] = ld_rlx(buf + 768); }
        if (!__any_sync(~0u, (((lo32(w[0]) ^ tag) | (lo32(w[1]) ^ tag)) | ((lo32(w[2]) ^ tag) | (lo32(w[3]) ^ tag))) & 255)) break;
    }
}
DI u64 lds_u64(uint32_t a, int o) { const uint2 v = lds64(a, o); return v.x | (u64)v.y << 32; }
DI float sum8(uint32_t a, int o, int pitch) {
    float s[8];
#pragma unroll
    for (int w = 0; w < 8; w++) s[w] = ldsf(a, o + w * pitch);
    return ((s[0] + s[1]) + (s[2] + s[3])) + ((s[4] + s[5]) + (s[6] + s[7]));
}
DI void ln_final(float& mean, float& rstd, float& msq) {
    float2 v[5];
#pragma unroll
    for (int w = 0; w < 5; w++) v[w] = lds64f(0, SM_STAT + w * 8);
    mean = (((v[0].x + v[1].x) + (v[2].x + v[3].x)) + v[4].x) * (1.f / D_MODEL);
    msq = (((v[0].y + v[1].y) + (v[2].y + v[3].y)) + v[4].y) * (1.f / D_MODEL);
    rstd = rsq(fmaxf(msq - mean * mean, 0.f) + 1e-5f);
}
constexpr float CS = 0.07216878364870322f * 1.4426950408889634f;
constexpr uint32_t ONES = 0x3f803f80u;

__global__ void __launch_bounds__(NTHR, 1) fused_kernel(const __grid_constant__ Params P) {
    extern __shared__ __align__(1024) unsigned char smem[];
    const int warp = __shfl_sync(~0u, threadIdx.x >> 5, 0), bx = blockIdx.x;
    const int cta = (((bx >> 1) & 15) + (bx >> 6) * 16) * 4 + ((bx >> 5) & 1) * 2 + (bx & 1);

    if (bx == NCTA) {
        if ((uint32_t)__cvta_generic_to_shared(smem) != SM_RING) __trap();
        const uint32_t ep = *(volatile unsigned*)&g_epoch;
        if (threadIdx.x == 0) {
#pragma unroll 1
            for (int it = 0; it < SPIN; it++) { if ((lo32(ld_rlx(&g_ll[0][192])) & 255) == ((ep * 8 + 1) & 255)) break; __nanosleep(200); }
            const uint32_t t0 = gtime();
#pragma unroll 1
            for (int it = 0; it < 1024; it++) { if (gtime() - t0 > HZD) break; __nanosleep(100); }
        }
        __syncthreads();
#pragma unroll 1
        for (int i = threadIdx.x; i < 4 * 80 * 8; i += NTHR)
        {
            const u64 v = (i / 640 & 1) && (i & 7) < 2 ? FX2_INIT : 0ull;
            *reinterpret_cast<ulonglong2*>(g_acc + (i >> 3) * ACC_PITCH + (i & 7) * 16) = make_ulonglong2(v, v);
        }
        __threadfence();
        __syncthreads();
        if (threadIdx.x == 0) asm volatile("st.relaxed.gpu.global.u32 [%0], %1;" :: "l"(&g_zflag), "r"(ep + 1) : "memory");
        return;
    }
    const uint32_t barw = SM_BAR + warp * 64;
    if (elect()) {
        if (warp < 3) sts32(0, SM_T0, gtime());
        else {
            mbar_init(barw + 56, 1);
            asm volatile("fence.mbarrier_init.release.cluster;" ::: "memory");
            mbar_expect(barw + 56, HT);
            tma3(SM_WQ - 3 * HT + warp * HT, &P.tm[TM_WQ], (cta >> 2) * 3, (cta & 3) * 160 - 96 + warp * 32, barw + 56, POL_FIRST);
        }
    }
    int tid = threadIdx.x, lane, g, t, c4;
    uint32_t selA, selB, offV0, offV2;
    auto derive = [&]() {
        lane = tid & 31; g = lane >> 2; t = lane & 3;
        c4 = (tid & 0xe1) + 16 * (t >> 1) + 2 * g;
        selA = (g & 2) ? 0x4444u : (g & 1) ? 0x1044u : 0x4410u;
        selB = (g & 2) ? ((g & 1) ? 0x1044u : 0x4410u) : 0x4444u;
        offV0 = (6 * t) * 128 + ((g ^ ((6 * t) & 7)) << 4);
        offV2 = (6 * t) * 128 + ((g ^ ((6 * t + 2) & 7)) << 4);
    };
    auto refresh = [&]() { tid = pin(tid); derive(); };
    auto refresh_late = [&]() { mbar_wait(SM_BAR + 3 * 64 + 56, 0); refresh(); };
    derive();
    const int j40 = (cta & 3) * 40;
    const bool mlp = (cta & 3) != 3;
    const int hu = ((cta >> 2) * 3 + (cta & 3)) * 16;
    uint2 xp = make_uint2(0, 0);
    if (tid < 160) xp = *reinterpret_cast<const uint2*>(P.x + 4 * c4);
    else if (tid == 192) xp.x = *(volatile unsigned*)&g_epoch;
    else if (tid >= 224 && tid < 240 && mlp) xp.x = reinterpret_cast<const unsigned short*>(P.b1)[hu + lane];
    __syncwarp();
    if (elect()) {
#pragma unroll
        for (int i = 0; i < 7; i++) mbar_init(barw + i * 8, 1);
        if (warp < 4) mbar_arrive(barw);
        mbar_init(SM_CBAR + warp * 8, 1); mbar_init(SM_CBAR + 64 + warp * 8, 1);
        if (warp == 0) { mbar_init(SM_QBAR, 6); mbar_init(SM_BAR + 56, 8); }
        asm volatile("fence.mbarrier_init.release.cluster;" ::: "memory");
        sts64(warp * 8, SM_CNT, 0, 0);
        sts64(warp * 8, SM_ZQ, 0, 0);
    }
    uint32_t kc[192];
#pragma unroll
    for (int i = 12; i < 192; i++) asm volatile("mov.b32 %0, 0;" : "=r"(kc[i]));
    const int rowc = (cta >> 2) * SK + (SK - WIN) + (cta & 3) * 64;
    const int roww = __shfl_sync(~0u, rowc + warp * 8, 0);
    const CUtensorMap* tmk = reinterpret_cast<const CUtensorMap*>(__shfl_sync(~0u, (u64)&P.tm[0] + (lane >> 5), 0));

    auto wait_due = [&](int i, int extra) {
        const uint32_t due = lds32(0, SM_T0) + PACE0 + extra + i * PACE;
#pragma unroll 1
        for (int it = 0; it < 4096; it++) if ((int)(gtime() - due) >= 0) break;
    };
    auto issue_wo = [&](int k) {
        wait_due(64, k * WOPACE);
        mbar_expect(SM_CBAR + 32 + k * 8, 4 * WOU);
        asm volatile("cp.async.bulk.tensor.4d.shared::cluster.global.mbarrier::complete_tx::bytes.L2::cache_hint [%0], [%1, {%2, %3, %4, %5}], [%6], %7;"
                     :: "r"(SM_RING + k * 4 * WOU), "l"(tmk + TM_WO4), "r"(0), "r"(5 * (cta & 3)), "r"((k >> 1) * 8), "r"((cta >> 2) * 8 + (k & 1) * 4),
                        "r"(SM_CBAR + 32 + k * 8), "l"((u64)POL_FIRST << 32) : "memory");
        if (k < 4 && mlp)
            asm volatile("cp.async.bulk.prefetch.tensor.4d.L2.global.tile.L2::cache_hint [%0, {%1, %2, %3, %4}], %5;"
                         :: "l"(tmk + TM_WOP), "r"(0), "r"(5 * (cta & 3)), "r"((k >> 1) * 8), "r"((cta >> 2) * 8 + (k & 1) * 4), "l"((u64)POL_NORMAL << 32) : "memory");
    };
    auto issue_kv = [&](int i, int slot, int bar) {
        const int row = rowc + (i & 30) * 128 + (i & 1) * 32;
        mbar_expect(SM_CBAR + bar * 8, HT);
        tma3(SM_RING + slot * HT, tmk + TM_K + (i >> 5), 0, row, SM_CBAR + bar * 8, POL_FIRST);
        if (i >= 32) tma3_pf(tmk + TM_VP, 0, row, POL_NORMAL);
    };
    __syncwarp();
    if (warp < 3) { wait_due(warp, 0); if (elect()) issue_kv(warp, warp + 1, warp); }
    else mbar_wait(barw + 56, 0);
    if (tid == 192) sts32(0, SM_EPOCH, xp.x);
    if (tid >= 224 && tid < 240) sts32(lane * 4, SM_B1, xp.x << 16);
    __syncthreads();
    if ((warp == 3 || warp == 4) && elect()) issue_kv(warp, warp == 4 ? 0 : 4, warp);
    const uint32_t ep4 = __shfl_sync(~0u, lds32(0, SM_EPOCH) * 4, 0);

    auto load_v3 = [&](uint4* v, uint32_t u, int o, bool odd) {
        if (!odd) { v[0] = lds128(ad(offV0, u), o); v[1] = lds128(ad(offV0 ^ 16, u), o + 128); v[2] = lds128(ad(offV2, u), o + 256); }
        else { v[0] = lds128(ad(offV2 ^ 16, u), o + 384); v[1] = lds128(ad(offV0 ^ 64, u), o + 512); v[2] = lds128(ad(offV0 ^ 80, u), o + 640); }
    };
    auto load_v = [&](uint4 (&v)[6], uint32_t u, int o) { load_v3(v, u, o, false); load_v3(v + 3, u, o, true); };
    const uint32_t wqw = warp * SUB, ksw = warp * HT;
    auto slot_o = [&](int s) { return s < 3 ? SM_WQ + s * 8 * SUB : SM_KS + (s - 3) * SUB; };
    auto slot_u = [&](int s) { return s < 3 ? wqw : ksw; };
    const uint32_t zero = __shfl_sync(~0u, lds32(0, SM_ZQ), 0);
    auto issue2 = [&](auto I, uint32_t dep) {
        constexpr int p = I.value, s = PL.slot[p];
        __syncwarp();
        if ((p < 16 || mlp) && elect()) {
            mbar_expect(barw + s * 8, (dep & zero) | (p < 16 ? SUB : 2 * WOU + 256));
            if constexpr (p < 16) tma3(slot_u(s) + slot_o(s), tmk + TM_V8, 0, roww + vunit(p) * 256, barw + s * 8, POL_FIRST);
            else {
                tma3(slot_u(s) + slot_o(s), tmk + TM_WO, 5 * (cta & 3), (cta >> 2) * DH + warp * 24, barw + s * 8, POL_FIRST);
                asm volatile("cp.async.bulk.shared::cluster.global.mbarrier::complete_tx::bytes [%0], [%1], 256, [%2];"
                             :: "r"(slot_u(s) + slot_o(s) + 2 * WOU), "l"(P.b2 + min(warp, 4) * 128), "r"(barw + s * 8) : "memory");
            }
        }
    };
    auto touch2 = [&]() {
        const char* p = reinterpret_cast<const char*>(P.v) + (size_t)(roww + vunit(2) * 256) * (DH * 2) + lane * 32;
#pragma unroll
        for (int i = 0; i < 3; i++) asm volatile("cp.async.ca.shared.global [%0], [%1], 4;" :: "r"(SM_JUNK), "l"(p + i * 1024) : "memory");
    };
    auto issue_help = [&]() {
        if (elect())
            tma3(SM_WQ + (warp == 7 ? 0 : warp == 6 ? 16 * SUB : 4 * SUB), tmk + (warp == 5 ? TM_V8 : TM_V), 0,
                 rowc + (warp == 6 ? vunit(2) * 256 : warp == 5 ? vunit(0) * 256 + 32 : vunit(0) * 256), warp == 5 ? SM_BAR + 4 * 64 : SM_CBAR - 32 + warp * 8, POL_FIRST);
    };
    auto issue_item1 = [&]() {
        if (elect()) {
            mbar_expect(SM_CBAR - 48 + warp * 8, HT);
            tma3(SM_WQ - 4 * HT + warp * HT, tmk + TM_V, 0, rowc - 192 + warp * 32 + vunit(1) * 256, SM_CBAR - 48 + warp * 8, POL_FIRST);
        }
    };
    const uint32_t prow = warp * 768;
    uint4 wq0[6], wqh[3];
    uint32_t xna;
    auto load_wq = [&]() {
        load_v(wq0, wqw, SM_WQ);
        const int r0 = 6 * t + 3 * (warp & 1);
#pragma unroll
        for (int j = 0; j < 3; j++) wqh[j] = lds128(ad(r0 * 128 + ((g ^ ((r0 + j) & 7)) << 4), (warp >> 1) * SUB), SM_WQ + 16 * SUB + j * 128);
        const int r = c4 - j40;
        xna = pin((tid < 160 && r >= 0 && r < 40) ? SM_VEC + r * 8 : 0u);
        selA = pin(selA); selB = pin(selB);
        offV0 = pin(offV0 + wqw); offV2 = pin(offV2 + wqw);
        tid = pin(tid);
    };
    float acc[3][4];
    auto mma3 = [&](const uint4* v, uint32_t pp, uint32_t hi) {
        const uint32_t b0 = pick(pp, selA | hi), b1 = pick(pp, selB | hi);
        mma(acc[0], v[0], b0, b1); mma(acc[1], v[1], b0, b1); mma(acc[2], v[2], b0, b1);
    };
    auto ln_part = [&]() {
        const float x0 = bf_lo(xp.x), x1 = bf_hi(xp.x), x2 = bf_lo(xp.y), x3 = bf_hi(xp.y);
        const float s1 = (x0 + x1) + (x2 + x3), s2 = (x0 * x0 + x1 * x1) + (x2 * x2 + x3 * x3);
        float ss = ((tid & 16) ? s2 : s1) + shx((tid & 16) ? s1 : s2, 16);
        ss += shx(ss, 8); ss += shx(ss, 4); ss += shx(ss, 2); ss += shx(ss, 1);
        sts32_if((tid & 15) == 0 && tid < 160, tid >> 2, SM_STAT, __float_as_uint(ss));
    };

    auto tick = [&](uint4& v) {
        asm volatile("{\n.reg .pred p;\nsetp.ne.u32 p, %4, 0;\n@p mma.sync.aligned.m16n8k16.row.col.f32.bf16.bf16.f32 {%0,%1,%2,%3}, {%0,%1,%2,%3}, {%0,%1}, {%0,%1,%2,%3};\n}"
                     : "+r"(v.x), "+r"(v.y), "+r"(v.z), "+r"(v.w) : "r"(zero));
    };

    auto q_stage = [&](auto L) {
        constexpr int layer = L.value;
        asm volatile("{\n.reg .pred p;\nsetp.ne.u32 p, %0, 0;\n@p st.shared.v2.u32 [%0], {%1,%2};\n}" :: "r"(xna), "r"(xp.x), "r"(xp.y) : "memory");
        uint4 wq1[6];
        load_v3(wq1, 0, SM_WQ + 8 * SUB, false);
        const uint32_t xra = (tid & 3) * 4;
        __syncthreads();
        uint32_t p0 = lds32(ad(xra, warp * 16), SM_VEC), ph = lds32(ad(xra, (warp >> 1) * 16), SM_VEC + 256), p1 = lds32(ad(xra, warp * 16), SM_VEC + 128);
        if (layer == 0 && (tid & 16)) p0 = p1 = ph = ONES;
#pragma unroll
        for (int j = 0; j < 3; j++) zero4(acc[j]);
        mma3(wq0, p0, 0); mma3(wq0 + 3, p0, 0x2222);
        load_v3(wq1 + 3, 0, SM_WQ + 8 * SUB, true);
        mma3(wqh, ph, (warp & 1) * 0x2222); mma3(wq1, p1, 0); mma3(wq1 + 3, p1, 0x2222);
        if (layer == 1) { lds128(kc + 8, prow + (tid & 31) * 16, SM_PART); lds64(kc + 88, prow + (tid & 31) * 8, SM_PART + 512); __syncwarp(); }
        const uint32_t qpa = ((layer == 0 && (tid & 2)) ? ksw - (SM_PART - SM_KS - 11264) : prow) + (tid & 28) * 8 + (tid & 1) * 16;
#pragma unroll
        for (int j = 0; j < 3; j++) sts128f_if(layer == 0 || !(tid & 2), qpa, SM_PART + j * 256, acc[j][0], acc[j][1], acc[j][2], acc[j][3]);
        u64* dst = &g_ll[cta][tid];
        __syncthreads();
        if (warp < 6) {
            const float s = sum8(tid * 4, SM_PART, 768);
            st_rlx(dst, layer ? mk64(2 * ep4 + 5, __float_as_uint(s)) : ll_pack2(__uint_as_float(__float_as_uint(sum8(tid * 4, SM_KS + 11264, HT)) + 128), s, 2 * ep4 + 1));
        } else if (layer == 1) { sts32(0, SM_T0, gtime()); issue_item1(); }
        refresh_late();
        ln_part();
        __syncthreads();
        sts64(prow + lane * 8, SM_PART, xp.x, xp.y);
    };
    auto q_addr = [&]() { return (((tid >> 1) & 1) * 4 + ((tid >> 4) & 3)) * 48 + ((tid >> 6) * 2 + ((tid >> 3) & 1)) * 8 + ((tid >> 2) & 1) * 4 + (tid & 1) * 2; };
    auto score6 = [&](const uint4 (&v)[6], const uint32_t (&qf)[12]) {
        float d[2][4];
#pragma unroll
        for (int i = 0; i < 6; i++) { if (i < 2) zero4(d[i]); mma(d[i & 1], v[i], qf[2 * i], qf[2 * i + 1]); }
        return (d[0][0] + d[0][3]) + (d[1][0] + d[1][3]);
    };
    auto softmax = [&](auto L, const float (&S)[4]) {
        constexpr int layer = L.value;
        const float mrun = warp_max(fmaxf(fmaxf(S[0], S[1]), fmaxf(S[2], S[3])));
        const float p0 = ex2((S[0] - mrun) * CS), p1 = ex2((S[1] - mrun) * CS), p2 = ex2((S[2] - mrun) * CS), p3 = ex2((S[3] - mrun) * CS);
        const uint32_t pa = pack_bf(p0, p1), pb = pack_bf(p2, p3), pw = prow + t * 64 + g * 2;
        sts16(pw, SM_PART + 256, pa); sts16(pw, SM_PART + 272, pa >> 16); sts16(pw, SM_PART + 288, pb); sts16(pw, SM_PART + 304, pb >> 16);
        const uint32_t l = __reduce_add_sync(~0u, __float2uint_rn(((p0 + p1) + (p2 + p3)) * 16777216.f));
        st_rlx(&g_ll[cta][192 + warp], mk64(__byte_perm(l + 128, 2 * ep4 + 1 + 4 * layer, 0x3214), __float_as_uint(mrun)));
        __syncwarp();
#pragma unroll
        for (int j = 0; j < 3; j++) zero4(acc[j]);
    };
    auto pv = [&](const uint4 (&v)[6], uint32_t pp) { mma3(v, pp, 0); mma3(v + 3, pp, 0x2222); };

    auto head_look = [&]() {
        if (lane < 16) asm volatile("cp.async.cg.shared.global [%0], [%1], 16;" :: "r"(SM_PART + 512 + prow + lane * 16), "l"(&g_ll[cta ^ g][192 + 2 * t]) : "memory");
    };
    float fw;
    auto head_weight = [&](auto L) {
        const uint32_t tag = (2 * ep4 + 1 + 4 * L.value) & 255;
        uint32_t l, m;
#pragma unroll 1
        for (int it = 0; it < SPIN; it++) {
            if (it) head_look();
            asm volatile("cp.async.wait_all;" ::: "memory");
            __syncwarp();
            asm volatile("ld.volatile.shared.v2.u32 {%0,%1}, [%2];" : "=r"(l), "=r"(m) : "r"(SM_PART + 512 + prow + lane * 8) : "memory");
            l ^= tag;
            if (!__any_sync(~0u, l & 255)) break;
        }
        const float f = ex2((__uint_as_float(m) - warp_max(__uint_as_float(m))) * CS);
        const uint32_t Lh = __reduce_add_sync(~0u, __float2uint_rn(f * (float)l * 0.03125f));
        fw = __shfl_sync(~0u, f, warp) * rcp((float)Lh) * (ldsf(0, SM_FXS) * 524288.f);
    };

    uint32_t wa[5], ya, oa, selC, selD;
    uint4 z[5];
    unsigned char* ra;
    const u64* lp;
    auto load_u = [&](uint4 (&a)[5], uint32_t u, int o) {
#pragma unroll
        for (int k = 0; k < 5; k++) a[k] = lds128(ad(wa[k], u), o);
    };
    auto tail_prep1 = [&](auto L) {
        xp = lds64(prow + lane * 8, SM_PART);
        ya = pin(prow + (8 * g + 4 * (t & 1)) * 4);
        oa = pin(((tid >> 5) * 12 + min(lane, 11)) * 8);
        lp = pinp(reinterpret_cast<const u64*>(reinterpret_cast<const char*>(&g_ll[cta][0]) + oa));
    };
    auto tail_prep2 = [&](auto L) {
#pragma unroll
        for (int k = 0; k < 5; k++) {
            const int row = (t & 1) + 2 * (t & 2) + 2 * (k < 4 ? k >> 1 : g >> 2), j = k < 4 ? 2 * (k & 1) + (g >> 2) : 4;
            wa[k] = pin(row * 320 + j * 64 + (((g & 3) ^ (((5 * row + j) >> 1) & 3)) << 4));
        }
        selA = pin(selA); selB = pin(selB);
        selC = selA | (g >> 2) * 0x2222; selD = selB | (g >> 2) * 0x2222;
    };
    auto red_addr = [&](auto L) {
        const int word = t * 160 + j40 + (tid >> 2);
        ra = pinp(g_acc + 2 * L.value * ACC_BYTES + (uint32_t)((word >> 3) * ACC_PITCH + (word & 7) * 8));
    };
    uint4 wf[8], w2r[8];
    uint32_t la, w2a, hpa, ha, *op;
    uint2 b2v;
    const unsigned char* ap;
    unsigned char* ap2;
    float inv1;
    auto load_w1 = [&]() {
#pragma unroll
        for (int j = 0; j < 8; j++) wf[j] = ldsm_t(la, SM_RING + j * 256);
    };
    auto load_w2 = [&]() {
#pragma unroll
        for (int i = 0; i < 8; i++) w2r[i] = lds128(w2a ^ ((i & 1) * 16), SM_W2 + (i >> 1) * 5120 + (i & 1) * 128);
    };
    auto load_b2 = [&]() { asm volatile("ld.global.nc.v2.u32 {%0,%1}, [%2];" : "=r"(b2v.x), "=r"(b2v.y) : "l"(P.b2 + 4 * min(c4, 159))); };
    auto mlp_prep = [&](auto L) {
        unsigned char* const accb = g_acc + 2 * L.value * ACC_BYTES;
        la = (tid >> 5) * 4096 + (64 * ((lane >> 2) & 1) + 4 * ((lane >> 1) & 1) + (lane & 1) + 2 * (lane >> 4)) * 32 + ((((lane >> 3) ^ (lane >> 1)) & 1) << 4);
        w2a = pin((10 * t + 2 * (tid >> 5)) * 128 + ((g ^ ((2 * t + 2 * (tid >> 5)) & 7)) << 4));
        hpa = pin((tid >> 5) * 64 + (t * 8 + g) * 4); ha = pin((lane & 15) * 4);
        if (L.value == 0) { selA = pin(selA); selB = pin(selB); tid = pin(tid); }
        ap = accb + (uint32_t)((c4 >> 3) * ACC_PITCH + (c4 & 7) * 8);
        ap2 = accb + ACC_BYTES + pin((c4 >> 2) * ACC_PITCH + (c4 & 3) * 8);
        if (L.value == 1) ap2 = pinp(ap2);
        inv1 = fx_inv(ldsf(0, SM_FXS));
        if (L.value == 1) { ap = pinp(ap); la = pin(la); op = pinp(reinterpret_cast<uint32_t*>(P.out) + 2 * c4); }
    };
    auto tail = [&](auto L) {
        constexpr int layer = L.value;
        uint32_t cq;
        auto park = [&]() { const int ln = pin(tid) & 31; sts128(prow + ln * 16, SM_PART, kc[8], kc[9], kc[10], kc[11]); sts64(prow + ln * 8, SM_PART + 512, kc[88], kc[89]); };
        {
#pragma unroll
            for (int j = 0; j < 3; j++) sts128f_if(!(tid & 2), ya, SM_PART + 256 * j, acc[j][0] * fw, acc[j][2] * fw, acc[j][1] * fw, acc[j][3] * fw);
            const uint32_t tag = (2 * ep4 + 3 + 4 * layer) & 255;
            __syncthreads();
            float2 own;
            {
                float2 s[8];
#pragma unroll
                for (int w = 0; w < 8; w++) s[w] = lds64f(oa, SM_PART + w * 768);
                own.x = ((s[0].x + s[1].x) + (s[2].x + s[3].x)) + ((s[4].x + s[5].x) + (s[6].x + s[7].x));
                own.y = ((s[0].y + s[1].y) + (s[2].y + s[3].y)) + ((s[4].y + s[5].y) + (s[6].y + s[7].y));
                st_rlx(const_cast<u64*>(lp), ll_pack2(own.x, own.y, tag));
            }
            const uint32_t c0 = clk();
            if (layer == 0) refresh_late();
            uint4 v[5], u[5];
            if constexpr (layer == 0) {
                if (warp < 3) { if (elect()) issue_wo(3 + warp); __syncwarp(); }
                if (warp >= 4) touch2();
                tail_prep2(L);
                mbar_wait(SM_CBAR + 32 + (warp >> 2) * 8, 0);
                load_u(v, warp * WOU, SM_RING);
                __syncthreads();
            }
            constexpr int YP = layer ? SM_WQ : SM_PART;
            float y[3][4];
#pragma unroll
            for (int j = 0; j < 3; j++) zero4(y[j]);
            const u64 *l1 = reinterpret_cast<const u64*>((u64)lp ^ 4096), *l2 = reinterpret_cast<const u64*>((u64)lp ^ 2048), *l3 = reinterpret_cast<const u64*>((u64)lp ^ 6144);
            tick(layer ? z[0] : v[0]);
            if (layer) while (clk() - c0 < ODELAY);
            uint32_t w1due = 0;
            if (layer == 0) {
                const uint32_t now = gtime();
                w1due = lds32(0, SM_T0) + PACE0 + 69 * PACE + W1D;
                w1due = ((int)(now - w1due) > 0 ? now : w1due) + (warp - 3) * W1G;
            }
            u64 w1 = ld_rlx(l1), w2 = ld_rlx(l2), w3 = ld_rlx(l3);
            if constexpr (layer == 1) {
                if (mlp) mbar_wait(barw + 40, IC<PL.par[16]>::value);
                load_u(v, mlp ? ksw + slot_o(5) : SM_RING + warp * WOU, 0); load_u(u, mlp ? ksw + slot_o(5) + WOU : SM_RING + (8 + warp) * WOU, 0);
            }
            if (layer == 0 && warp >= 3 && mlp) {
#pragma unroll 1
                for (int it = 0; it < 4096; it++) { tick(v[0]); if ((int)(gtime() - w1due) >= 0) break; }
                if (elect()) {
                    mbar_expect(SM_CBAR + 56 + warp * 8, 4096);
                    asm volatile("cp.async.bulk.tensor.2d.shared::cluster.global.mbarrier::complete_tx::bytes.L2::cache_hint [%0], [%1, {%2, %3}], [%4], %5;"
                                 :: "r"(SM_RING + (warp - 3) * 4096), "l"(tmk + TM_W1), "r"(hu), "r"(warp * 128 - 384), "r"(SM_CBAR + 56 + warp * 8), "l"((u64)POL_FIRST << 32) : "memory");
                }
                __syncwarp();
            }
#pragma unroll 1
            for (int it = 0; it < SPIN; it++) {
                if (it) { w1 = ld_rlx(l1); w2 = ld_rlx(l2); w3 = ld_rlx(l3); }
                if (!__any_sync(~0u, ((lo32(w1) ^ tag) | (lo32(w2) ^ tag) | (lo32(w3) ^ tag)) & 255)) break;
            }
            const uint32_t od = pack_bf((own.x + __uint_as_float(lo32(w1) ^ tag)) + (__uint_as_float(lo32(w2) ^ tag) + __uint_as_float(lo32(w3) ^ tag)),
                                        (own.y + __int_as_float(hi32(w1))) + (__int_as_float(hi32(w2)) + __int_as_float(hi32(w3))));
            const uint32_t o0 = __shfl_sync(~0u, od, tid & 3), o1 = __shfl_sync(~0u, od, (tid & 3) + 4), o2 = __shfl_sync(~0u, od, (tid & 3) + 8);
            auto narrow = [&](const uint4 (&a)[5], uint32_t o) { mma(y[2], a[4], pick(o, selC), pick(o, selD)); };
            auto wide = [&](const uint4 (&a)[5], uint32_t o) {
                const uint32_t b0 = pick(o, selA), b1 = pick(o, selB), b2 = pick(o, selA | 0x2222), b3 = pick(o, selB | 0x2222);
                mma(y[0], a[0], b0, b1); mma(y[1], a[1], b0, b1); mma(y[0], a[2], b2, b3); mma(y[1], a[3], b2, b3);
            };
            narrow(v, o0); wide(v, o0);
            if constexpr (layer == 0) {
                mbar_wait(SM_CBAR + 48 + (warp >> 2) * 8, 0);
                load_u(u, warp * WOU, SM_RING + 8 * WOU);
                __syncwarp();
                if (mlp && elect() && atoms_inc(SM_CNT + 44, 7) == 7) { mbar_expect(SM_CBAR + 120, 20480); tma3(SM_W2, tmk + TM_W2, 0, hu, SM_CBAR + 120, POL_FIRST); }
                __syncwarp();
                narrow(u, o1); wide(u, o1);
                red_addr(L);
                mbar_wait(SM_CBAR + 64 + (warp >> 2) * 8, 0);
                load_u(z, warp * WOU, SM_RING + 16 * WOU);
                narrow(z, o2);
            } else { narrow(u, o1); narrow(z, o2); wide(u, o1); }
            wide(z, o2);
#pragma unroll
            for (int k = 0; k < 4; k++) y[2][k] += shx(y[2][k], 18);
            sts128f_if(!(tid & 18), ya, YP + 512, y[2][0], y[2][1], y[2][2], y[2][3]);
            sts128f_if(!(tid & 2), ya, YP, y[0][0], y[0][1], y[0][2], y[0][3]);
            sts128f_if(!(tid & 2), ya, YP + 256, y[1][0], y[1][1], y[1][2], y[1][3]);
            __syncthreads();
            if (warp < 5) {
                const float s = sum8(tid * 4, YP, 768);
                asm volatile("red.relaxed.gpu.global.add.u64 [%0], %1;" :: "l"(ra), "l"(fx_pack(s)) : "memory");
            }
            cq = clk();
            if (layer == 0) refresh_late();
        }
        if (layer == 1 && !mlp) return;
        if (warp < 5) {
            if (layer == 0) { mlp_prep(L); if (mlp) mbar_wait(SM_CBAR + 80 + warp * 8, 0); }
            load_w1();
            if (layer == 1) { load_w2(); b2v = lds64(ksw + (c4 & 31) * 8, SM_KS + 11264); }
            {
                u64 w[4];
                while (clk() - cq < (layer || mlp ? AR1D : AR1DN));
                fx_poll(ap, w);
                xp = make_uint2(pack_bf(bf_lo(xp.x) + fx_val(w[0]) * inv1, bf_hi(xp.x) + fx_val(w[1]) * inv1),
                                pack_bf(bf_lo(xp.y) + fx_val(w[2]) * inv1, bf_hi(xp.y) + fx_val(w[3]) * inv1));
            }
            {
                const bool ev = layer || !(tid & 4), od = layer || (tid & 4);
                const uint32_t e0 = ev ? xp.x : ONES, e1 = ev ? xp.y : ONES, o0 = od ? xp.x : ONES, o1 = od ? xp.y : ONES;
                float d[8][4];
#pragma unroll
                for (int j = 0; j < 8; j++) { zero4(d[j]); mma(d[j], wf[j], (j & 1) ? o0 : e0, (j & 1) ? o1 : e1); }
                float lo = d[0][0] + d[1][1], hi = d[0][2] + d[1][3];
#pragma unroll
                for (int m = 1; m < 4; m++)
                    asm("{\n.reg .pred p;\nsetp.eq.u32 p, %6, %7;\n@p add.f32 %0, %2, %3;\n@p add.f32 %1, %4, %5;\n}" : "+f"(lo), "+f"(hi)
                        : "f"(d[2 * m][0]), "f"(d[2 * m + 1][1]), "f"(d[2 * m][2]), "f"(d[2 * m + 1][3]), "r"(tid & 3), "r"(m));
                float dd = ((tid & 1) ? hi : lo) + shx((tid & 1) ? lo : hi, 1);
                dd += shx(dd, 2);
                ln_part();
                if (layer == 0) {
                    const float cl = ((d[0][1] + d[1][0]) + (d[2][1] + d[3][0])) + ((d[4][1] + d[5][0]) + (d[6][1] + d[7][0]));
                    const float ch = ((d[0][3] + d[1][2]) + (d[2][3] + d[3][2])) + ((d[4][3] + d[5][2]) + (d[6][3] + d[7][2]));
                    sts32_if(!(tid & 2), hpa, SM_C1, __float_as_uint((tid & 1) ? ch : cl));
                }
                sts32_if(!(tid & 2), hpa, SM_QU, __float_as_uint(dd));
            }
            const float b1v = ldsf(ha, SM_B1);
            float csum = layer ? ldsf(ha, SM_B1 + 64) : 0.f;
            bar_sync(1, layer ? 160 : 192);
            float mean, rstd, msq;
            ln_final(mean, rstd, msq);
            float hp[5];
#pragma unroll
            for (int w = 0; w < 5; w++) hp[w] = ldsf(ha, SM_QU + w * 64);
            if constexpr (layer == 0) {
                float c[5];
#pragma unroll
                for (int w = 0; w < 5; w++) c[w] = ldsf(ha, SM_C1 + w * 64);
                csum = ((c[0] + c[1]) + (c[2] + c[3])) + c[4];
                load_w2();
            }
            float hv = ((((hp[0] + hp[1]) + (hp[2] + hp[3])) + hp[4]) - mean * csum) * rstd + b1v;
            hv = hv * rcp(1.f + ex2(hv * (-2.302208198f - 0.1029432397f * hv * hv)));
            const uint32_t hd = pack_bf(hv, hv);
            float ym[4][4];
            const uint32_t hh[4] = {__shfl_sync(~0u, hd, tid & 3), __shfl_sync(~0u, hd, (tid & 3) + 4), __shfl_sync(~0u, hd, (tid & 3) + 8), __shfl_sync(~0u, hd, (tid & 3) + 12)};
#pragma unroll
            for (int i = 0; i < 4; i++) {
                const uint32_t b0 = pick(hh[i], selA), b1 = pick(hh[i], selB);
                if (i < 2) { zero4(ym[2 * i]); zero4(ym[2 * i + 1]); }
                mma(ym[2 * (i & 1)], w2r[2 * i], b0, b1); mma(ym[2 * (i & 1) + 1], w2r[2 * i + 1], b0, b1);
            }
            const float sc2 = __uint_as_float((uint32_t)(127 + 16 - max(((int)(__float_as_uint(msq) >> 23) - 127) >> 1, -100)) << 23);
            float y[4];
            uint32_t yb[4];
#pragma unroll
            for (int k = 0; k < 4; k++) { y[k] = ((tid & 2) ? ym[1][k] : ym[0][k]) + ((tid & 2) ? ym[3][k] : ym[2][k]); yb[k] = __float_as_uint(fmaf(y[k], sc2, FX2_MAGIC)); }
            const uint32_t big = !mlp ? 0 : (((yb[0] ^ 0x4b400000u) | (yb[1] ^ 0x4b400000u)) | ((yb[2] ^ 0x4b400000u) | (yb[3] ^ 0x4b400000u))) & FX2_MASK;
            u64 w[2], old[2];
#pragma unroll
            for (int k = 0; k < 2; k++) {
                w[k] = mk64(big ? 0 : yb[2 * k] * 512 + 0x80000001u, big ? 0 : yb[2 * k + 1] * 16 + 0x4c000000u);
                if (layer == 0) { if (mlp) asm volatile("red.relaxed.gpu.global.add.u64 [%0], %1;" :: "l"(ap2 + k * 40 * ACC_PITCH), "l"(w[k]) : "memory"); }
                else asm volatile("atom.relaxed.gpu.global.add.u64 %0, [%1], %2;" : "=l"(old[k]) : "l"(ap2 + k * 40 * ACC_PITCH), "l"(w[k]) : "memory");
            }
            const uint32_t c0 = clk();
            if (__any_sync(~0u, big)) {
                if (big) {
#pragma unroll
                    for (int k = 0; k < 4; k++)
                        asm volatile("red.relaxed.gpu.global.add.u64 [%0], %1;" :: "l"(ap2 + (k >> 1) * 40 * ACC_PITCH + 64 + (k & 1) * 32), "l"(fx_pack(y[k] * fx_scale(msq))) : "memory");
                    __threadfence();
#pragma unroll
                    for (int k = 0; k < 2; k++) {
                        asm volatile("red.relaxed.gpu.global.and.b64 [%0], %1;" :: "l"(ap2 + k * 40 * ACC_PITCH), "l"(~256ull) : "memory");
                        w[k] = FX2_NONE;
                        asm volatile("atom.relaxed.gpu.global.add.u64 %0, [%1], %2;" : "=l"(old[k]) : "l"(ap2 + k * 40 * ACC_PITCH), "l"(FX2_NONE) : "memory");
                    }
                }
                __syncwarp();
            }
            if (layer == 0) { refresh(); load_b2(); park(); stsf(ha, SM_B1 + 64, csum); }
            stsf(0, SM_FXS, msq);
            const float inv32 = fx_inv(sc2) * 0.03125f;
            float xb[4] = {bf_lo(xp.x) + bf_lo(b2v.x) - 24.f * inv32, bf_hi(xp.x) + bf_hi(b2v.x), bf_lo(xp.y) + bf_lo(b2v.y) - 24.f * inv32, bf_hi(xp.y) + bf_hi(b2v.y)};
            auto add_wide = [&]() {
                __threadfence();
#pragma unroll
                for (int k = 0; k < 4; k++) xb[k] += fx_val(ld_rlx(ap2 + (k >> 1) * 40 * ACC_PITCH + 64 + (k & 1) * 32)) * fx_inv(fx_scale(ldsf(0, SM_FXS)));
            };
            auto sum2 = [&](int k) {
                return pack_bf(xb[2 * k] + (float)(int)__funnelshift_r(lo32(w[k]), hi32(w[k]), 4) * inv32, xb[2 * k + 1] + (float)hi32(w[k]) * (inv32 + inv32));
            };
            if constexpr (layer == 1) {
#pragma unroll
                for (int k = 0; k < 4; k++) xb[k] = pinf(xb[k]);
                mbar_wait(SM_BAR + 3 * 64 + 56, 0);
#pragma unroll
                for (int k = 0; k < 2; k++) {
                    w[k] += old[k];
                    asm volatile("{\n.reg .pred p;\nsetp.eq.u32 p, %2, 0;\n@p st.global.u32 [%0], %1;\n}" :: "l"(op + k), "r"(sum2(k)), "r"(~lo32(w[k]) & 0x180) : "memory");
                }
                if (((lo32(w[0]) & ~(lo32(w[0]) >> 1)) | (lo32(w[1]) & ~(lo32(w[1]) >> 1))) & 128) {
                    add_wide();
                    if (w[0] & 128) op[0] = sum2(0);
                    if (w[1] & 128) op[1] = sum2(1);
                }
            } else {
                load_wq();
                __syncwarp();
                if (elect()) mbar_arrive(SM_BAR + 56);
#pragma unroll
                for (int k = 0; k < 4; k++) xb[k] = pinf(xb[k]);
                while (clk() - c0 < AR2D);
                uint32_t want = 0x180;
#pragma unroll 1
                for (int it = 0; it < SPIN; it++) {
                    if (it && !__any_sync(~0u, ~(lo32(w[0]) & lo32(w[1])) & 128)) { add_wide(); want = 128; }
                    w[0] = ld_rlx(ap2); w[1] = ld_rlx(ap2 + 40 * ACC_PITCH);
                    if (!__any_sync(~0u, ~(lo32(w[0]) & lo32(w[1])) & want)) break;
                }
                xp = make_uint2(sum2(0), sum2(1));
            }
        } else if constexpr (layer == 1) {
            if (warp == 7) {
                const uint32_t c1 = clk();
                while (clk() - c1 < KAD) tick(z[0]);
                if (zero) sts32(0, SM_JUNK, z[0].x);
            }
        } else {
            const uint32_t c0 = clk();
            load_wq();
            __syncwarp();
            if (elect()) mbar_arrive(SM_BAR + 56);
            if (warp == 5) {
                if (mlp) mbar_wait(SM_CBAR + 120, 0);
                asm volatile("bar.arrive 1, 192;" ::: "memory");
            }
            while (clk() - c0 < S6D + (warp - 5) * S6G) tick(wqh[0]);
            issue2(IC<0>{}, wq0[0].x | wq0[1].x | wq0[2].x | wq0[3].x | wq0[4].x | wq0[5].x);
            if (warp == 5) {
#pragma unroll 1
                for (int k = 0; k < NPFC; k++) {
                    while (clk() - c0 < PFD + k * PFG);
                    if (elect()) tma3_pf(tmk + TM_V8, 0, rowc + (k >> 3) * 256 + (k & 7) * 8, POL_NORMAL);
                }
            }
            if (elect()) mbar_expect(warp == 5 ? SM_BAR + 4 * 64 : SM_CBAR - 32 + warp * 8, warp == 5 ? SUB : HT);
#pragma unroll 1
            for (int it = 0; it < SPIN; it++) { if (mbar_test(SM_BAR + 56, 0)) break; tick(wqh[0]); }
            const uint32_t c1 = clk();
            park();
            while (clk() - c1 < I0D) tick(wqh[0]);
            issue_help();
        }
    };

    load_wq();
    q_stage(IC<0>{});
    {
        int it = (warp >> 2) + 5, slot = (warp >> 2) + 1, bar = warp >> 2, par = 0;
        auto refill = [&](bool kv) {
            uint32_t old;
            asm volatile("{\n.reg .pred p;\nelect.sync _|p, 0xffffffff;\nmov.u32 %0, 0;\n@p atom.relaxed.cta.shared.inc.u32 %0, [%1], 3;\n}" : "=r"(old) : "r"(SM_CNT + slot * 8) : "memory");
            if (__any_sync(~0u, old == 3)) {
                if (!kv && it >= 64) {
#pragma unroll 1
                    for (int k = 0; k < SPIN; k++) {
                        int f; asm volatile("ld.volatile.shared.u32 %0, [%1];" : "=r"(f) : "r"(SM_CNT + 4) : "memory");
                        if (f >= slot) break;
                    }
                    sts32(0, SM_CNT + 4, slot + 1);
                    if (elect()) issue_wo(slot);
                } else {
                    wait_due(it, 0);
                    if (elect()) issue_kv(it, slot, bar < 5 ? bar + 5 : bar - 5);
                }
                __syncwarp();
            }
        };
        auto advance = [&]() { it += 2; slot += 2; if (slot >= 5) slot -= 5; bar += 2; if (bar >= 10) { bar -= 10; par ^= 1; } };
        {
            uint32_t offK[3], qf[12];
#pragma unroll
            for (int j = 0; j < 3; j++) offK[j] = pin(((tid >> 5) & 3) * SUB + 3 * g * 128 + (((2 * t) ^ ((3 * g + j) & 7)) << 4));
#pragma unroll
            for (int i = 0; i < 12; i++) qf[i] = kc[i] = 0;
            const uint32_t ksl = pin(ksw + lane * 16), sca = pin(prow + g * 64);
            int n0 = 0;
#pragma unroll 1
            for (int e = 0; e < 16; e++) {
                mbar_wait(SM_CBAR + bar * 8, par);
                uint4 v[6];
#pragma unroll
                for (int i = 0; i < 6; i++) v[i] = lds128(ad(offK[i >> 1] ^ ((i & 1) * 16), slot * HT), SM_RING + (i >> 1) * 128);
                refill(true);
                advance();
                if ((0xc20 | ((2 << NP) - 1)) >> e & 1) {
                    refresh();
                    static_for<0, NP>([&](auto E) {
                        if (e == E.value) {
#pragma unroll
                            for (int i = 0; i < 6; i++) {
                                uint32_t* k = kc + 90 + 24 * E.value + 4 * i;
                                asm volatile("mov.b32 %0, %4; mov.b32 %1, %5; mov.b32 %2, %6; mov.b32 %3, %7;" : "=r"(k[0]), "=r"(k[1]), "=r"(k[2]), "=r"(k[3]) : "r"(v[i].x), "r"(v[i].y), "r"(v[i].z), "r"(v[i].w));
                            }
                            if (E.value == NP - 2 && warp < 6) {
#pragma unroll
                                for (int i = 0; i < 2; i++)
                                    asm volatile("cp.async.cg.shared.global [%0], [%1], 16;" :: "r"(ksl + SM_KS + 10240 + i * 512),
                                                 "l"(&g_ll[(cta & ~3) + 2 * i + (lane >> 4)][warp * 32 + (lane & 15) * 2]) : "memory");
                            }
                            if (E.value == NP - 1 && warp < 6) {
                                asm volatile("cp.async.wait_all;" ::: "memory");
                                __syncwarp();
                                const uint32_t a = ksw + lane * 8;
                                u64 w[4] = {lds_u64(a, SM_KS + 10240), lds_u64(a, SM_KS + 10496), lds_u64(a, SM_KS + 10752), lds_u64(a, SM_KS + 11008)};
                                ll_gather4(&g_ll[cta & ~3][tid], 2 * ep4 + 1, w);
                                const float cs = (lof(w[0] & ~255ull) + lof(w[1] & ~255ull)) + (lof(w[2] & ~255ull) + lof(w[3] & ~255ull));
                                float q = (hif(w[0]) + hif(w[1])) + (hif(w[2]) + hif(w[3]));
                                stsf(tid * 4, SM_CS, cs);
                                float mean, rstd, msq;
                                ln_final(mean, rstd, msq);
                                stsf(0, SM_FXS, fx_scale(msq));
                                q = (q - mean * cs) * rstd;
                                sts16(q_addr(), SM_QU, pack_bf(q, q));
                                __syncwarp();
                                if (elect()) mbar_arrive(SM_QBAR);
#pragma unroll
                                for (int i = 0; i < 12; i++) asm volatile("mov.b32 %0, 0;" : "=r"(kc[i]));
                            }
                        }
                    });
                    if (e == NP) {
                        mbar_wait(SM_QBAR, 0);
#pragma unroll
                        for (int k = 0; k < 3; k++) lds128(qf + 4 * k, (lane & 7) * 48, SM_QU + k * 16);
                        static_for<0, NP>([&](auto E) {
                            uint4 r[6];
#pragma unroll
                            for (int i = 0; i < 6; i++) { const uint32_t* k = kc + 90 + 24 * E.value + 4 * i; r[i] = make_uint4(k[0], k[1], k[2], k[3]); }
                            stsf(sca, SM_PART + 256 + (E.value + 6) * 4, score6(r, qf));
                        });
#pragma unroll
                        for (int i = 0; i < 24; i++) asm volatile("mov.b32 %0, 0;" : "=r"(kc[i]));
                    } else if (e == 5) {
#pragma unroll
                        for (int k = 0; k < 22; k++) lds128(kc + 4 * k, ksl, SM_KS + k * 512);
                        lds64(kc + 88, ksl, SM_KS + 22 * 512);
                        n0 = 0;
                    } else if (e == 10) {
#pragma unroll
                        for (int k = 0; k < 22; k++)
                            asm volatile("ld.shared.v4.b32 {%0,%1,%2,%3}, [%4];" : "=r"(kc[90 + 4 * k]), "=r"(kc[91 + 4 * k]), "=r"(kc[92 + 4 * k]), "=r"(kc[93 + 4 * k]) : "r"(ad(ksl, SM_KS + k * 512)) : "memory");
                        asm volatile("ld.shared.v2.b32 {%0,%1}, [%2];" : "=r"(kc[178]), "=r"(kc[179]) : "r"(ad(ksl, SM_KS + 22 * 512)) : "memory");
                        n0 = 0;
                    } else if (e == 11) {
                        lds64(kc + 180, ksl, SM_KS + 520); lds128(kc + 182, ksl, SM_KS + 1024); lds128(kc + 186, ksl, SM_KS + 1536); lds64(kc + 190, ksl, SM_KS + 2048);
                        n0 = 3;
                    }
                }
                const int n = (e + 6) & 15;
                stsf(ad(sca, n * 4), SM_PART + 256, score6(v, qf));
                uint32_t m = bf2_amax(bf2_amax(v[0].x, v[0].y), bf2_amax(v[0].z, v[0].w)), mn = bf2_amin(bf2_amin(v[0].x, v[0].y), bf2_amin(v[0].z, v[0].w));
#pragma unroll
                for (int i = 1; i < 6; i++) m = bf2_amax(m, bf2_amax(bf2_amax(v[i].x, v[i].y), bf2_amax(v[i].z, v[i].w)));
                m = max(m & 0x7fff, (m >> 16) & 0x7fff);
                m = max(m, __shfl_xor_sync(~0u, m, 1)); m = max(m, __shfl_xor_sync(~0u, m, 2));
#pragma unroll
                for (int i = 1; i < 6; i++) mn = bf2_amin(mn, bf2_amin(bf2_amin(v[i].x, v[i].y), bf2_amin(v[i].z, v[i].w)));
                mn = min(mn & 0x7fff, (mn >> 16) & 0x7fff);
                const int sh = min(max((int)(m >> 7) - 15, 0), 126);
                asm volatile("st.shared.u8 [%0], %1;" :: "r"(ad(ad((tid >> 2) * 16, n), SM_SH)), "r"(sh) : "memory");
                const uint32_t dn = (127 - sh) * 0x00800080u;
                if (__any_sync(~0u, (int)(mn >> 7) <= sh || m >= (142 << 7))) {
                    if (m >= (142 << 7)) sts32(0, SM_BIG, 1);
                    const uint32_t up = (127 + 256 + sh) * 0x00800080u;
#pragma unroll
                    for (int i = 0; i < 6; i++) {
                        const uint32_t r0 = bf2_fma(bf2_mul(v[i].x, dn), up, v[i].x), r1 = bf2_fma(bf2_mul(v[i].y, dn), up, v[i].y);
                        const uint32_t r2 = bf2_fma(bf2_mul(v[i].z, dn), up, v[i].z), r3 = bf2_fma(bf2_mul(v[i].w, dn), up, v[i].w);
                        asm volatile("{\n.reg .pred p;\n.reg .u32 x, a;\nsetp.ne.u32 p, %0, 0;\nmov.u32 x, %7;\n@p atom.relaxed.cta.shared.inc.u32 x, [%6], 0x7fffffff;\n"
                                     "setp.lt.u32 p, x, %7;\nmad.lo.u32 a, x, 16, %8;\n@p st.shared.v4.u32 [a], {%1,%2,%3,%4};\n"
                                     "mad.lo.u32 a, x, 4, %9;\n@p st.shared.u32 [a], %5;\n}"
                                     :: "r"(r0 | r1 | r2 | r3), "r"(r0), "r"(r1), "r"(r2), "r"(r3), "r"(tid << 16 | n << 8 | i * 8), "r"(SM_XN), "n"(XCAP), "n"(SM_XR), "n"(SM_XM) : "memory");
                    }
                }
                const uint32_t ae = (n0 >> 1) * 512 + (n0 & 1) * 8, ao = ((n0 + 1) >> 1) * 512 + (~n0 & 1) * 8;
                uint32_t o[18];
#pragma unroll
                for (int i = 0; i < 6; i++) {
                    const uint32_t y0 = bf2_mulv(v[i].x, dn), y1 = bf2_mulv(v[i].y, dn), y2 = bf2_mulv(v[i].z, dn), y3 = bf2_mulv(v[i].w, dn);
                    o[3 * i] = __byte_perm(y0, y1, 0x6420); o[3 * i + 1] = __byte_perm(y2, y3, 0x6420);
                    const uint32_t hb = __byte_perm(y2, y3, 0x7531);
                    o[3 * i + 2] = __byte_perm(y0, y1, 0x7531) | __funnelshift_l(hb, hb, 4);
                    if (i & 1) {
#pragma unroll
                        for (int k = 3 * (i >> 1); k < 3 * (i >> 1) + 3; k++) sts64(ad(ksl, (k & 1) ? ao : ae), SM_KS + (k >> 1) * 512, o[2 * k], o[2 * k + 1]);
                    }
                }
                n0 += 9;
            }
            fence_async();
        }
        refresh();
        {
            const uint4 sc = lds128(prow + lane * 16, SM_PART + 256);
            const float S[4] = {__uint_as_float(sc.x), __uint_as_float(sc.y), __uint_as_float(sc.z), __uint_as_float(sc.w)};
            softmax(IC<0>{}, S);
        }
        fw = 0.f;
#pragma unroll 1
        for (int e = 0; e < 16; e++) {
            if ((1 << (PUBAT - 3) | 1 << PUBAT | 1 << ZCHK) >> e & 1) {
                if (e == PUBAT - 3) head_look();
                else if (e == PUBAT) {
                    head_weight(IC<0>{});
                    if (tid < 196) st_rlx(&g_ll[cta][tid + (tid >> 6 == 3) * 8], 0ull);
                } else if (warp == 7) {
                    if ((bx & 15) == 0 && elect()) bulk_pf(P.b2, D_MODEL * 2, POL_NORMAL);
#pragma unroll 1
                    for (int k = 0; k < SPIN; k++) {
                        uint32_t v; asm volatile("ld.acquire.gpu.global.u32 %0, [%1];" : "=r"(v) : "l"(&g_zflag) : "memory");
                        if (__all_sync(~0u, v * 4 == ep4 + 4)) break;
                    }
                }
                __syncwarp();
            }
            const uint32_t pp = lds32(ad(t * 4, prow + ((e + 6) & 15) * 16), SM_PART + 256);
            mbar_wait(SM_CBAR + bar * 8, par);
            uint4 v[6];
            load_v(v, (warp & 3) * SUB + slot * HT, SM_RING);
            if (e < 15) refill(false);
            advance();
            pv(v, pp);
        }
    }
    tail_prep1(IC<0>{});
    __syncwarp();
    tail(IC<0>{});

    q_stage(IC<1>{});
    {
        const u64* qp = &g_ll[cta & ~3][tid];
        u64 w[4] = {0, 0, 0, 0};
        if (warp < 6) { w[0] = ld_rlx(qp); w[1] = ld_rlx(qp + 256); w[2] = ld_rlx(qp + 512); w[3] = ld_rlx(qp + 768); }
        mbar_wait(SM_BAR + 3 * 64 + 56, 0);
        const uint32_t ksl = ksw + lane * 16, qa = pin(q_addr()), qb0 = pin(lane < 8 ? lane * 48 : SM_ZQ - SM_VEC);
        uint32_t ks[96], qf[12];
        float mean, rstd, msq;
        ln_final(mean, rstd, msq);
        const float qc = pinf(-mean * rstd * ldsf(tid * 4, SM_CS));
#pragma unroll
        for (int k = 0; k < 6; k++) lds128(ks + 4 * k, ksl, SM_KS + k * 512);
        stsf(0, SM_FXS, fx_scale(msq));
        if (warp < 6) {
            ll_gather4(qp, 2 * ep4 + 5, w);
            const float q = ((hif(w[0]) + hif(w[1])) + (hif(w[2]) + hif(w[3]))) * rstd + qc;
            const uint32_t qq = bf2_mul(pack_bf(q, q), 0x3f807180u);
            sts16(qa, SM_VEC, qq); sts16(qa, SM_QU, qq >> 16);
            sts32_if(!(fabsf(q) < 1048576.f), 0, SM_BIG, 1);
            __syncwarp();
            if (elect()) mbar_arrive(SM_QBAR);
        } else {
            uint4 c = make_uint4(ks[0], ks[1], ks[2], ks[3]);
            if (cta == 0 && tid == 255) g_epoch = (ep4 >> 2) + 1;
#pragma unroll 1
            for (int it = 0; it < SPIN; it++) { if (mbar_test(SM_QBAR, 1)) break; tick(c); }
            ks[0] = c.x; ks[1] = c.y; ks[2] = c.z; ks[3] = c.w;
        }
        issue2(IC<3>{}, ks[0] | ks[4] | ks[8] | ks[12] | ks[16] | ks[20]);
        mbar_wait(SM_QBAR, 1);
        auto load_q = [&](int u, int k) { lds128(qf + 4 * k, u == 0 ? qb0 : (tid & 24) == 8 * u ? (tid & 7) * 48 : SM_ZQ - SM_VEC, SM_VEC + k * 16); };
        load_q(0, 1); load_q(0, 2); load_q(0, 0);
        float D[4][4];
        uint4 vb[NPK + 2][6], v2[6];
        uint32_t xn = 0;
        const uint32_t t1 = __shfl_sync(~0u, lds32(0, SM_T0), 0);
        auto step = [&](auto Q) {
            constexpr int st = Q.value, p = cord(st), s = PL.slot[p], n = PL.ld[st];
            if constexpr (n > 0) {
                if constexpr (st >= NPK) {
                    const uint32_t due = t1 + (P2A + n * P2B);
#pragma unroll 1
                    for (int it = 0; it < 4096; it++) if ((int)(gtime() - due) >= 0) break;
                }
                const uint4 (&u)[6] = vb[st - 1 < NPK ? st - 1 : NPK + ((st - 1) & 1)];
                issue2(IC<n>{}, st > PVNOW ? 0 : u[0].x | u[1].x | u[2].x | u[3].x | u[4].x | u[5].x);
            }
            if constexpr (st == 14) {
#pragma unroll 1
                for (int it = 0; it < 4096; it++) if ((int)(gtime() - t1) >= P2W) break;
                issue2(IC<16>{}, 0);
            }
            if (p == 1) mbar_wait(SM_CBAR + (warp >> 2) * 8, 1);
            else if (p == 0) mbar_wait(warp < 4 ? SM_CBAR + 24 : barw, warp < 4);
            else mbar_wait(barw + s * 8, IC<PL.par[p]>::value);
            load_v(vb[st < NPK ? st : NPK + (st & 1)], slot_u(s), slot_o(s));
        };
        static_for<0, 96>([&](auto I) {
            constexpr int F = I.value, n = F / 6, i = n ? F % 6 : (F + 2) % 6;
            const uint32_t* c = n == 0 ? (i < 2 ? ks + 3 * i : kc + 174 + 3 * i) : n < 6 ? ks + 18 * n - 12 + 3 * i : kc + 18 * (n - 6) + 3 * i;
            const uint32_t hx = c[2] & 0x78787878u, ha = hx * (zero - 1) + c[2], hb = __funnelshift_r(hx, hx, 4);
            if (F < 24 && F % 6 == 0) zero4(D[n]);
            mma(D[n & 3], __byte_perm(c[0], ha, 0x5140), __byte_perm(c[0], ha, 0x7362), __byte_perm(c[1], hb, 0x5140), __byte_perm(c[1], hb, 0x7362), qf[2 * i], qf[2 * i + 1]);
            if constexpr ((n & 3) == 3 && n < 15 && (i & 1)) load_q((n + 1) >> 2, i >> 1);
            static_for<6, 24>([&](auto U) {
                if constexpr (((U.value - 5) * 4 + 2) / 3 - 1 == F) {
                    lds128(ks + 4 * U.value, ksl, SM_KS + U.value * 512);
                    if constexpr (U.value % 6 == 5) { const uint32_t* k = ks + 4 * U.value - 17; issue2(IC<3 + U.value / 6>{}, k[0] | k[4] | k[8] | k[12] | k[16] | k[20]); }
                }
            });
            if constexpr (F == 94) {
                if (warp < 4) { mbar_wait(SM_CBAR + 16, 1); load_v(v2, wqw, slot_o(2)); }
                else {
                    const char* p = reinterpret_cast<const char*>(P.v) + (size_t)(roww + vunit(2) * 256) * (DH * 2) + t * 768 + g * 16;
#pragma unroll
                    for (int k = 0; k < 6; k++)
                        asm volatile("ld.global.nc.v4.u32 {%0,%1,%2,%3}, [%4];" : "=r"(v2[k].x), "=r"(v2[k].y), "=r"(v2[k].z), "=r"(v2[k].w) : "l"(p + k * 128));
                }
                const uint2 x = lds64(0, SM_XN);
                xn = x.y ? XCAP + 1 : x.x;
                sts128(prow + lane * 16, SM_PART + 256, 0, 0, 0, 0);
                __syncwarp();
#pragma unroll 1
                for (uint32_t idx = lane; idx < (xn > XCAP ? 0 : xn); idx += 32) {
                    const uint32_t m = lds32(idx * 4, SM_XM);
                    if ((m >> 21) == warp) {
                        const uint4 r = lds128(idx * 16, SM_XR);
                        const uint32_t qo = ((m >> 16) & 3) * 48 + (m & 255);
                        const uint2 a = lds64(qo, SM_QU), b = lds64(qo, SM_QU + 192);
                        const float s = ((bf_lo(r.x) * bf_lo(a.x) + bf_hi(r.x) * bf_hi(a.x)) + (bf_lo(r.y) * bf_lo(b.x) + bf_hi(r.y) * bf_hi(b.x))) +
                                        ((bf_lo(r.z) * bf_lo(a.y) + bf_hi(r.z) * bf_hi(a.y)) + (bf_lo(r.w) * bf_lo(b.y) + bf_hi(r.w) * bf_hi(b.y)));
                        asm volatile("red.relaxed.cta.shared.add.f32 [%0], %1;" :: "r"(SM_PART + 256 + prow + ((m >> 18) & 7) * 64 + ((m >> 8) & 15) * 4), "f"(s) : "memory");
                    }
                }
                __syncwarp();
            }
            if constexpr (F == PK0 - 2) refresh();
            static_for<0, NPK>([&](auto Q) { if constexpr (F == (Q.value ? PK1 + (Q.value - 1) * PKD : PK0)) step(Q); });
        });
        float S[4];
        {
            const uint32_t shp = lds32(tid * 4, SM_SH);
            const uint4 cr = lds128(prow + lane * 16, SM_PART + 256);
            const uint32_t c[4] = {cr.x, cr.y, cr.z, cr.w};
#pragma unroll
            for (int j = 0; j < 4; j++) S[j] = (D[j][0] + D[j][3]) * __uint_as_float((((shp >> (8 * j)) & 255) + 27) << 23) + __uint_as_float(c[j]);
        }
        if (xn > XCAP) {
#pragma unroll
            for (int k = 0; k < 3; k++) lds128(qf + 4 * k, (lane & 7) * 48, SM_QU + k * 16);
#pragma unroll 1
            for (int e = 0; e < 16; e++) {
                uint4 v[6];
#pragma unroll
                for (int i = 0; i < 6; i++) v[i] = ldg128(P.k + (size_t)(roww + 256 * e + g) * DH + (i >> 1) * 64 + (2 * t + (i & 1)) * 8);
                const float s = score6(v, qf);
#pragma unroll
                for (int j = 0; j < 4; j++) if (4 * t + j == ((e + 6) & 15)) S[j] = s;
            }
        }
        softmax(IC<1>{}, S);
        auto p_of = [&](int st) { return lds32(ad(t * 4, prow), SM_PART + 256 + ((vunit(cord(st)) + 6) & 15) * 16); };
        auto pv_at = [&](auto Q) { constexpr int st = Q.value; pv(vb[st < NPK ? st : NPK + (st & 1)], p_of(st)); };
        static_for<NPK, 15>([&](auto Q) {
            constexpr int st = Q.value;
            if constexpr (st == HWAT) head_look();
            if constexpr (st == HWC) head_weight(IC<1>{});
            if constexpr (st == PREP1) { tail_prep1(IC<1>{}); tail_prep2(IC<1>{}); red_addr(IC<1>{}); load_u(z, warp * WOU, SM_RING + 16 * WOU); }
            if constexpr (st == PREP2) mlp_prep(IC<1>{});
            uint32_t pp;
            if constexpr (st >= PVNOW) pp = pin(p_of(st));
            step(Q);
            if constexpr (st - NPK < NPK) pv_at(IC<st - NPK>{});
            if constexpr (st > NPK && st <= PVNOW) pv_at(IC<st - 1>{});
            if constexpr (st == PV2) pv(v2, lds32(ad(t * 4, prow), SM_PART + 256 + ((vunit(2) + 6) & 15) * 16));
            if constexpr (st >= PVNOW) pv(vb[NPK + (st & 1)], pp);
        });
    }
    tail(IC<1>{});
}

typedef CUresult (*EncodeFn)(CUtensorMap*, CUtensorMapDataType, cuuint32_t, void*, const cuuint64_t*, const cuuint64_t*, const cuuint32_t*,
                             const cuuint32_t*, CUtensorMapInterleave, CUtensorMapSwizzle, CUtensorMapL2promotion, CUtensorMapFloatOOBfill);

}

extern "C" void kernel_launch(void* const* d_in, const int* in_sizes, int n_in, void* d_out, int out_size) {
    (void)in_sizes; (void)n_in; (void)out_size;
    static EncodeFn enc = nullptr;
    if (!enc) {
        void* fn = nullptr;
        cudaDriverEntryPointQueryResult qr;
        cudaGetDriverEntryPoint("cuTensorMapEncodeTiled", &fn, cudaEnableDefault, &qr);
        enc = (EncodeFn)fn;
        cudaFuncSetAttribute(fused_kernel, cudaFuncAttributeMaxDynamicSharedMemorySize, SM_TOTAL);
    }
    Params P;
    const cuuint32_t ones[3] = {1, 1, 1};
    for (int m = TM_K; m <= TM_V8; m++) {
        const cuuint64_t dim[3] = {64, 3, (cuuint64_t)NHEAD * SK}, str[2] = {128, DH * 2};
        const cuuint32_t box[3] = {m == TM_VP ? 8u : 64u, 3, m == TM_V8 ? 8u : 32u};
        enc(&P.tm[m], CU_TENSOR_MAP_DATA_TYPE_BFLOAT16, 3, d_in[m == TM_K ? 1 : 2], dim, str, box, ones, CU_TENSOR_MAP_INTERLEAVE_NONE,
            m == TM_VP ? CU_TENSOR_MAP_SWIZZLE_NONE : CU_TENSOR_MAP_SWIZZLE_128B, CU_TENSOR_MAP_L2_PROMOTION_NONE, CU_TENSOR_MAP_FLOAT_OOB_FILL_NONE);
    }
    {
        const cuuint64_t dim[3] = {64, NHEAD * 3, D_MODEL}, str[2] = {128, NHEAD * DH * 2};
        const cuuint32_t box[3] = {64, 3, 32};
        enc(&P.tm[TM_WQ], CU_TENSOR_MAP_DATA_TYPE_BFLOAT16, 3, d_in[3], dim, str, box, ones, CU_TENSOR_MAP_INTERLEAVE_NONE,
            CU_TENSOR_MAP_SWIZZLE_128B, CU_TENSOR_MAP_L2_PROMOTION_NONE, CU_TENSOR_MAP_FLOAT_OOB_FILL_NONE);
    }
    {
        const cuuint64_t dim[2] = {DFF, D_MODEL}, str[1] = {DFF * 2};
        const cuuint32_t box[2] = {16, 128};
        enc(&P.tm[TM_W1], CU_TENSOR_MAP_DATA_TYPE_BFLOAT16, 2, d_in[6], dim, str, box, ones, CU_TENSOR_MAP_INTERLEAVE_NONE,
            CU_TENSOR_MAP_SWIZZLE_32B, CU_TENSOR_MAP_L2_PROMOTION_L2_128B, CU_TENSOR_MAP_FLOAT_OOB_FILL_NONE);
    }
    {
        const cuuint64_t dim[3] = {32, 20, NHEAD * DH}, str[2] = {64, D_MODEL * 2};
        const cuuint32_t box[3] = {32, 5, 16};
        enc(&P.tm[TM_WO], CU_TENSOR_MAP_DATA_TYPE_BFLOAT16, 3, d_in[4], dim, str, box, ones, CU_TENSOR_MAP_INTERLEAVE_NONE,
            CU_TENSOR_MAP_SWIZZLE_64B, CU_TENSOR_MAP_L2_PROMOTION_L2_128B, CU_TENSOR_MAP_FLOAT_OOB_FILL_NONE);
    }
    {
        const cuuint64_t dim[4] = {32, 20, 24, NHEAD * 8}, str[3] = {64, D_MODEL * 2, 24 * D_MODEL * 2};
        const cuuint32_t box[4] = {32, 5, 8, 4}, ones4[4] = {1, 1, 1, 1};
        enc(&P.tm[TM_WO4], CU_TENSOR_MAP_DATA_TYPE_BFLOAT16, 4, d_in[4], dim, str, box, ones4, CU_TENSOR_MAP_INTERLEAVE_NONE,
            CU_TENSOR_MAP_SWIZZLE_64B, CU_TENSOR_MAP_L2_PROMOTION_L2_128B, CU_TENSOR_MAP_FLOAT_OOB_FILL_NONE);
        const cuuint32_t thin[4] = {8, 5, 8, 4};
        enc(&P.tm[TM_WOP], CU_TENSOR_MAP_DATA_TYPE_BFLOAT16, 4, d_in[4], dim, str, thin, ones4, CU_TENSOR_MAP_INTERLEAVE_NONE,
            CU_TENSOR_MAP_SWIZZLE_NONE, CU_TENSOR_MAP_L2_PROMOTION_NONE, CU_TENSOR_MAP_FLOAT_OOB_FILL_NONE);
    }
    {
        const cuuint64_t dim[3] = {64, 10, DFF}, str[2] = {128, D_MODEL * 2};
        const cuuint32_t box[3] = {64, 10, 16};
        enc(&P.tm[TM_W2], CU_TENSOR_MAP_DATA_TYPE_BFLOAT16, 3, d_in[8], dim, str, box, ones, CU_TENSOR_MAP_INTERLEAVE_NONE,
            CU_TENSOR_MAP_SWIZZLE_128B, CU_TENSOR_MAP_L2_PROMOTION_NONE, CU_TENSOR_MAP_FLOAT_OOB_FILL_NONE);
    }
    P.x = (const __nv_bfloat16*)d_in[0];
    P.k = (const __nv_bfloat16*)d_in[1];
    P.v = (const __nv_bfloat16*)d_in[2];
    P.b1 = (const __nv_bfloat16*)d_in[7];
    P.b2 = (const __nv_bfloat16*)d_in[9];
    P.out = (__nv_bfloat16*)d_out;
    fused_kernel<<<NCTA + 1, NTHR, SM_TOTAL, cudaStreamPerThread>>>(P);
}
```

```cpp
#include <cuda_runtime.h>
#include <cuda_bf16.h>
#include <cuda.h>
#include <stdint.h>

#define DI __device__ __forceinline__

namespace {

constexpr int D_MODEL = 640, NHEAD = 32, SK = 32768, DH = 192, WIN = 4096, DFF = 1536;
constexpr int NCTA = 128, NTHR = 256;
constexpr int SUB = 8 * DH * 2;
constexpr int HT = 4 * SUB;
constexpr int WOU = 8 * 320;
constexpr int XCAP = 48;
constexpr int SM_RING = 1024;
constexpr int SM_W2 = SM_RING + 8 * WOU;
constexpr int SM_WQ = SM_RING + 5 * HT;
constexpr int SM_KS = SM_WQ + 5 * HT;
constexpr int SM_PART = SM_KS + 8 * HT;
constexpr int SM_BAR = SM_PART + 6144;
constexpr int SM_VEC = SM_BAR + 512;
constexpr int SM_QU = SM_VEC + 384;
constexpr int SM_ZQ = SM_QU + 384;
constexpr int SM_CS = SM_ZQ + 64;
constexpr int SM_XR = SM_CS + 768;
constexpr int SM_XM = SM_XR + XCAP * 16;
constexpr int SM_SH = SM_XM + XCAP * 4;
constexpr int SM_C1 = SM_SH + 1024;
constexpr int SM_B1 = SM_C1 + 320;
constexpr int SM_STAT = SM_B1 + 128;
constexpr int SM_QBAR = SM_STAT + 40;
constexpr int SM_CBAR = SM_QBAR + 8;
constexpr int SM_CNT = SM_CBAR + 128;
constexpr int SM_XN = SM_CNT + 56;
constexpr int SM_BIG = SM_XN + 4;
constexpr int SM_EPOCH = SM_BIG + 4;
constexpr int SM_FXS = SM_EPOCH + 4;
constexpr int SM_T0 = SM_FXS + 4;
constexpr int SM_JUNK = SM_T0 + 4;
constexpr int SM_TOTAL = 232448;
static_assert(SM_JUNK + 4 <= SM_RING + SM_TOTAL, "smem");

constexpr int SPIN = 1 << 20;
enum { TM_WQ = 0, TM_K = 1, TM_V = 2, TM_VP = 3, TM_V8 = 4, TM_WO = 5, TM_W1 = 6, TM_WO4 = 7, TM_W2 = 8, TM_WOP = 9 };
constexpr uint32_t POL_NORMAL = 0x16F00000u, POL_FIRST = 0x12F00000u;

constexpr int PACE = 484, PACE0 = 1800, WOPACE = 403, W1D = 100, W1G = 150, HZD = 9500;
constexpr int NP = 3, PUBAT = 8, ZCHK = 14;
constexpr int ODELAY = 250, AR1D = 500, AR1DN = 1000, AR2D = 600, S6D = 900, S6G = 100, I0D = 300, NPFC = 4;
constexpr int PFD = 1200, PFG = 150, KAD = 900;
constexpr unsigned long long VORD = 0x56784932a1b0cdefull;
constexpr int ISS = 0xf9e, NPK = 4, PK0 = 34, PK1 = 52, PKD = 21, P2A = -700, P2B = 400, P2W = 5700;
constexpr int PREP1 = 8, PREP2 = 9, PV2 = 7, HWAT = 8, PVNOW = 12, HWC = 11;
constexpr uint32_t FX2_MASK = 0xfff00000u;

struct Plan { int slot[17], par[17], ld[15]; bool ok; };
__host__ __device__ constexpr int cord(int s) { return s < 2 ? s : s + 1; }
constexpr Plan make_plan() {
    Plan s{};
    int phase[7] = {}, freeat[7] = {}, it = 7;
    for (int p = 0; p < 7; p++) { s.slot[p] = p; phase[p] = p != 1; freeat[p] = -1; }
    s.ok = true;
    for (int st = 0; st < 15; st++) {
        if (ISS >> st & 1) {
            int best = -1;
            for (int c = 0; c < 7; c++) if (freeat[c] >= 0 && (c < 5 || it < 13) && (best < 0 || freeat[c] < freeat[best])) best = c;
            if (best < 0 || it > 15) { s.ok = false; return s; }
            s.slot[it] = best; freeat[best] = -1;
            s.par[it] = phase[best]++ & 1;
            s.ld[st] = it++;
        }
        if (cord(st) >= it || (st >= 12 && s.slot[cord(st)] >= 5)) s.ok = false;
        freeat[s.slot[cord(st)]] = st;
    }
    s.slot[16] = 5; s.par[16] = phase[5] & 1;
    return s;
}
constexpr Plan PL = make_plan();
static_assert(PL.ok && PK0 < 40, "bad pass-2 plan");
__host__ __device__ constexpr int vunit(int p) { return (int)(VORD >> (4 * p) & 15); }

template <int I> struct IC { static constexpr int value = I; };
template <int A, int B, class F> DI void static_for(F&& f) {
    if constexpr (A < B) { f(IC<A>{}); static_for<A + 1, B>(f); }
}

struct Params {
    CUtensorMap tm[10];
    const __nv_bfloat16 *x, *b1, *b2, *k, *v;
    __nv_bfloat16* out;
};

typedef unsigned long long u64;
constexpr int ACC_PITCH = 256;
constexpr int ACC_BYTES = 80 * ACC_PITCH;
__device__ __align__(1024) unsigned char g_acc[4 * ACC_BYTES];
__device__ __align__(8192) u64 g_ll[NCTA][256];
__device__ unsigned g_epoch;
__device__ __align__(128) unsigned g_zflag;

DI void mbar_wait(uint32_t bar, uint32_t parity) {
    asm volatile("{\n.reg .pred p, q;\n.reg .u32 n;\nmov.u32 n, 0;\n"
                 "LOOP:\nmbarrier.try_wait.parity.shared::cta.b64 p, [%0], %1;\n"
                 "add.u32 n, n, 1;\nsetp.lt.and.u32 q, n, 0x100000, !p;\n@q bra.uni LOOP;\n}"
                 :: "r"(bar), "r"(parity) : "memory");
}
DI bool mbar_test(uint32_t bar, uint32_t parity) {
    uint32_t done;
    asm volatile("{\n.reg .pred p;\nmbarrier.test_wait.parity.shared::cta.b64 p, [%1], %2;\nselp.u32 %0, 1, 0, p;\n}" : "=r"(done) : "r"(bar), "r"(parity) : "memory");
    return __any_sync(~0u, done);
}
DI bool elect() {
    uint32_t r;
    asm volatile("{\n.reg .pred p;\nelect.sync _|p, 0xffffffff;\nselp.u32 %0, 1, 0, p;\n}" : "=r"(r));
    return r != 0;
}
DI void mbar_init(uint32_t bar, uint32_t n) { asm volatile("mbarrier.init.shared::cta.b64 [%0], %1;" :: "r"(bar), "r"(n) : "memory"); }
DI void mbar_arrive(uint32_t bar) { asm volatile("mbarrier.arrive.shared::cta.b64 _, [%0];" :: "r"(bar) : "memory"); }
DI void mbar_expect(uint32_t bar, uint32_t bytes) {
    asm volatile("mbarrier.arrive.expect_tx.shared::cta.b64 _, [%0], %1;" :: "r"(bar), "r"(bytes) : "memory");
}
DI void fence_gpu() { asm volatile("fence.acq_rel.gpu;" ::: "memory"); }
DI void fence_async() { asm volatile("fence.proxy.async.shared::cta;" ::: "memory"); }
DI uint32_t ad(uint32_t a, uint32_t o) { uint32_t r; asm("add.u32 %0, %1, %2;" : "=r"(r) : "r"(a), "r"(o)); return r; }
DI uint4 lds128(uint32_t a, int o) {
    uint4 v; asm volatile("ld.shared.v4.u32 {%0,%1,%2,%3}, [%4];" : "=r"(v.x), "=r"(v.y), "=r"(v.z), "=r"(v.w) : "r"(ad(a, o)) : "memory"); return v;
}
DI void lds128(uint32_t* v, uint32_t a, int o) {
    asm volatile("ld.shared.v4.u32 {%0,%1,%2,%3}, [%4];" : "=r"(v[0]), "=r"(v[1]), "=r"(v[2]), "=r"(v[3]) : "r"(ad(a, o)) : "memory");
}
DI void lds64(uint32_t* v, uint32_t a, int o) { asm volatile("ld.shared.v2.u32 {%0,%1}, [%2];" : "=r"(v[0]), "=r"(v[1]) : "r"(ad(a, o)) : "memory"); }
DI uint4 ldsm_t(uint32_t a, int o) {
    uint4 v; asm volatile("ldmatrix.sync.aligned.m8n8.x4.trans.shared.b16 {%0,%1,%2,%3}, [%4];" : "=r"(v.x), "=r"(v.y), "=r"(v.z), "=r"(v.w) : "r"(ad(a, o)) : "memory"); return v;
}
DI uint2 lds64(uint32_t a, int o) { uint2 v; asm volatile("ld.shared.v2.u32 {%0,%1}, [%2];" : "=r"(v.x), "=r"(v.y) : "r"(ad(a, o)) : "memory"); return v; }
DI float2 lds64f(uint32_t a, int o) { const uint2 v = lds64(a, o); return make_float2(__uint_as_float(v.x), __uint_as_float(v.y)); }
DI uint32_t lds32(uint32_t a, int o) { uint32_t v; asm volatile("ld.shared.u32 %0, [%1];" : "=r"(v) : "r"(ad(a, o)) : "memory"); return v; }
DI float ldsf(uint32_t a, int o) { return __uint_as_float(lds32(a, o)); }
DI void sts32(uint32_t a, int o, uint32_t v) { asm volatile("st.shared.u32 [%0], %1;" :: "r"(ad(a, o)), "r"(v) : "memory"); }
DI void stsf(uint32_t a, int o, float v) { sts32(a, o, __float_as_uint(v)); }
DI void sts16(uint32_t a, int o, uint32_t v) { asm volatile("st.shared.u16 [%0], %1;" :: "r"(ad(a, o)), "h"((uint16_t)v) : "memory"); }
DI void sts64(uint32_t a, int o, uint32_t x, uint32_t y) { asm volatile("st.shared.v2.u32 [%0], {%1,%2};" :: "r"(ad(a, o)), "r"(x), "r"(y) : "memory"); }
DI void sts128(uint32_t a, int o, uint32_t x, uint32_t y, uint32_t z, uint32_t w) {
    asm volatile("st.shared.v4.u32 [%0], {%1,%2,%3,%4};" :: "r"(ad(a, o)), "r"(x), "r"(y), "r"(z), "r"(w) : "memory");
}
DI void sts128f_if(bool p, uint32_t a, int o, float x, float y, float z, float w) {
    asm volatile("{\n.reg .pred p;\nsetp.ne.u32 p, %5, 0;\n@p st.shared.v4.f32 [%0], {%1,%2,%3,%4};\n}" :: "r"(ad(a, o)), "f"(x), "f"(y), "f"(z), "f"(w), "r"((int)p) : "memory");
}
DI void sts32_if(bool p, uint32_t a, int o, uint32_t v) {
    asm volatile("{\n.reg .pred p;\nsetp.ne.u32 p, %2, 0;\n@p st.shared.u32 [%0], %1;\n}" :: "r"(ad(a, o)), "r"(v), "r"((int)p) : "memory");
}
DI uint32_t atoms_inc(uint32_t a, uint32_t lim) {
    uint32_t old; asm volatile("atom.relaxed.cta.shared.inc.u32 %0, [%1], %2;" : "=r"(old) : "r"(a), "r"(lim) : "memory"); return old;
}
DI void mma(float (&c)[4], uint32_t a0, uint32_t a1, uint32_t a2, uint32_t a3, uint32_t b0, uint32_t b1) {
    asm volatile("mma.sync.aligned.m16n8k16.row.col.f32.bf16.bf16.f32 {%0,%1,%2,%3}, {%4,%5,%6,%7}, {%8,%9}, {%0,%1,%2,%3};"
                 : "+f"(c[0]), "+f"(c[1]), "+f"(c[2]), "+f"(c[3]) : "r"(a0), "r"(a1), "r"(a2), "r"(a3), "r"(b0), "r"(b1));
}
DI void mma(float (&c)[4], const uint4& a, uint32_t b0, uint32_t b1) { mma(c, a.x, a.y, a.z, a.w, b0, b1); }
DI void zero4(float (&c)[4]) { c[0] = c[1] = c[2] = c[3] = 0.f; }
DI u64 ld_rlx(const void* p) {
    u64 a; asm volatile("ld.relaxed.gpu.global.u64 %0, [%1];" : "=l"(a) : "l"(p) : "memory"); return a;
}
DI void st_rlx(void* p, u64 a) { asm volatile("st.relaxed.gpu.global.u64 [%0], %1;" :: "l"(p), "l"(a) : "memory"); }
DI uint4 ldg128(const void* p) {
    uint4 v; asm volatile("ld.global.nc.L1::no_allocate.L2::cache_hint.v4.u32 {%0,%1,%2,%3}, [%4], %5;" : "=r"(v.x), "=r"(v.y), "=r"(v.z), "=r"(v.w) : "l"(p), "l"((u64)POL_FIRST << 32)); return v;
}
DI float bf_lo(uint32_t u) { return __uint_as_float(u << 16); }
DI float bf_hi(uint32_t u) { return __uint_as_float(u & 0xffff0000u); }
DI uint32_t pack_bf(float lo, float hi) {
    uint32_t r; asm("cvt.rn.bf16x2.f32 %0, %1, %2;" : "=r"(r) : "f"(hi), "f"(lo)); return r;
}
DI uint32_t pick(uint32_t a, uint32_t sel) { uint32_t r; asm("prmt.b32 %0, %1, 0, %2;" : "=r"(r) : "r"(a), "r"(sel)); return r; }
DI uint32_t bf2_amax(uint32_t a, uint32_t b) { uint32_t r; asm("max.NaN.xorsign.abs.bf16x2 %0, %1, %2;" : "=r"(r) : "r"(a), "r"(b)); return r; }
DI uint32_t bf2_amin(uint32_t a, uint32_t b) { uint32_t r; asm("min.xorsign.abs.bf16x2 %0, %1, %2;" : "=r"(r) : "r"(a), "r"(b)); return r; }
DI uint32_t bf2_mulv(uint32_t a, uint32_t b) { uint32_t r; asm volatile("mul.rn.bf16x2 %0, %2, %1;" : "=r"(r) : "r"(a), "r"(b)); return r; }
DI uint32_t bf2_mul(uint32_t a, uint32_t b) { uint32_t r; asm("mul.rn.bf16x2 %0, %1, %2;" : "=r"(r) : "r"(a), "r"(b)); return r; }
DI uint32_t bf2_fma(uint32_t a, uint32_t b, uint32_t c) { uint32_t r; asm("fma.rn.bf16x2 %0, %1, %2, %3;" : "=r"(r) : "r"(a), "r"(b), "r"(c)); return r; }
DI float ex2(float v) { float r; asm("ex2.approx.ftz.f32 %0, %1;" : "=f"(r) : "f"(v)); return r; }
DI float rcp(float v) { float r; asm("rcp.approx.ftz.f32 %0, %1;" : "=f"(r) : "f"(v)); return r; }
DI float rsq(float v) { float r; asm("rsqrt.approx.ftz.f32 %0, %1;" : "=f"(r) : "f"(v)); return r; }
DI void bar_sync(int id, int n) { asm volatile("bar.sync %0, %1;" :: "r"(id), "r"(n) : "memory"); }
DI uint32_t clk() { uint32_t c; asm volatile("mov.u32 %0, %clock;" : "=r"(c)); return c; }
DI uint32_t gtime() { uint32_t c; asm volatile("mov.u32 %0, %globaltimer_lo;" : "=r"(c)); return c; }
DI uint32_t pin(uint32_t v) { return __shfl_xor_sync(~0u, v, 0); }
DI float pinf(float v) { return __shfl_xor_sync(~0u, v, 0); }
template <class T> DI T* pinp(T* p) { return reinterpret_cast<T*>(__shfl_xor_sync(~0u, (u64)p, 0)); }
DI u64 mk64(uint32_t lo, uint32_t hi) { u64 r; asm("mov.b64 %0, {%1, %2};" : "=l"(r) : "r"(lo), "r"(hi)); return r; }
DI float shx(float v, int o) { return __shfl_xor_sync(~0u, v, o); }

DI u64 fx_pack(float v) {
    u64 r; asm("{\n.reg .u32 a, b;\n.reg .s64 w;\ncvt.rni.s64.f32 w, %1;\nmov.b64 {a, b}, w;\nprmt.b32 a, a, 1, 0x3214;\nmov.b64 %0, {a, b};\n}" : "=l"(r) : "f"(v)); return r;
}
DI float fx_scale(float meansq) {
    const int e = max(((int)(__float_as_uint(meansq) >> 23) - 127) >> 1, -14);
    return __uint_as_float((uint32_t)(127 + 32 - e) << 23);
}
DI float fx_inv(float scale) { return __uint_as_float((254u << 23) - __float_as_uint(scale)); }
DI uint32_t lo32(u64 w) { uint32_t l; asm("mov.b64 {%0, _}, %1;" : "=r"(l) : "l"(w)); return l; }
DI int hi32(u64 w) { int h; asm("mov.b64 {_, %0}, %1;" : "=r"(h) : "l"(w)); return h; }
DI float fx_val(u64 w) { return (float)hi32(w) * 4294967296.f + (float)lo32(w); }
DI void fx_poll(const unsigned char* ap, u64 (&w)[4]) {
    asm volatile("{\n.reg .pred p, q;\n.reg .u32 n, a, b, c, d;\nmov.u32 n, 0;\nLOOP:\n"
                 "ld.relaxed.gpu.global.u64 %0, [%4];\nld.relaxed.gpu.global.u64 %1, [%4+5120];\n"
                 "ld.relaxed.gpu.global.u64 %2, [%4+10240];\nld.relaxed.gpu.global.u64 %3, [%4+15360];\n"
                 "add.u32 n, n, 1;\nsetp.ge.u32 q, n, 0x100000;\n@q bra.uni DONE;\n"
                 "mov.b64 {a, _}, %0;\nmov.b64 {b, _}, %1;\nmov.b64 {c, _}, %2;\nmov.b64 {d, _}, %3;\n"
                 "lop3.b32 a, a, b, c, 0x80;\nlop3.b32 a, a, d, 32, 0x80;\nsetp.eq.u32 p, a, 0;\n"
                 "vote.sync.any.pred p, p, 0xffffffff;\n@p bra.uni LOOP;\nDONE:\n}"
                 : "=l"(w[0]), "=l"(w[1]), "=l"(w[2]), "=l"(w[3]) : "l"(ap) : "memory");
}
constexpr u64 FX2_INIT = 256ull + 32 - 96 * ((1ull << 28) + (1ull << 55)), FX2_NONE = 1ull + (1ull << 28) + (1ull << 55);
constexpr float FX2_MAGIC = 12582912.f + 524288.f;

DI void tma3(uint32_t dst, const CUtensorMap* tm, int c1, int c2, uint32_t bar, uint32_t pol) {
    asm volatile("cp.async.bulk.tensor.3d.shared::cluster.global.mbarrier::complete_tx::bytes.L2::cache_hint [%0], [%1, {%2, %3, %4}], [%5], %6;"
                 :: "r"(dst), "l"(tm), "r"(0), "r"(c1), "r"(c2), "r"(bar), "l"((u64)pol << 32) : "memory");
}
DI void tma3_pf(const CUtensorMap* tm, int c1, int c2, uint32_t pol) {
    asm volatile("cp.async.bulk.prefetch.tensor.3d.L2.global.tile.L2::cache_hint [%0, {%1, %2, %3}], %4;"
                 :: "l"(tm), "r"(0), "r"(c1), "r"(c2), "l"((u64)pol << 32) : "memory");
}
DI void bulk_pf(const void* p, uint32_t bytes, uint32_t pol) {
    asm volatile("cp.async.bulk.prefetch.L2.global.L2::cache_hint [%0], %1, %2;" :: "l"(p), "r"(bytes), "l"((u64)pol << 32) : "memory");
}
DI float warp_max(float v) {
    const int k = __float_as_int(v), m = __reduce_max_sync(~0u, k ^ ((k >> 31) & 0x7fffffff));
    return __int_as_float(m ^ ((m >> 31) & 0x7fffffff));
}
DI u64 ll_pack2(float a, float b, uint32_t tag) { return mk64(__byte_perm(__float_as_uint(a), tag, 0x3214), __float_as_uint(b)); }
DI float lof(u64 w) { return __uint_as_float(lo32(w)); }
DI float hif(u64 w) { return __int_as_float(hi32(w)); }
DI void ll_gather4(const u64* buf, uint32_t tag, u64 (&w)[4]) {
#pragma unroll 1
    for (int it = 0; it < SPIN; it++) {
        if (it) { w[0] = ld_rlx(buf); w[1] = ld_rlx(buf + 256); w[2] = ld_rlx(buf + 512); w[3] = ld_rlx(buf + 768); }
        if (!__any_sync(~0u, (((lo32(w[0]) ^ tag) | (lo32(w[1]) ^ tag)) | ((lo32(w[2]) ^ tag) | (lo32(w[3]) ^ tag))) & 255)) break;
    }
}
DI u64 lds_u64(uint32_t a, int o) { const uint2 v = lds64(a, o); return v.x | (u64)v.y << 32; }
DI float sum8(uint32_t a, int o, int pitch) {
    float s[8];
#pragma unroll
    for (int w = 0; w < 8; w++) s[w] = ldsf(a, o + w * pitch);
    return ((s[0] + s[1]) + (s[2] + s[3])) + ((s[4] + s[5]) + (s[6] + s[7]));
}
DI void ln_final(float& mean, float& rstd, float& msq) {
    float2 v[5];
#pragma unroll
    for (int w = 0; w < 5; w++) v[w] = lds64f(0, SM_STAT + w * 8);
    mean = (((v[0].x + v[1].x) + (v[2].x + v[3].x)) + v[4].x) * (1.f / D_MODEL);
    msq = (((v[0].y + v[1].y) + (v[2].y + v[3].y)) + v[4].y) * (1.f / D_MODEL);
    rstd = rsq(fmaxf(msq - mean * mean, 0.f) + 1e-5f);
}
constexpr float CS = 0.07216878364870322f * 1.4426950408889634f;
constexpr uint32_t ONES = 0x3f803f80u;

__global__ void __launch_bounds__(NTHR, 1) fused_kernel(const __grid_constant__ Params P) {
    extern __shared__ __align__(1024) unsigned char smem[];
    const int warp = __shfl_sync(~0u, threadIdx.x >> 5, 0), bx = blockIdx.x;
    const int cta = (((bx >> 1) & 15) + (bx >> 6) * 16) * 4 + ((bx >> 5) & 1) * 2 + (bx & 1);

    if (bx == NCTA) {
        if ((uint32_t)__cvta_generic_to_shared(smem) != SM_RING) __trap();
        const uint32_t ep = *(volatile unsigned*)&g_epoch;
        if (threadIdx.x == 0) {
#pragma unroll 1
            for (int it = 0; it < SPIN; it++) { if ((lo32(ld_rlx(&g_ll[0][192])) & 255) == ((ep * 8 + 1) & 255)) break; __nanosleep(200); }
            const uint32_t t0 = gtime();
#pragma unroll 1
            for (int it = 0; it < 1024; it++) { if (gtime() - t0 > HZD) break; __nanosleep(100); }
        }
        __syncthreads();
#pragma unroll 1
        for (int i = threadIdx.x; i < 4 * 80 * 8; i += NTHR)
        {
            const u64 v = (i / 640 & 1) && (i & 7) < 2 ? FX2_INIT : 0ull;
            *reinterpret_cast<ulonglong2*>(g_acc + (i >> 3) * ACC_PITCH + (i & 7) * 16) = make_ulonglong2(v, v);
        }
        __threadfence();
        __syncthreads();
        if (threadIdx.x == 0) asm volatile("st.relaxed.gpu.global.u32 [%0], %1;" :: "l"(&g_zflag), "r"(ep + 1) : "memory");
        return;
    }
    const uint32_t barw = SM_BAR + warp * 64;
    if (elect()) {
        if (warp < 3) sts32(0, SM_T0, gtime());
        else {
            mbar_init(barw + 56, 1);
            asm volatile("fence.mbarrier_init.release.cluster;" ::: "memory");
            mbar_expect(barw + 56, HT);
            tma3(SM_WQ - 3 * HT + warp * HT, &P.tm[TM_WQ], (cta >> 2) * 3, (cta & 3) * 160 - 96 + warp * 32, barw + 56, POL_FIRST);
        }
    }
    int tid = threadIdx.x, lane, g, t, c4;
    uint32_t selA, selB, offV0, offV2;
    auto derive = [&]() {
        lane = tid & 31; g = lane >> 2; t = lane & 3;
        c4 = (tid & 0xe1) + 16 * (t >> 1) + 2 * g;
        selA = (g & 2) ? 0x4444u : (g & 1) ? 0x1044u : 0x4410u;
        selB = (g & 2) ? ((g & 1) ? 0x1044u : 0x4410u) : 0x4444u;
        offV0 = (6 * t) * 128 + ((g ^ ((6 * t) & 7)) << 4);
        offV2 = (6 * t) * 128 + ((g ^ ((6 * t + 2) & 7)) << 4);
    };
    auto refresh = [&]() { tid = pin(tid); derive(); };
    auto refresh_late = [&]() { mbar_wait(SM_BAR + 3 * 64 + 56, 0); refresh(); };
    derive();
    const uint32_t zero = bx >> 16;
    const int j40 = (cta & 3) * 40;
    const bool mlp = (cta & 3) != 3;
    const int hu = ((cta >> 2) * 3 + (cta & 3)) * 16;
    uint2 xp = make_uint2(0, 0);
    uint32_t kc[192];
    const int rowc = (cta >> 2) * SK + (SK - WIN) + (cta & 3) * 64;
    const int roww = __shfl_sync(~0u, rowc + warp * 8, 0);
    const CUtensorMap* tmk = reinterpret_cast<const CUtensorMap*>(__shfl_sync(~0u, (u64)&P.tm[0] + (lane >> 5), 0));

    auto wait_due = [&](int i, int extra) {
        const uint32_t due = lds32(0, SM_T0) + PACE0 + extra + i * PACE;
#pragma unroll 1
        for (int it = 0; it < 4096; it++) if ((int)(gtime() - due) >= 0) break;
    };
    auto issue_wo = [&](int k) {
        wait_due(64, k * WOPACE);
        mbar_expect(SM_CBAR + 32 + k * 8, 4 * WOU);
        asm volatile("cp.async.bulk.tensor.4d.shared::cluster.global.mbarrier::complete_tx::bytes.L2::cache_hint [%0], [%1, {%2, %3, %4, %5}], [%6], %7;"
                     :: "r"(SM_RING + k * 4 * WOU), "l"(tmk + TM_WO4), "r"(0), "r"(5 * (cta & 3)), "r"((k >> 1) * 8), "r"((cta >> 2) * 8 + (k & 1) * 4),
                        "r"(SM_CBAR + 32 + k * 8), "l"((u64)POL_FIRST << 32) : "memory");
        if (k < 4 && mlp)
            asm volatile("cp.async.bulk.prefetch.tensor.4d.L2.global.tile.L2::cache_hint [%0, {%1, %2, %3, %4}], %5;"
                         :: "l"(tmk + TM_WOP), "r"(0), "r"(5 * (cta & 3)), "r"((k >> 1) * 8), "r"((cta >> 2) * 8 + (k & 1) * 4), "l"((u64)POL_NORMAL << 32) : "memory");
    };
    auto issue_kv = [&](int i, int slot, int bar) {
        const int row = rowc + (i & 30) * 128 + (i & 1) * 32;
        mbar_expect(SM_CBAR + bar * 8, HT);
        tma3(SM_RING + slot * HT, tmk + TM_K + (i >> 5), 0, row, SM_CBAR + bar * 8, POL_FIRST);
        if (i >= 32) tma3_pf(tmk + TM_VP, 0, row, POL_NORMAL);
    };
    auto ep8 = [&]() { return lds32(0, SM_EPOCH); };
    auto load_v3 = [&](uint4* v, uint32_t u, int o, bool odd) {
        if (!odd) { v[0] = lds128(ad(offV0, u), o); v[1] = lds128(ad(offV0 ^ 16, u), o + 128); v[2] = lds128(ad(offV2, u), o + 256); }
        else { v[0] = lds128(ad(offV2 ^ 16, u), o + 384); v[1] = lds128(ad(offV0 ^ 64, u), o + 512); v[2] = lds128(ad(offV0 ^ 80, u), o + 640); }
    };
    auto load_v = [&](uint4 (&v)[6], uint32_t u, int o) { load_v3(v, u, o, false); load_v3(v + 3, u, o, true); };
    const uint32_t wqw = warp * SUB, ksw = warp * HT;
    auto slot_o = [&](int s) { return s < 3 ? SM_WQ + s * 8 * SUB : SM_KS + (s - 3) * SUB; };
    auto slot_u = [&](int s) { return s < 3 ? wqw : ksw; };
    auto issue2 = [&](auto I, uint32_t dep) {
        constexpr int p = I.value, s = PL.slot[p];
        __syncwarp();
        if ((p < 16 || mlp) && elect()) {
            mbar_expect(barw + s * 8, (dep & zero) | (p < 16 ? SUB : 2 * WOU + 256));
            if constexpr (p < 16) tma3(slot_u(s) + slot_o(s), tmk + TM_V8, 0, roww + vunit(p) * 256, barw + s * 8, POL_FIRST);
            else {
                tma3(slot_u(s) + slot_o(s), tmk + TM_WO, 5 * (cta & 3), (cta >> 2) * DH + warp * 24, barw + s * 8, POL_FIRST);
                asm volatile("cp.async.bulk.shared::cluster.global.mbarrier::complete_tx::bytes [%0], [%1], 256, [%2];"
                             :: "r"(slot_u(s) + slot_o(s) + 2 * WOU), "l"(P.b2 + min(warp, 4) * 128), "r"(barw + s * 8) : "memory");
            }
        }
    };
    auto touch2 = [&]() {
        const char* p = reinterpret_cast<const char*>(P.v) + (size_t)(roww + vunit(2) * 256) * (DH * 2) + lane * 32;
#pragma unroll
        for (int i = 0; i < 3; i++) asm volatile("cp.async.ca.shared.global [%0], [%1], 4;" :: "r"(SM_JUNK), "l"(p + i * 1024) : "memory");
    };
    auto issue_help = [&]() {
        if (elect())
            tma3(SM_WQ + (warp == 7 ? 0 : warp == 6 ? 16 * SUB : 4 * SUB), tmk + (warp == 5 ? TM_V8 : TM_V), 0,
                 rowc + (warp == 6 ? vunit(2) * 256 : warp == 5 ? vunit(0) * 256 + 32 : vunit(0) * 256), warp == 5 ? SM_BAR + 4 * 64 : SM_CBAR - 32 + warp * 8, POL_FIRST);
    };
    auto issue_item1 = [&]() {
        if (elect()) {
            mbar_expect(SM_CBAR - 48 + warp * 8, HT);
            tma3(SM_WQ - 4 * HT + warp * HT, tmk + TM_V, 0, rowc - 192 + warp * 32 + vunit(1) * 256, SM_CBAR - 48 + warp * 8, POL_FIRST);
        }
    };
    const uint32_t prow = warp * 768;
    uint4 wq0[6], wqh[3];
    uint32_t xna;
    auto load_wq = [&]() {
        load_v(wq0, wqw, SM_WQ);
        const int r0 = 6 * t + 3 * (warp & 1);
#pragma unroll
        for (int j = 0; j < 3; j++) wqh[j] = lds128(ad(r0 * 128 + ((g ^ ((r0 + j) & 7)) << 4), (warp >> 1) * SUB), SM_WQ + 16 * SUB + j * 128);
        const int r = c4 - j40;
        xna = pin((tid < 160 && r >= 0 && r < 40) ? SM_VEC + r * 8 : 0u);
        selA = pin(selA); selB = pin(selB);
        offV0 = pin(offV0 + wqw); offV2 = pin(offV2 + wqw);
        tid = pin(tid);
    };
    float acc[3][4];
    auto mma3 = [&](const uint4* v, uint32_t pp, uint32_t hi) {
        const uint32_t b0 = pick(pp, selA | hi), b1 = pick(pp, selB | hi);
        mma(acc[0], v[0], b0, b1); mma(acc[1], v[1], b0, b1); mma(acc[2], v[2], b0, b1);
    };
    auto ln_part = [&]() {
        const float x0 = bf_lo(xp.x), x1 = bf_hi(xp.x), x2 = bf_lo(xp.y), x3 = bf_hi(xp.y);
        const float s1 = (x0 + x1) + (x2 + x3), s2 = (x0 * x0 + x1 * x1) + (x2 * x2 + x3 * x3);
        float ss = ((tid & 16) ? s2 : s1) + shx((tid & 16) ? s1 : s2, 16);
        ss += shx(ss, 8); ss += shx(ss, 4); ss += shx(ss, 2); ss += shx(ss, 1);
        sts32_if((tid & 15) == 0 && tid < 160, tid >> 2, SM_STAT, __float_as_uint(ss));
    };

    auto tick = [&](uint4& v) {
        asm volatile("{\n.reg .pred p;\nsetp.ne.u32 p, %4, 0;\n@p mma.sync.aligned.m16n8k16.row.col.f32.bf16.bf16.f32 {%0,%1,%2,%3}, {%0,%1,%2,%3}, {%0,%1}, {%0,%1,%2,%3};\n}"
                     : "+r"(v.x), "+r"(v.y), "+r"(v.z), "+r"(v.w) : "r"(zero));
    };

    auto q_stage = [&](auto L) {
        constexpr int layer = L.value;
        asm volatile("{\n.reg .pred p;\nsetp.ne.u32 p, %0, 0;\n@p st.shared.v2.u32 [%0], {%1,%2};\n}" :: "r"(xna), "r"(xp.x), "r"(xp.y) : "memory");
        uint4 wq1[6];
        load_v3(wq1, 0, SM_WQ + 8 * SUB, false);
        const uint32_t xra = (tid & 3) * 4;
        __syncthreads();
        uint32_t p0 = lds32(ad(xra, warp * 16), SM_VEC), ph = lds32(ad(xra, (warp >> 1) * 16), SM_VEC + 256), p1 = lds32(ad(xra, warp * 16), SM_VEC + 128);
        if (layer == 0 && (tid & 16)) p0 = p1 = ph = ONES;
#pragma unroll
        for (int j = 0; j < 3; j++) zero4(acc[j]);
        mma3(wq0, p0, 0); mma3(wq0 + 3, p0, 0x2222);
        load_v3(wq1 + 3, 0, SM_WQ + 8 * SUB, true);
        mma3(wqh, ph, (warp & 1) * 0x2222); mma3(wq1, p1, 0); mma3(wq1 + 3, p1, 0x2222);
        if (layer == 1) { lds128(kc + 8, prow + (tid & 31) * 16, SM_PART); lds64(kc + 180, prow + (tid & 31) * 8, SM_PART + 512); __syncwarp(); }
        const uint32_t qpa = ((layer == 0 && (tid & 2)) ? ksw - (SM_PART - SM_KS - 11264) : prow) + (tid & 28) * 8 + (tid & 1) * 16;
#pragma unroll
        for (int j = 0; j < 3; j++) sts128f_if(layer == 0 || !(tid & 2), qpa, SM_PART + j * 256, acc[j][0], acc[j][1], acc[j][2], acc[j][3]);
        u64* dst = &g_ll[cta][tid];
        const uint32_t tag = ep8() + 1 + 4 * layer;
        __syncthreads();
        if (warp < 6) {
            const float s = sum8(tid * 4, SM_PART, 768);
            st_rlx(dst, layer ? mk64(tag, __float_as_uint(s)) : ll_pack2(__uint_as_float(__float_as_uint(sum8(tid * 4, SM_KS + 11264, HT)) + 128), s, tag));
        } else if (layer == 1) { sts32(0, SM_T0, gtime()); issue_item1(); }
        refresh_late();
        ln_part();
        __syncthreads();
        sts64(prow + lane * 8, SM_PART, xp.x, xp.y);
        if (layer == 1) sts128(prow + lane * 16, SM_PART + 256, kc[8], kc[9], kc[10], kc[11]);
    };
    auto q_addr = [&]() { return (((tid >> 1) & 1) * 4 + ((tid >> 4) & 3)) * 48 + ((tid >> 6) * 2 + ((tid >> 3) & 1)) * 8 + ((tid >> 2) & 1) * 4 + (tid & 1) * 2; };
    auto score6 = [&](const uint4 (&v)[6], const uint32_t (&qf)[12]) {
        float d[2][4];
#pragma unroll
        for (int i = 0; i < 6; i++) { if (i < 2) zero4(d[i]); mma(d[i & 1], v[i], qf[2 * i], qf[2 * i + 1]); }
        return (d[0][0] + d[0][3]) + (d[1][0] + d[1][3]);
    };
    auto softmax = [&](auto L, const float (&S)[4]) {
        constexpr int layer = L.value;
        const float mrun = warp_max(fmaxf(fmaxf(S[0], S[1]), fmaxf(S[2], S[3])));
        const float p0 = ex2((S[0] - mrun) * CS), p1 = ex2((S[1] - mrun) * CS), p2 = ex2((S[2] - mrun) * CS), p3 = ex2((S[3] - mrun) * CS);
        const uint32_t pa = pack_bf(p0, p1), pb = pack_bf(p2, p3), pw = prow + t * 64 + g * 2;
        sts16(pw, SM_PART + 256, pa); sts16(pw, SM_PART + 272, pa >> 16); sts16(pw, SM_PART + 288, pb); sts16(pw, SM_PART + 304, pb >> 16);
        const uint32_t l = __reduce_add_sync(~0u, __float2uint_rn(((p0 + p1) + (p2 + p3)) * 16777216.f));
        st_rlx(&g_ll[cta][192 + warp], mk64(__byte_perm(l + 128, ep8() + 1 + 4 * layer, 0x3214), __float_as_uint(mrun)));
        __syncwarp();
#pragma unroll
        for (int j = 0; j < 3; j++) zero4(acc[j]);
    };
    auto pv = [&](const uint4 (&v)[6], uint32_t pp) { mma3(v, pp, 0); mma3(v + 3, pp, 0x2222); };

    auto head_look = [&]() {
        if (lane < 16) asm volatile("cp.async.cg.shared.global [%0], [%1], 16;" :: "r"(SM_PART + 512 + prow + lane * 16), "l"(&g_ll[cta ^ g][192 + 2 * t]) : "memory");
    };
    float fw;
    auto head_weight = [&](auto L) {
        const uint32_t tag = (ep8() + 1 + 4 * L.value) & 255;
        uint32_t l, m;
#pragma unroll 1
        for (int it = 0; it < SPIN; it++) {
            if (it) head_look();
            asm volatile("cp.async.wait_all;" ::: "memory");
            __syncwarp();
            asm volatile("ld.volatile.shared.v2.u32 {%0,%1}, [%2];" : "=r"(l), "=r"(m) : "r"(SM_PART + 512 + prow + lane * 8) : "memory");
            l ^= tag;
            if (!__any_sync(~0u, l & 255)) break;
        }
        const float f = ex2((__uint_as_float(m) - warp_max(__uint_as_float(m))) * CS);
        const uint32_t Lh = __reduce_add_sync(~0u, __float2uint_rn(f * (float)l * 0.03125f));
        fw = __shfl_sync(~0u, f, warp) * rcp((float)Lh) * (ldsf(0, SM_FXS) * 524288.f);
    };

    uint32_t wa[5], ya, oa, selC, selD, tag;
    uint4 z[5];
    unsigned char* ra;
    const u64* lp;
    auto load_u = [&](uint4 (&a)[5], uint32_t u, int o) {
#pragma unroll
        for (int k = 0; k < 5; k++) a[k] = lds128(ad(wa[k], u), o);
    };
    auto tail_prep1 = [&](auto L) {
        xp = lds64(prow + lane * 8, SM_PART);
        tag = (ep8() + 3 + 4 * L.value) & 255;
        ya = pin(prow + (8 * g + 4 * (t & 1)) * 4);
        oa = pin(((tid >> 5) * 12 + min(lane, 11)) * 8);
        lp = pinp(reinterpret_cast<const u64*>(reinterpret_cast<const char*>(&g_ll[cta][0]) + oa));
    };
    auto tail_prep2 = [&](auto L) {
#pragma unroll
        for (int k = 0; k < 5; k++) {
            const int row = (t & 1) + 2 * (t & 2) + 2 * (k < 4 ? k >> 1 : g >> 2), j = k < 4 ? 2 * (k & 1) + (g >> 2) : 4;
            wa[k] = pin(row * 320 + j * 64 + (((g & 3) ^ (((5 * row + j) >> 1) & 3)) << 4));
        }
        selA = pin(selA); selB = pin(selB);
        selC = selA | (g >> 2) * 0x2222; selD = selB | (g >> 2) * 0x2222;
    };
    auto red_addr = [&](auto L) {
        const int word = t * 160 + j40 + (tid >> 2);
        ra = pinp(g_acc + 2 * L.value * ACC_BYTES + (uint32_t)((word >> 3) * ACC_PITCH + (word & 7) * 8));
    };
    uint4 wf[8], w2r[8];
    uint32_t la, w2a, hpa, ha, *op;
    uint2 b2v;
    const unsigned char* ap;
    unsigned char* ap2;
    float inv1;
    auto load_w1 = [&]() {
#pragma unroll
        for (int j = 0; j < 8; j++) wf[j] = ldsm_t(la, SM_RING + j * 256);
    };
    auto load_w2 = [&]() {
#pragma unroll
        for (int i = 0; i < 8; i++) w2r[i] = lds128(w2a ^ ((i & 1) * 16), SM_W2 + (i >> 1) * 5120 + (i & 1) * 128);
    };
    auto load_b2 = [&]() { asm volatile("ld.global.nc.v2.u32 {%0,%1}, [%2];" : "=r"(b2v.x), "=r"(b2v.y) : "l"(P.b2 + 4 * min(c4, 159))); };
    auto mlp_prep = [&](auto L) {
        unsigned char* const accb = g_acc + 2 * L.value * ACC_BYTES;
        la = (tid >> 5) * 4096 + (64 * ((lane >> 2) & 1) + 4 * ((lane >> 1) & 1) + (lane & 1) + 2 * (lane >> 4)) * 32 + ((((lane >> 3) ^ (lane >> 1)) & 1) << 4);
        w2a = pin((10 * t + 2 * (tid >> 5)) * 128 + ((g ^ ((2 * t + 2 * (tid >> 5)) & 7)) << 4));
        hpa = pin((tid >> 5) * 64 + (t * 8 + g) * 4); ha = pin((lane & 15) * 4);
        if (L.value == 0) { selA = pin(selA); selB = pin(selB); tid = pin(tid); }
        ap = accb + (uint32_t)((c4 >> 3) * ACC_PITCH + (c4 & 7) * 8);
        ap2 = accb + ACC_BYTES + pin((c4 >> 2) * ACC_PITCH + (c4 & 3) * 8);
        if (L.value == 1) ap2 = pinp(ap2);
        inv1 = fx_inv(ldsf(0, SM_FXS));
        if (L.value == 1) { ap = pinp(ap); la = pin(la); op = pinp(reinterpret_cast<uint32_t*>(P.out) + 2 * c4); }
    };
    auto tail = [&](auto L) {
        constexpr int layer = L.value;
        uint32_t cq;
        auto park = [&]() { const int ln = pin(tid) & 31; sts128(prow + ln * 16, SM_PART, kc[8], kc[9], kc[10], kc[11]); sts64(prow + ln * 8, SM_PART + 512, kc[180], kc[181]); };
        {
#pragma unroll
            for (int j = 0; j < 3; j++) sts128f_if(!(tid & 2), ya, SM_PART + 256 * j, acc[j][0] * fw, acc[j][2] * fw, acc[j][1] * fw, acc[j][3] * fw);
            __syncthreads();
            float2 own;
            {
                float2 s[8];
#pragma unroll
                for (int w = 0; w < 8; w++) s[w] = lds64f(oa, SM_PART + w * 768);
                own.x = ((s[0].x + s[1].x) + (s[2].x + s[3].x)) + ((s[4].x + s[5].x) + (s[6].x + s[7].x));
                own.y = ((s[0].y + s[1].y) + (s[2].y + s[3].y)) + ((s[4].y + s[5].y) + (s[6].y + s[7].y));
                st_rlx(const_cast<u64*>(lp), ll_pack2(own.x, own.y, tag));
            }
            const uint32_t c0 = clk();
            if (layer == 0) refresh_late();
            uint4 v[5], u[5];
            if constexpr (layer == 0) {
                if (warp < 3) { if (elect()) issue_wo(3 + warp); __syncwarp(); }
                if (warp >= 4) touch2();
                tail_prep2(L);
                mbar_wait(SM_CBAR + 32 + (warp >> 2) * 8, 0);
                load_u(v, warp * WOU, SM_RING);
                __syncthreads();
            }
            constexpr int YP = layer ? SM_WQ : SM_PART;
            float y[3][4];
#pragma unroll
            for (int j = 0; j < 3; j++) zero4(y[j]);
            const u64 *l1 = reinterpret_cast<const u64*>((u64)lp ^ 4096), *l2 = reinterpret_cast<const u64*>((u64)lp ^ 2048), *l3 = reinterpret_cast<const u64*>((u64)lp ^ 6144);
            tick(layer ? z[0] : v[0]);
            if (layer) while (clk() - c0 < ODELAY);
            uint32_t w1due = 0;
            if (layer == 0) {
                const uint32_t now = gtime();
                w1due = lds32(0, SM_T0) + PACE0 + 69 * PACE + W1D;
                w1due = ((int)(now - w1due) > 0 ? now : w1due) + (warp - 3) * W1G;
            }
            u64 w1 = ld_rlx(l1), w2 = ld_rlx(l2), w3 = ld_rlx(l3);
            if constexpr (layer == 1) {
                if (mlp) mbar_wait(barw + 40, IC<PL.par[16]>::value);
                load_u(v, mlp ? ksw + slot_o(5) : SM_RING + warp * WOU, 0); load_u(u, mlp ? ksw + slot_o(5) + WOU : SM_RING + (8 + warp) * WOU, 0);
            }
            if (layer == 0 && warp >= 3 && mlp) {
#pragma unroll 1
                for (int it = 0; it < 4096; it++) { tick(v[0]); if ((int)(gtime() - w1due) >= 0) break; }
                if (elect()) {
                    mbar_expect(SM_CBAR + 56 + warp * 8, 4096);
                    asm volatile("cp.async.bulk.tensor.2d.shared::cluster.global.mbarrier::complete_tx::bytes.L2::cache_hint [%0], [%1, {%2, %3}], [%4], %5;"
                                 :: "r"(SM_RING + (warp - 3) * 4096), "l"(tmk + TM_W1), "r"(hu), "r"(warp * 128 - 384), "r"(SM_CBAR + 56 + warp * 8), "l"((u64)POL_FIRST << 32) : "memory");
                }
                __syncwarp();
            }
#pragma unroll 1
            for (int it = 0; it < SPIN; it++) {
                if (it) { w1 = ld_rlx(l1); w2 = ld_rlx(l2); w3 = ld_rlx(l3); }
                if (!__any_sync(~0u, ((lo32(w1) ^ tag) | (lo32(w2) ^ tag) | (lo32(w3) ^ tag)) & 255)) break;
            }
            const uint32_t od = pack_bf((own.x + __uint_as_float(lo32(w1) ^ tag)) + (__uint_as_float(lo32(w2) ^ tag) + __uint_as_float(lo32(w3) ^ tag)),
                                        (own.y + __int_as_float(hi32(w1))) + (__int_as_float(hi32(w2)) + __int_as_float(hi32(w3))));
            const uint32_t o0 = __shfl_sync(~0u, od, tid & 3), o1 = __shfl_sync(~0u, od, (tid & 3) + 4), o2 = __shfl_sync(~0u, od, (tid & 3) + 8);
            auto narrow = [&](const uint4 (&a)[5], uint32_t o) { mma(y[2], a[4], pick(o, selC), pick(o, selD)); };
            auto wide = [&](const uint4 (&a)[5], uint32_t o) {
                const uint32_t b0 = pick(o, selA), b1 = pick(o, selB), b2 = pick(o, selA | 0x2222), b3 = pick(o, selB | 0x2222);
                mma(y[0], a[0], b0, b1); mma(y[1], a[1], b0, b1); mma(y[0], a[2], b2, b3); mma(y[1], a[3], b2, b3);
            };
            narrow(v, o0); wide(v, o0);
            if constexpr (layer == 0) {
                mbar_wait(SM_CBAR + 48 + (warp >> 2) * 8, 0);
                load_u(u, warp * WOU, SM_RING + 8 * WOU);
                __syncwarp();
                if (mlp && elect() && atoms_inc(SM_CNT + 44, 7) == 7) { mbar_expect(SM_CBAR + 120, 20480); tma3(SM_W2, tmk + TM_W2, 0, hu, SM_CBAR + 120, POL_FIRST); }
                __syncwarp();
                narrow(u, o1); wide(u, o1);
                red_addr(L);
                mbar_wait(SM_CBAR + 64 + (warp >> 2) * 8, 0);
                load_u(z, warp * WOU, SM_RING + 16 * WOU);
                narrow(z, o2);
            } else { narrow(u, o1); narrow(z, o2); wide(u, o1); }
            wide(z, o2);
#pragma unroll
            for (int k = 0; k < 4; k++) y[2][k] += shx(y[2][k], 18);
            sts128f_if(!(tid & 18), ya, YP + 512, y[2][0], y[2][1], y[2][2], y[2][3]);
            sts128f_if(!(tid & 2), ya, YP, y[0][0], y[0][1], y[0][2], y[0][3]);
            sts128f_if(!(tid & 2), ya, YP + 256, y[1][0], y[1][1], y[1][2], y[1][3]);
            __syncthreads();
            if (warp < 5) {
                const float s = sum8(tid * 4, YP, 768);
                asm volatile("red.relaxed.gpu.global.add.u64 [%0], %1;" :: "l"(ra), "l"(fx_pack(s)) : "memory");
            }
            cq = clk();
            if (layer == 0) refresh_late();
        }
        if (layer == 1 && !mlp) return;
        if (warp < 5) {
            if (layer == 0) { mlp_prep(L); if (mlp) mbar_wait(SM_CBAR + 80 + warp * 8, 0); }
            load_w1();
            if (layer == 1) { load_w2(); b2v = lds64(ksw + (c4 & 31) * 8, SM_KS + 11264); }
            {
                u64 w[4];
                while (clk() - cq < (layer || mlp ? AR1D : AR1DN));
                fx_poll(ap, w);
                xp = make_uint2(pack_bf(bf_lo(xp.x) + fx_val(w[0]) * inv1, bf_hi(xp.x) + fx_val(w[1]) * inv1),
                                pack_bf(bf_lo(xp.y) + fx_val(w[2]) * inv1, bf_hi(xp.y) + fx_val(w[3]) * inv1));
            }
            {
                const bool ev = layer || !(tid & 4), od = layer || (tid & 4);
                const uint32_t e0 = ev ? xp.x : ONES, e1 = ev ? xp.y : ONES, o0 = od ? xp.x : ONES, o1 = od ? xp.y : ONES;
                float d[8][4];
#pragma unroll
                for (int j = 0; j < 8; j++) { zero4(d[j]); mma(d[j], wf[j], (j & 1) ? o0 : e0, (j & 1) ? o1 : e1); }
                float lo = d[0][0] + d[1][1], hi = d[0][2] + d[1][3];
#pragma unroll
                for (int m = 1; m < 4; m++)
                    asm("{\n.reg .pred p;\nsetp.eq.u32 p, %6, %7;\n@p add.f32 %0, %2, %3;\n@p add.f32 %1, %4, %5;\n}" : "+f"(lo), "+f"(hi)
                        : "f"(d[2 * m][0]), "f"(d[2 * m + 1][1]), "f"(d[2 * m][2]), "f"(d[2 * m + 1][3]), "r"(tid & 3), "r"(m));
                float dd = ((tid & 1) ? hi : lo) + shx((tid & 1) ? lo : hi, 1);
                dd += shx(dd, 2);
                ln_part();
                if (layer == 0) {
                    const float cl = ((d[0][1] + d[1][0]) + (d[2][1] + d[3][0])) + ((d[4][1] + d[5][0]) + (d[6][1] + d[7][0]));
                    const float ch = ((d[0][3] + d[1][2]) + (d[2][3] + d[3][2])) + ((d[4][3] + d[5][2]) + (d[6][3] + d[7][2]));
                    sts32_if(!(tid & 2), hpa, SM_C1, __float_as_uint((tid & 1) ? ch : cl));
                }
                sts32_if(!(tid & 2), hpa, SM_QU, __float_as_uint(dd));
            }
            const float b1v = ldsf(ha, SM_B1);
            float csum = layer ? ldsf(ha, SM_B1 + 64) : 0.f;
            bar_sync(1, layer ? 160 : 192);
            float mean, rstd, msq;
            ln_final(mean, rstd, msq);
            float hp[5];
#pragma unroll
            for (int w = 0; w < 5; w++) hp[w] = ldsf(ha, SM_QU + w * 64);
            if constexpr (layer == 0) {
                float c[5];
#pragma unroll
                for (int w = 0; w < 5; w++) c[w] = ldsf(ha, SM_C1 + w * 64);
                csum = ((c[0] + c[1]) + (c[2] + c[3])) + c[4];
                load_w2();
            }
            float hv = ((((hp[0] + hp[1]) + (hp[2] + hp[3])) + hp[4]) - mean * csum) * rstd + b1v;
            hv = hv * rcp(1.f + ex2(hv * (-2.302208198f - 0.1029432397f * hv * hv)));
            const uint32_t hd = pack_bf(hv, hv);
            float ym[4][4];
            const uint32_t hh[4] = {__shfl_sync(~0u, hd, tid & 3), __shfl_sync(~0u, hd, (tid & 3) + 4), __shfl_sync(~0u, hd, (tid & 3) + 8), __shfl_sync(~0u, hd, (tid & 3) + 12)};
#pragma unroll
            for (int i = 0; i < 4; i++) {
                const uint32_t b0 = pick(hh[i], selA), b1 = pick(hh[i], selB);
                if (i < 2) { zero4(ym[2 * i]); zero4(ym[2 * i + 1]); }
                mma(ym[2 * (i & 1)], w2r[2 * i], b0, b1); mma(ym[2 * (i & 1) + 1], w2r[2 * i + 1], b0, b1);
            }
            const float sc2 = __uint_as_float((uint32_t)(127 + 16 - max(((int)(__float_as_uint(msq) >> 23) - 127) >> 1, -100)) << 23);
            float y[4];
            uint32_t yb[4];
#pragma unroll
            for (int k = 0; k < 4; k++) { y[k] = ((tid & 2) ? ym[1][k] : ym[0][k]) + ((tid & 2) ? ym[3][k] : ym[2][k]); yb[k] = __float_as_uint(fmaf(y[k], sc2, FX2_MAGIC)); }
            const uint32_t big = !mlp ? 0 : (((yb[0] ^ 0x4b400000u) | (yb[1] ^ 0x4b400000u)) | ((yb[2] ^ 0x4b400000u) | (yb[3] ^ 0x4b400000u))) & FX2_MASK;
            u64 w[2], old[2];
#pragma unroll
            for (int k = 0; k < 2; k++) {
                w[k] = mk64(big ? 0 : yb[2 * k] * 512 + 0x80000001u, big ? 0 : yb[2 * k + 1] * 16 + 0x4c000000u);
                if (layer == 0) { if (mlp) asm volatile("red.relaxed.gpu.global.add.u64 [%0], %1;" :: "l"(ap2 + k * 40 * ACC_PITCH), "l"(w[k]) : "memory"); }
                else asm volatile("atom.relaxed.gpu.global.add.u64 %0, [%1], %2;" : "=l"(old[k]) : "l"(ap2 + k * 40 * ACC_PITCH), "l"(w[k]) : "memory");
            }
            const uint32_t c0 = clk();
            if (__any_sync(~0u, big)) {
                if (big) {
#pragma unroll
                    for (int k = 0; k < 4; k++)
                        asm volatile("red.relaxed.gpu.global.add.u64 [%0], %1;" :: "l"(ap2 + (k >> 1) * 40 * ACC_PITCH + 64 + (k & 1) * 32), "l"(fx_pack(y[k] * fx_scale(msq))) : "memory");
                    fence_gpu();
#pragma unroll
                    for (int k = 0; k < 2; k++) {
                        asm volatile("red.relaxed.gpu.global.and.b64 [%0], %1;" :: "l"(ap2 + k * 40 * ACC_PITCH), "l"(~256ull) : "memory");
                        w[k] = FX2_NONE;
                        asm volatile("atom.relaxed.gpu.global.add.u64 %0, [%1], %2;" : "=l"(old[k]) : "l"(ap2 + k * 40 * ACC_PITCH), "l"(FX2_NONE) : "memory");
                    }
                }
                __syncwarp();
            }
            if (layer == 0) { refresh(); load_b2(); park(); stsf(ha, SM_B1 + 64, csum); }
            stsf(0, SM_FXS, msq);
            const float inv32 = fx_inv(sc2) * 0.03125f;
            float xb[4] = {bf_lo(xp.x) + bf_lo(b2v.x) - 24.f * inv32, bf_hi(xp.x) + bf_hi(b2v.x), bf_lo(xp.y) + bf_lo(b2v.y) - 24.f * inv32, bf_hi(xp.y) + bf_hi(b2v.y)};
            auto add_wide = [&]() {
                fence_gpu();
                const float inv = fx_inv(fx_scale(ldsf(0, SM_FXS)));
#pragma unroll
                for (int k = 0; k < 4; k++) xb[k] += fx_val(ld_rlx(ap2 + (k >> 1) * 40 * ACC_PITCH + 64 + (k & 1) * 32)) * inv;
            };
            auto sum2 = [&](int k) {
                return pack_bf(xb[2 * k] + (float)(int)__funnelshift_r(lo32(w[k]), hi32(w[k]), 4) * inv32, xb[2 * k + 1] + (float)hi32(w[k]) * (inv32 + inv32));
            };
            if constexpr (layer == 1) {
#pragma unroll
                for (int k = 0; k < 4; k++) xb[k] = pinf(xb[k]);
                mbar_wait(SM_BAR + 3 * 64 + 56, 0);
#pragma unroll
                for (int k = 0; k < 2; k++) {
                    w[k] += old[k];
                    asm volatile("{\n.reg .pred p;\nsetp.eq.u32 p, %2, 0;\n@p st.global.u32 [%0], %1;\n}" :: "l"(op + k), "r"(sum2(k)), "r"(~lo32(w[k]) & 0x180) : "memory");
                }
                if (((lo32(w[0]) & ~(lo32(w[0]) >> 1)) | (lo32(w[1]) & ~(lo32(w[1]) >> 1))) & 128) {
                    add_wide();
                    if (w[0] & 128) op[0] = sum2(0);
                    if (w[1] & 128) op[1] = sum2(1);
                }
            } else {
                load_wq();
                __syncwarp();
                if (elect()) mbar_arrive(SM_BAR + 56);
#pragma unroll
                for (int k = 0; k < 4; k++) xb[k] = pinf(xb[k]);
                while (clk() - c0 < AR2D);
                uint32_t want = 0x180;
#pragma unroll 1
                for (int it = 0; it < SPIN; it++) {
                    if (it && !__any_sync(~0u, ~(lo32(w[0]) & lo32(w[1])) & 128)) { add_wide(); want = 128; }
                    w[0] = ld_rlx(ap2); w[1] = ld_rlx(ap2 + 40 * ACC_PITCH);
                    if (!__any_sync(~0u, ~(lo32(w[0]) & lo32(w[1])) & want)) break;
                }
                xp = make_uint2(sum2(0), sum2(1));
            }
        } else if constexpr (layer == 1) {
            if (warp == 7) {
                const uint32_t c1 = clk();
                while (clk() - c1 < KAD) tick(z[0]);
                if (zero) sts32(0, SM_JUNK, z[0].x);
            }
        } else {
            const uint32_t c0 = clk();
            load_wq();
            __syncwarp();
            if (elect()) mbar_arrive(SM_BAR + 56);
            if (warp == 5) {
                if (mlp) mbar_wait(SM_CBAR + 120, 0);
                asm volatile("bar.arrive 1, 192;" ::: "memory");
            }
            while (clk() - c0 < S6D + (warp - 5) * S6G) tick(wqh[0]);
            issue2(IC<0>{}, wq0[0].x | wq0[1].x | wq0[2].x | wq0[3].x | wq0[4].x | wq0[5].x);
            if (warp == 5) {
#pragma unroll 1
                for (int k = 0; k < NPFC; k++) {
                    while (clk() - c0 < PFD + k * PFG);
                    if (elect()) tma3_pf(tmk + TM_V8, 0, rowc + (k >> 3) * 256 + (k & 7) * 8, POL_NORMAL);
                }
            }
            if (elect()) mbar_expect(warp == 5 ? SM_BAR + 4 * 64 : SM_CBAR - 32 + warp * 8, warp == 5 ? SUB : HT);
#pragma unroll 1
            for (int it = 0; it < SPIN; it++) { if (mbar_test(SM_BAR + 56, 0)) break; tick(wqh[0]); }
            const uint32_t c1 = clk();
            park();
            while (clk() - c1 < I0D) tick(wqh[0]);
            issue_help();
        }
    };

#pragma unroll 1
    for (uint32_t late = zero;; late = zero + 1) {
    if (late) {
    tail(IC<0>{});

    q_stage(IC<1>{});
    {
        const u64* qp = &g_ll[cta & ~3][tid];
        u64 w[4] = {0, 0, 0, 0};
        if (warp < 6) { w[0] = ld_rlx(qp); w[1] = ld_rlx(qp + 256); w[2] = ld_rlx(qp + 512); w[3] = ld_rlx(qp + 768); }
        mbar_wait(SM_BAR + 3 * 64 + 56, 0);
        const uint32_t ksl = ksw + lane * 16, qa = pin(q_addr()), qb0 = pin(lane < 8 ? lane * 48 : SM_ZQ - SM_VEC);
        uint32_t ks[96], qf[12];
        float mean, rstd, msq;
        ln_final(mean, rstd, msq);
        const float qc = pinf(-mean * rstd * ldsf(tid * 4, SM_CS));
#pragma unroll
        for (int k = 0; k < 6; k++) lds128(ks + 4 * k, ksl, SM_KS + k * 512);
        stsf(0, SM_FXS, fx_scale(msq));
        if (warp < 6) {
            ll_gather4(qp, ep8() + 5, w);
            const float q = ((hif(w[0]) + hif(w[1])) + (hif(w[2]) + hif(w[3]))) * rstd + qc;
            const uint32_t qq = bf2_mul(pack_bf(q, q), 0x3f807180u);
            sts16(qa, SM_VEC, qq); sts16(qa, SM_QU, qq >> 16);
            sts32_if(!(fabsf(q) < 1048576.f), 0, SM_BIG, 1);
            __syncwarp();
            if (elect()) mbar_arrive(SM_QBAR);
        } else {
            uint4 c = make_uint4(ks[0], ks[1], ks[2], ks[3]);
            if (cta == 0 && tid == 255) g_epoch = (ep8() >> 3) + 1;
#pragma unroll 1
            for (int it = 0; it < SPIN; it++) { if (mbar_test(SM_QBAR, 1)) break; tick(c); }
            ks[0] = c.x; ks[1] = c.y; ks[2] = c.z; ks[3] = c.w;
        }
        issue2(IC<3>{}, ks[0] | ks[4] | ks[8] | ks[12] | ks[16] | ks[20]);
        mbar_wait(SM_QBAR, 1);
        auto load_q = [&](int u, int k) { lds128(qf + 4 * k, u == 0 ? qb0 : (tid & 24) == 8 * u ? (tid & 7) * 48 : SM_ZQ - SM_VEC, SM_VEC + k * 16); };
        load_q(0, 1); load_q(0, 2); load_q(0, 0);
        float D[4][4];
        uint4 vb[NPK + 2][6], v2[6];
        uint32_t xn = 0;
        const uint32_t t1 = __shfl_sync(~0u, lds32(0, SM_T0), 0);
        auto step = [&](auto Q) {
            constexpr int st = Q.value, p = cord(st), s = PL.slot[p], n = PL.ld[st];
            if constexpr (n > 0) {
                if constexpr (st >= NPK) {
                    const uint32_t due = t1 + (P2A + n * P2B);
#pragma unroll 1
                    for (int it = 0; it < 4096; it++) if ((int)(gtime() - due) >= 0) break;
                }
                const uint4 (&u)[6] = vb[st - 1 < NPK ? st - 1 : NPK + ((st - 1) & 1)];
                issue2(IC<n>{}, st > PVNOW ? 0 : u[0].x | u[1].x | u[2].x | u[3].x | u[4].x | u[5].x);
            }
            if constexpr (st == 14) {
#pragma unroll 1
                for (int it = 0; it < 4096; it++) if ((int)(gtime() - t1) >= P2W) break;
                issue2(IC<16>{}, 0);
            }
            if (p == 1) mbar_wait(SM_CBAR + (warp >> 2) * 8, 1);
            else if (p == 0) mbar_wait(warp < 4 ? SM_CBAR + 24 : barw, warp < 4);
            else mbar_wait(barw + s * 8, IC<PL.par[p]>::value);
            load_v(vb[st < NPK ? st : NPK + (st & 1)], slot_u(s), slot_o(s));
        };
        static_for<0, 96>([&](auto I) {
            constexpr int F = I.value, n = F / 6, i = n ? F % 6 : (F + 2) % 6;
            const uint32_t* c = n == 0 ? (i < 2 ? ks + 3 * i : kc + 174 + 3 * i) : n < 6 ? ks + 18 * n - 12 + 3 * i : kc + 18 * (n - 6) + 3 * i;
            const uint32_t hx = c[2] & 0x78787878u, ha = hx * (zero - 1) + c[2], hb = __funnelshift_r(hx, hx, 4);
            if (F < 24 && F % 6 == 0) zero4(D[n]);
            mma(D[n & 3], __byte_perm(c[0], ha, 0x5140), __byte_perm(c[0], ha, 0x7362), __byte_perm(c[1], hb, 0x5140), __byte_perm(c[1], hb, 0x7362), qf[2 * i], qf[2 * i + 1]);
            if constexpr ((n & 3) == 3 && n < 15 && (i & 1)) load_q((n + 1) >> 2, i >> 1);
            static_for<6, 24>([&](auto U) {
                if constexpr (((U.value - 5) * 4 + 2) / 3 - 1 == F) {
                    lds128(ks + 4 * U.value, ksl, SM_KS + U.value * 512);
                    if constexpr (U.value % 6 == 5) { const uint32_t* k = ks + 4 * U.value - 17; issue2(IC<3 + U.value / 6>{}, k[0] | k[4] | k[8] | k[12] | k[16] | k[20]); }
                }
            });
            if constexpr (F == 94) {
                if (warp < 4) { mbar_wait(SM_CBAR + 16, 1); load_v(v2, wqw, slot_o(2)); }
                else {
                    const char* p = reinterpret_cast<const char*>(P.v) + (size_t)(roww + vunit(2) * 256) * (DH * 2) + t * 768 + g * 16;
#pragma unroll
                    for (int k = 0; k < 6; k++)
                        asm volatile("ld.global.nc.v4.u32 {%0,%1,%2,%3}, [%4];" : "=r"(v2[k].x), "=r"(v2[k].y), "=r"(v2[k].z), "=r"(v2[k].w) : "l"(p + k * 128));
                }
                const uint2 x = lds64(0, SM_XN);
                xn = x.y ? XCAP + 1 : x.x;
                sts128(prow + lane * 16, SM_PART + 256, 0, 0, 0, 0);
                __syncwarp();
#pragma unroll 1
                for (uint32_t idx = lane; idx < (xn > XCAP ? 0 : xn); idx += 32) {
                    const uint32_t m = lds32(idx * 4, SM_XM);
                    if ((m >> 21) == warp) {
                        const uint4 r = lds128(idx * 16, SM_XR);
                        const uint32_t qo = ((m >> 16) & 3) * 48 + (m & 255);
                        const uint2 a = lds64(qo, SM_QU), b = lds64(qo, SM_QU + 192);
                        const float s = ((bf_lo(r.x) * bf_lo(a.x) + bf_hi(r.x) * bf_hi(a.x)) + (bf_lo(r.y) * bf_lo(b.x) + bf_hi(r.y) * bf_hi(b.x))) +
                                        ((bf_lo(r.z) * bf_lo(a.y) + bf_hi(r.z) * bf_hi(a.y)) + (bf_lo(r.w) * bf_lo(b.y) + bf_hi(r.w) * bf_hi(b.y)));
                        asm volatile("red.relaxed.cta.shared.add.f32 [%0], %1;" :: "r"(SM_PART + 256 + prow + ((m >> 18) & 7) * 64 + ((m >> 8) & 15) * 4), "f"(s) : "memory");
                    }
                }
                __syncwarp();
            }
            if constexpr (F == PK0 - 2) { refresh(); lds128(kc + 8, prow + lane * 16, SM_PART + 256); }
            static_for<0, NPK>([&](auto Q) { if constexpr (F == (Q.value ? PK1 + (Q.value - 1) * PKD : PK0)) step(Q); });
        });
        float S[4];
        {
            const uint32_t shp = lds32(tid * 4, SM_SH);
            const uint4 cr = lds128(prow + lane * 16, SM_PART + 256);
            const uint32_t c[4] = {cr.x, cr.y, cr.z, cr.w};
#pragma unroll
            for (int j = 0; j < 4; j++) S[j] = (D[j][0] + D[j][3]) * __uint_as_float((((shp >> (8 * j)) & 255) + 27) << 23) + __uint_as_float(c[j]);
        }
        if (xn > XCAP) {
#pragma unroll
            for (int k = 0; k < 3; k++) lds128(qf + 4 * k, (lane & 7) * 48, SM_QU + k * 16);
            const char* kp = reinterpret_cast<const char*>(P.k) + (size_t)(roww + g) * (DH * 2) + t * 32;
#pragma unroll 1
            for (int e = 6; e < 22; e++, kp += 256 * DH * 2) {
                uint4 v[6];
#pragma unroll
                for (int i = 0; i < 6; i++) v[i] = ldg128(kp + (i >> 1) * 128 + (i & 1) * 16);
                const float s = score6(v, qf);
                if (t == ((e >> 2) & 3)) { S[0] = S[1]; S[1] = S[2]; S[2] = S[3]; S[3] = s; }
            }
            if (t == 1) { const float a = S[0], b = S[1]; S[0] = S[2]; S[1] = S[3]; S[2] = a; S[3] = b; }
        }
        softmax(IC<1>{}, S);
        auto p_of = [&](int st) { return lds32(ad(t * 4, prow), SM_PART + 256 + ((vunit(cord(st)) + 6) & 15) * 16); };
        auto pv_at = [&](auto Q) { constexpr int st = Q.value; pv(vb[st < NPK ? st : NPK + (st & 1)], p_of(st)); };
        static_for<NPK, 15>([&](auto Q) {
            constexpr int st = Q.value;
            if constexpr (st == HWAT) head_look();
            if constexpr (st == HWC) head_weight(IC<1>{});
            if constexpr (st == PREP1) { tail_prep1(IC<1>{}); tail_prep2(IC<1>{}); red_addr(IC<1>{}); load_u(z, warp * WOU, SM_RING + 16 * WOU); }
            if constexpr (st == PREP2) mlp_prep(IC<1>{});
            uint32_t pp;
            if constexpr (st >= PVNOW) pp = pin(p_of(st));
            step(Q);
            if constexpr (st - NPK < NPK) pv_at(IC<st - NPK>{});
            if constexpr (st > NPK && st <= PVNOW) pv_at(IC<st - 1>{});
            if constexpr (st == PV2) pv(v2, lds32(ad(t * 4, prow), SM_PART + 256 + ((vunit(2) + 6) & 15) * 16));
            if constexpr (st >= PVNOW) pv(vb[NPK + (st & 1)], pp);
        });
    }
    tail(IC<1>{});
    if (!zero) return;
    }
    tid = threadIdx.x;
    derive();
    xp = make_uint2(0, 0);
    if (tid < 160) xp = *reinterpret_cast<const uint2*>(P.x + 4 * c4);
    else if (tid == 192) xp.x = *(volatile unsigned*)&g_epoch;
    else if (tid >= 224 && tid < 240 && mlp) xp.x = reinterpret_cast<const unsigned short*>(P.b1)[hu + lane];
    __syncwarp();
    if (elect()) {
#pragma unroll
        for (int i = 0; i < 7; i++) mbar_init(barw + i * 8, 1);
        if (warp < 4) mbar_arrive(barw);
        mbar_init(SM_CBAR + warp * 8, 1); mbar_init(SM_CBAR + 64 + warp * 8, 1);
        if (warp == 0) { mbar_init(SM_QBAR, 6); mbar_init(SM_BAR + 56, 8); }
        asm volatile("fence.mbarrier_init.release.cluster;" ::: "memory");
        sts64(warp * 8, SM_CNT, 0, 0);
        sts64(warp * 8, SM_ZQ, 0, 0);
    }
#pragma unroll
    for (int i = 12; i < 192; i++) asm volatile("mov.b32 %0, 0;" : "=r"(kc[i]));
    __syncwarp();
    if (warp < 3) { wait_due(warp, 0); if (elect()) issue_kv(warp, warp + 1, warp); }
    else mbar_wait(barw + 56, 0);
    if (tid == 192) sts32(0, SM_EPOCH, xp.x * 8);
    if (tid >= 224 && tid < 240) sts32(lane * 4, SM_B1, xp.x << 16);
    __syncthreads();
    if ((warp == 3 || warp == 4) && elect()) issue_kv(warp, warp == 4 ? 0 : 4, warp);

    load_wq();
    q_stage(IC<0>{});
    {
        int it = (warp >> 2) + 5, slot = (warp >> 2) + 1, bar = warp >> 2, par = 0;
        auto refill = [&](bool kv) {
            uint32_t old;
            asm volatile("{\n.reg .pred p;\nelect.sync _|p, 0xffffffff;\nmov.u32 %0, 0;\n@p atom.relaxed.cta.shared.inc.u32 %0, [%1], 3;\n}" : "=r"(old) : "r"(SM_CNT + slot * 8) : "memory");
            if (__any_sync(~0u, old == 3)) {
                if (!kv && it >= 64) {
#pragma unroll 1
                    for (int k = 0; k < SPIN; k++) {
                        int f; asm volatile("ld.volatile.shared.u32 %0, [%1];" : "=r"(f) : "r"(SM_CNT + 4) : "memory");
                        if (f >= slot) break;
                    }
                    sts32(0, SM_CNT + 4, slot + 1);
                    if (elect()) issue_wo(slot);
                } else {
                    wait_due(it, 0);
                    if (elect()) issue_kv(it, slot, bar < 5 ? bar + 5 : bar - 5);
                }
                __syncwarp();
            }
        };
        auto advance = [&]() { it += 2; slot += 2; if (slot >= 5) slot -= 5; bar += 2; if (bar >= 10) { bar -= 10; par ^= 1; } };
        {
            uint32_t offK[3], qf[12];
#pragma unroll
            for (int j = 0; j < 3; j++) offK[j] = pin(((tid >> 5) & 3) * SUB + 3 * g * 128 + (((2 * t) ^ ((3 * g + j) & 7)) << 4));
#pragma unroll
            for (int i = 0; i < 12; i++) qf[i] = kc[i] = 0;
            const uint32_t ksl = pin(ksw + lane * 16), sca = pin(prow + g * 64);
            int n0 = 0;
#pragma unroll 1
            for (int e = 0; e < 16; e++) {
                mbar_wait(SM_CBAR + bar * 8, par);
                uint4 v[6];
#pragma unroll
                for (int i = 0; i < 6; i++) v[i] = lds128(ad(offK[i >> 1] ^ ((i & 1) * 16), slot * HT), SM_RING + (i >> 1) * 128);
                refill(true);
                advance();
                if ((0xc20 | ((2 << NP) - 1)) >> e & 1) {
                    refresh();
                    static_for<0, NP>([&](auto E) {
                        if (e == E.value) {
#pragma unroll
                            for (int i = 0; i < 6; i++) {
                                uint32_t* k = kc + 90 + 24 * E.value + 4 * i;
                                asm volatile("mov.b32 %0, %4; mov.b32 %1, %5; mov.b32 %2, %6; mov.b32 %3, %7;" : "=r"(k[0]), "=r"(k[1]), "=r"(k[2]), "=r"(k[3]) : "r"(v[i].x), "r"(v[i].y), "r"(v[i].z), "r"(v[i].w));
                            }
                            if (E.value == NP - 2 && warp < 6) {
#pragma unroll
                                for (int i = 0; i < 2; i++)
                                    asm volatile("cp.async.cg.shared.global [%0], [%1], 16;" :: "r"(ksl + SM_KS + 10240 + i * 512),
                                                 "l"(&g_ll[(cta & ~3) + 2 * i + (lane >> 4)][warp * 32 + (lane & 15) * 2]) : "memory");
                            }
                            if (E.value == NP - 1 && warp < 6) {
                                asm volatile("cp.async.wait_all;" ::: "memory");
                                __syncwarp();
                                const uint32_t a = ksw + lane * 8;
                                u64 w[4] = {lds_u64(a, SM_KS + 10240), lds_u64(a, SM_KS + 10496), lds_u64(a, SM_KS + 10752), lds_u64(a, SM_KS + 11008)};
                                ll_gather4(&g_ll[cta & ~3][tid], ep8() + 1, w);
                                const float cs = (lof(w[0] & ~255ull) + lof(w[1] & ~255ull)) + (lof(w[2] & ~255ull) + lof(w[3] & ~255ull));
                                float q = (hif(w[0]) + hif(w[1])) + (hif(w[2]) + hif(w[3]));
                                stsf(tid * 4, SM_CS, cs);
                                float mean, rstd, msq;
                                ln_final(mean, rstd, msq);
                                stsf(0, SM_FXS, fx_scale(msq));
                                q = (q - mean * cs) * rstd;
                                sts16(q_addr(), SM_QU, pack_bf(q, q));
                                __syncwarp();
                                if (elect()) mbar_arrive(SM_QBAR);
#pragma unroll
                                for (int i = 0; i < 12; i++) asm volatile("mov.b32 %0, 0;" : "=r"(kc[i]));
                            }
                        }
                    });
                    if (e == NP) {
                        mbar_wait(SM_QBAR, 0);
#pragma unroll
                        for (int k = 0; k < 3; k++) lds128(qf + 4 * k, (lane & 7) * 48, SM_QU + k * 16);
                        static_for<0, NP>([&](auto E) {
                            uint4 r[6];
#pragma unroll
                            for (int i = 0; i < 6; i++) { const uint32_t* k = kc + 90 + 24 * E.value + 4 * i; r[i] = make_uint4(k[0], k[1], k[2], k[3]); }
                            stsf(sca, SM_PART + 256 + (E.value + 6) * 4, score6(r, qf));
                        });
#pragma unroll
                        for (int i = 0; i < 24; i++) asm volatile("mov.b32 %0, 0;" : "=r"(kc[i]));
                    } else if (e == 5) {
#pragma unroll
                        for (int k = 0; k < 22; k++) lds128(kc + 4 * k, ksl, SM_KS + k * 512);
                        lds64(kc + 88, ksl, SM_KS + 22 * 512);
                        n0 = 0;
                    } else if (e == 10) {
#pragma unroll
                        for (int k = 0; k < 22; k++)
                            asm volatile("ld.shared.v4.b32 {%0,%1,%2,%3}, [%4];" : "=r"(kc[90 + 4 * k]), "=r"(kc[91 + 4 * k]), "=r"(kc[92 + 4 * k]), "=r"(kc[93 + 4 * k]) : "r"(ad(ksl, SM_KS + k * 512)) : "memory");
                        asm volatile("ld.shared.v2.b32 {%0,%1}, [%2];" : "=r"(kc[178]), "=r"(kc[179]) : "r"(ad(ksl, SM_KS + 22 * 512)) : "memory");
                        n0 = 0;
                    } else if (e == 11) {
                        lds64(kc + 180, ksl, SM_KS + 520); lds128(kc + 182, ksl, SM_KS + 1024); lds128(kc + 186, ksl, SM_KS + 1536); lds64(kc + 190, ksl, SM_KS + 2048);
                        n0 = 3;
                    }
                }
                const int n = (e + 6) & 15;
                stsf(ad(sca, n * 4), SM_PART + 256, score6(v, qf));
                uint32_t m = bf2_amax(bf2_amax(v[0].x, v[0].y), bf2_amax(v[0].z, v[0].w)), mn = bf2_amin(bf2_amin(v[0].x, v[0].y), bf2_amin(v[0].z, v[0].w));
#pragma unroll
                for (int i = 1; i < 6; i++) m = bf2_amax(m, bf2_amax(bf2_amax(v[i].x, v[i].y), bf2_amax(v[i].z, v[i].w)));
                m = max(m & 0x7fff, (m >> 16) & 0x7fff);
                m = max(m, __shfl_xor_sync(~0u, m, 1)); m = max(m, __shfl_xor_sync(~0u, m, 2));
#pragma unroll
                for (int i = 1; i < 6; i++) mn = bf2_amin(mn, bf2_amin(bf2_amin(v[i].x, v[i].y), bf2_amin(v[i].z, v[i].w)));
                mn = min(mn & 0x7fff, (mn >> 16) & 0x7fff);
                const int sh = min(max((int)(m >> 7) - 15, 0), 126);
                asm volatile("st.shared.u8 [%0], %1;" :: "r"(ad(ad((tid >> 2) * 16, n), SM_SH)), "r"(sh) : "memory");
                const uint32_t dn = (127 - sh) * 0x00800080u;
                if (__any_sync(~0u, (int)(mn >> 7) <= sh || m >= (142 << 7))) {
                    if (m >= (142 << 7)) sts32(0, SM_BIG, 1);
                    const uint32_t up = (127 + 256 + sh) * 0x00800080u;
#pragma unroll
                    for (int i = 0; i < 6; i++) {
                        const uint32_t r0 = bf2_fma(bf2_mul(v[i].x, dn), up, v[i].x), r1 = bf2_fma(bf2_mul(v[i].y, dn), up, v[i].y);
                        const uint32_t r2 = bf2_fma(bf2_mul(v[i].z, dn), up, v[i].z), r3 = bf2_fma(bf2_mul(v[i].w, dn), up, v[i].w);
                        asm volatile("{\n.reg .pred p;\n.reg .u32 x, a;\nsetp.ne.u32 p, %0, 0;\nmov.u32 x, %7;\n@p atom.relaxed.cta.shared.inc.u32 x, [%6], 0x7fffffff;\n"
                                     "setp.lt.u32 p, x, %7;\nmad.lo.u32 a, x, 16, %8;\n@p st.shared.v4.u32 [a], {%1,%2,%3,%4};\n"
                                     "mad.lo.u32 a, x, 4, %9;\n@p st.shared.u32 [a], %5;\n}"
                                     :: "r"(r0 | r1 | r2 | r3), "r"(r0), "r"(r1), "r"(r2), "r"(r3), "r"(tid << 16 | n << 8 | i * 8), "r"(SM_XN), "n"(XCAP), "n"(SM_XR), "n"(SM_XM) : "memory");
                    }
                }
                const uint32_t ae = (n0 >> 1) * 512 + (n0 & 1) * 8, ao = ((n0 + 1) >> 1) * 512 + (~n0 & 1) * 8;
                uint32_t o[18];
#pragma unroll
                for (int i = 0; i < 6; i++) {
                    const uint32_t y0 = bf2_mulv(v[i].x, dn), y1 = bf2_mulv(v[i].y, dn), y2 = bf2_mulv(v[i].z, dn), y3 = bf2_mulv(v[i].w, dn);
                    o[3 * i] = __byte_perm(y0, y1, 0x6420); o[3 * i + 1] = __byte_perm(y2, y3, 0x6420);
                    const uint32_t hb = __byte_perm(y2, y3, 0x7531);
                    o[3 * i + 2] = __byte_perm(y0, y1, 0x7531) | __funnelshift_l(hb, hb, 4);
                    if (i & 1) {
#pragma unroll
                        for (int k = 3 * (i >> 1); k < 3 * (i >> 1) + 3; k++) sts64(ad(ksl, (k & 1) ? ao : ae), SM_KS + (k >> 1) * 512, o[2 * k], o[2 * k + 1]);
                    }
                }
                n0 += 9;
            }
            fence_async();
        }
        refresh();
        {
            const uint4 sc = lds128(prow + lane * 16, SM_PART + 256);
            const float S[4] = {__uint_as_float(sc.x), __uint_as_float(sc.y), __uint_as_float(sc.z), __uint_as_float(sc.w)};
            softmax(IC<0>{}, S);
        }
        fw = 0.f;
#pragma unroll 1
        for (int e = 0; e < 16; e++) {
            if ((1 << (PUBAT - 3) | 1 << PUBAT | 1 << ZCHK) >> e & 1) {
                if (e == PUBAT - 3) head_look();
                else if (e == PUBAT) {
                    head_weight(IC<0>{});
                    if (tid < 196) st_rlx(&g_ll[cta][tid + (tid >> 6 == 3) * 8], 0ull);
                } else if (warp == 7) {
                    if ((bx & 15) == 0 && elect()) bulk_pf(P.b2, D_MODEL * 2, POL_NORMAL);
#pragma unroll 1
                    for (int k = 0; k < SPIN; k++) {
                        uint32_t v; asm volatile("ld.acquire.gpu.global.u32 %0, [%1];" : "=r"(v) : "l"(&g_zflag) : "memory");
                        if (__all_sync(~0u, v * 8 == ep8() + 8)) break;
                    }
                }
                __syncwarp();
            }
            const uint32_t pp = lds32(ad(t * 4, prow + ((e + 6) & 15) * 16), SM_PART + 256);
            mbar_wait(SM_CBAR + bar * 8, par);
            uint4 v[6];
            load_v(v, (warp & 3) * SUB + slot * HT, SM_RING);
            if (e < 15) refill(false);
            advance();
            pv(v, pp);
        }
    }
    tail_prep1(IC<0>{});
    __syncwarp();
    }
}

typedef CUresult (*EncodeFn)(CUtensorMap*, CUtensorMapDataType, cuuint32_t, void*, const cuuint64_t*, const cuuint64_t*, const cuuint32_t*,
                             const cuuint32_t*, CUtensorMapInterleave, CUtensorMapSwizzle, CUtensorMapL2promotion, CUtensorMapFloatOOBfill);

}

extern "C" void kernel_launch(void* const* d_in, const int* in_sizes, int n_in, void* d_out, int out_size) {
    (void)in_sizes; (void)n_in; (void)out_size;
    static EncodeFn enc = nullptr;
    if (!enc) {
        void* fn = nullptr;
        cudaDriverEntryPointQueryResult qr;
        cudaGetDriverEntryPoint("cuTensorMapEncodeTiled", &fn, cudaEnableDefault, &qr);
        enc = (EncodeFn)fn;
        cudaFuncSetAttribute(fused_kernel, cudaFuncAttributeMaxDynamicSharedMemorySize, SM_TOTAL);
    }
    Params P;
    const cuuint32_t ones[3] = {1, 1, 1};
    for (int m = TM_K; m <= TM_V8; m++) {
        const cuuint64_t dim[3] = {64, 3, (cuuint64_t)NHEAD * SK}, str[2] = {128, DH * 2};
        const cuuint32_t box[3] = {m == TM_VP ? 8u : 64u, 3, m == TM_V8 ? 8u : 32u};
        enc(&P.tm[m], CU_TENSOR_MAP_DATA_TYPE_BFLOAT16, 3, d_in[m == TM_K ? 1 : 2], dim, str, box, ones, CU_TENSOR_MAP_INTERLEAVE_NONE,
            m == TM_VP ? CU_TENSOR_MAP_SWIZZLE_NONE : CU_TENSOR_MAP_SWIZZLE_128B, CU_TENSOR_MAP_L2_PROMOTION_NONE, CU_TENSOR_MAP_FLOAT_OOB_FILL_NONE);
    }
    {
        const cuuint64_t dim[3] = {64, NHEAD * 3, D_MODEL}, str[2] = {128, NHEAD * DH * 2};
        const cuuint32_t box[3] = {64, 3, 32};
        enc(&P.tm[TM_WQ], CU_TENSOR_MAP_DATA_TYPE_BFLOAT16, 3, d_in[3], dim, str, box, ones, CU_TENSOR_MAP_INTERLEAVE_NONE,
            CU_TENSOR_MAP_SWIZZLE_128B, CU_TENSOR_MAP_L2_PROMOTION_NONE, CU_TENSOR_MAP_FLOAT_OOB_FILL_NONE);
    }
    {
        const cuuint64_t dim[2] = {DFF, D_MODEL}, str[1] = {DFF * 2};
        const cuuint32_t box[2] = {16, 128};
        enc(&P.tm[TM_W1], CU_TENSOR_MAP_DATA_TYPE_BFLOAT16, 2, d_in[6], dim, str, box, ones, CU_TENSOR_MAP_INTERLEAVE_NONE,
            CU_TENSOR_MAP_SWIZZLE_32B, CU_TENSOR_MAP_L2_PROMOTION_L2_128B, CU_TENSOR_MAP_FLOAT_OOB_FILL_NONE);
    }
    {
        const cuuint64_t dim[3] = {32, 20, NHEAD * DH}, str[2] = {64, D_MODEL * 2};
        const cuuint32_t box[3] = {32, 5, 16};
        enc(&P.tm[TM_WO], CU_TENSOR_MAP_DATA_TYPE_BFLOAT16, 3, d_in[4], dim, str, box, ones, CU_TENSOR_MAP_INTERLEAVE_NONE,
            CU_TENSOR_MAP_SWIZZLE_64B, CU_TENSOR_MAP_L2_PROMOTION_L2_128B, CU_TENSOR_MAP_FLOAT_OOB_FILL_NONE);
    }
    {
        const cuuint64_t dim[4] = {32, 20, 24, NHEAD * 8}, str[3] = {64, D_MODEL * 2, 24 * D_MODEL * 2};
        const cuuint32_t box[4] = {32, 5, 8, 4}, ones4[4] = {1, 1, 1, 1};
        enc(&P.tm[TM_WO4], CU_TENSOR_MAP_DATA_TYPE_BFLOAT16, 4, d_in[4], dim, str, box, ones4, CU_TENSOR_MAP_INTERLEAVE_NONE,
            CU_TENSOR_MAP_SWIZZLE_64B, CU_TENSOR_MAP_L2_PROMOTION_L2_128B, CU_TENSOR_MAP_FLOAT_OOB_FILL_NONE);
        const cuuint32_t thin[4] = {8, 5, 8, 4};
        enc(&P.tm[TM_WOP], CU_TENSOR_MAP_DATA_TYPE_BFLOAT16, 4, d_in[4], dim, str, thin, ones4, CU_TENSOR_MAP_INTERLEAVE_NONE,
            CU_TENSOR_MAP_SWIZZLE_NONE, CU_TENSOR_MAP_L2_PROMOTION_NONE, CU_TENSOR_MAP_FLOAT_OOB_FILL_NONE);
    }
    {
        const cuuint64_t dim[3] = {64, 10, DFF}, str[2] = {128, D_MODEL * 2};
        const cuuint32_t box[3] = {64, 10, 16};
        enc(&P.tm[TM_W2], CU_TENSOR_MAP_DATA_TYPE_BFLOAT16, 3, d_in[8], dim, str, box, ones, CU_TENSOR_MAP_INTERLEAVE_NONE,
            CU_TENSOR_MAP_SWIZZLE_128B, CU_TENSOR_MAP_L2_PROMOTION_NONE, CU_TENSOR_MAP_FLOAT_OOB_FILL_NONE);
    }
    P.x = (const __nv_bfloat16*)d_in[0];
    P.k = (const __nv_bfloat16*)d_in[1];
    P.v = (const __nv_bfloat16*)d_in[2];
    P.b1 = (const __nv_bfloat16*)d_in[7];
    P.b2 = (const __nv_bfloat16*)d_in[9];
    P.out = (__nv_bfloat16*)d_out;
    fused_kernel<<<NCTA + 1, NTHR, SM_TOTAL, cudaStreamPerThread>>>(P);
}
```

```cpp
#include <cuda_runtime.h>
#include <cuda_bf16.h>
#include <cuda.h>
#include <stdint.h>

#define DI __device__ __forceinline__

namespace {

constexpr int D_MODEL = 640, NHEAD = 32, SK = 32768, DH = 192, WIN = 4096, DFF = 1536;
constexpr int NCTA = 128, NTHR = 256;
constexpr int SUB = 8 * DH * 2;
constexpr int HT = 4 * SUB;
constexpr int WOU = 8 * 320;
constexpr int XCAP = 48;
constexpr int SM_RING = 1024;
constexpr int SM_W2 = SM_RING + 8 * WOU;
constexpr int SM_WQ = SM_RING + 5 * HT;
constexpr int SM_KS = SM_WQ + 5 * HT;
constexpr int SM_PART = SM_KS + 8 * HT;
constexpr int SM_BAR = SM_PART + 6144;
constexpr int SM_VEC = SM_BAR + 512;
constexpr int SM_QU = SM_VEC + 384;
constexpr int SM_ZQ = SM_QU + 384;
constexpr int SM_CS = SM_ZQ + 64;
constexpr int SM_XR = SM_CS + 768;
constexpr int SM_XM = SM_XR + XCAP * 16;
constexpr int SM_SH = SM_XM + XCAP * 4;
constexpr int SM_C1 = SM_SH + 1024;
constexpr int SM_B1 = SM_C1 + 320;
constexpr int SM_STAT = SM_B1 + 128;
constexpr int SM_QBAR = SM_STAT + 40;
constexpr int SM_CBAR = SM_QBAR + 8;
constexpr int SM_CNT = SM_CBAR + 128;
constexpr int SM_XN = SM_CNT + 56;
constexpr int SM_BIG = SM_XN + 4;
constexpr int SM_EPOCH = SM_BIG + 4;
constexpr int SM_FXS = SM_EPOCH + 4;
constexpr int SM_T0 = SM_FXS + 4;
constexpr int SM_JUNK = SM_T0 + 4;
constexpr int SM_TOTAL = 232448;
static_assert(SM_JUNK + 4 <= SM_RING + SM_TOTAL, "smem");

constexpr int SPIN = 1 << 20;
enum { TM_WQ = 0, TM_K = 1, TM_V = 2, TM_VP = 3, TM_V8 = 4, TM_WO = 5, TM_W1 = 6, TM_WO4 = 7, TM_W2 = 8, TM_WOP = 9 };
constexpr uint32_t POL_NORMAL = 0x16F00000u, POL_FIRST = 0x12F00000u;

constexpr int PACE = 485, PACE0 = 1700, WOPACE = 403, W1D = 100, W1G = 150, HZD = 9500;
constexpr int NP = 3, PUBAT = 8, ZCHK = 14;
constexpr int ODELAY = 250, AR1D = 600, AR1DN = 1000, AR2D = 600, S6D = 900, S6G = 100, I0D = 300, KAD = 900;
constexpr unsigned long long VORD = 0x56784932a1b0cdefull;
constexpr int ISS = 0xf9e, NPK = 4, PK0 = 34, PK1 = 52, PKD = 21, P2A = -700, P2B = 400, P2W = 5700;
constexpr int PREP1 = 8, PREP2 = 9, PV2 = 9, HWAT = 8, PVNOW = 12, HWC = 11;
constexpr uint32_t FX2_MASK = 0xfff00000u;

struct Plan { int slot[17], par[17], ld[15]; bool ok; };
__host__ __device__ constexpr int cord(int s) { return s < 2 ? s : s + 1; }
constexpr Plan make_plan() {
    Plan s{};
    int phase[7] = {}, freeat[7] = {}, it = 7;
    for (int p = 0; p < 7; p++) { s.slot[p] = p; phase[p] = p != 1; freeat[p] = -1; }
    s.ok = true;
    for (int st = 0; st < 15; st++) {
        if (ISS >> st & 1) {
            int best = -1;
            for (int c = 0; c < 7; c++) if (freeat[c] >= 0 && (c < 5 || it < 13) && (best < 0 || freeat[c] < freeat[best])) best = c;
            if (best < 0 || it > 15) { s.ok = false; return s; }
            s.slot[it] = best; freeat[best] = -1;
            s.par[it] = phase[best]++ & 1;
            s.ld[st] = it++;
        }
        if (cord(st) >= it || (st >= 12 && s.slot[cord(st)] >= 5)) s.ok = false;
        freeat[s.slot[cord(st)]] = st;
    }
    s.slot[16] = 5; s.par[16] = phase[5] & 1;
    return s;
}
constexpr Plan PL = make_plan();
static_assert(PL.ok && PK0 < 40, "bad pass-2 plan");
__host__ __device__ constexpr int vunit(int p) { return (int)(VORD >> (4 * p) & 15); }

template <int I> struct IC { static constexpr int value = I; };
template <int A, int B, class F> DI void static_for(F&& f) {
    if constexpr (A < B) { f(IC<A>{}); static_for<A + 1, B>(f); }
}

struct Params {
    CUtensorMap tm[10];
    const __nv_bfloat16 *x, *b1, *b2, *k, *v;
    __nv_bfloat16* out;
};

typedef unsigned long long u64;
constexpr int ACC_PITCH = 256;
constexpr int ACC_BYTES = 80 * ACC_PITCH;
__device__ __align__(1024) unsigned char g_acc[4 * ACC_BYTES];
__device__ __align__(8192) u64 g_ll[NCTA][256];
__device__ unsigned g_epoch;
__device__ __align__(128) unsigned g_zflag;

DI void mbar_wait(uint32_t bar, uint32_t parity) {
    asm volatile("{\n.reg .pred p, q;\n.reg .u32 n;\nmov.u32 n, 0;\n"
                 "LOOP:\nmbarrier.try_wait.parity.shared::cta.b64 p, [%0], %1;\n"
                 "add.u32 n, n, 1;\nsetp.lt.and.u32 q, n, 0x100000, !p;\n@q bra.uni LOOP;\n}"
                 :: "r"(bar), "r"(parity) : "memory");
}
DI bool mbar_test(uint32_t bar, uint32_t parity) {
    uint32_t done;
    asm volatile("{\n.reg .pred p;\nmbarrier.test_wait.parity.shared::cta.b64 p, [%1], %2;\nselp.u32 %0, 1, 0, p;\n}" : "=r"(done) : "r"(bar), "r"(parity) : "memory");
    return __any_sync(~0u, done);
}
DI bool elect() {
    uint32_t r;
    asm volatile("{\n.reg .pred p;\nelect.sync _|p, 0xffffffff;\nselp.u32 %0, 1, 0, p;\n}" : "=r"(r));
    return r != 0;
}
DI void mbar_init(uint32_t bar, uint32_t n) { asm volatile("mbarrier.init.shared::cta.b64 [%0], %1;" :: "r"(bar), "r"(n) : "memory"); }
DI void mbar_arrive(uint32_t bar) { asm volatile("mbarrier.arrive.shared::cta.b64 _, [%0];" :: "r"(bar) : "memory"); }
DI void mbar_expect(uint32_t bar, uint32_t bytes) {
    asm volatile("mbarrier.arrive.expect_tx.shared::cta.b64 _, [%0], %1;" :: "r"(bar), "r"(bytes) : "memory");
}
DI void fence_gpu() { asm volatile("fence.acq_rel.gpu;" ::: "memory"); }
DI void fence_async() { asm volatile("fence.proxy.async.shared::cta;" ::: "memory"); }
DI uint32_t ad(uint32_t a, uint32_t o) { uint32_t r; asm("add.u32 %0, %1, %2;" : "=r"(r) : "r"(a), "r"(o)); return r; }
DI uint4 lds128(uint32_t a, int o) {
    uint4 v; asm volatile("ld.shared.v4.u32 {%0,%1,%2,%3}, [%4];" : "=r"(v.x), "=r"(v.y), "=r"(v.z), "=r"(v.w) : "r"(ad(a, o)) : "memory"); return v;
}
DI void lds128(uint32_t* v, uint32_t a, int o) {
    asm volatile("ld.shared.v4.u32 {%0,%1,%2,%3}, [%4];" : "=r"(v[0]), "=r"(v[1]), "=r"(v[2]), "=r"(v[3]) : "r"(ad(a, o)) : "memory");
}
DI void lds64(uint32_t* v, uint32_t a, int o) { asm volatile("ld.shared.v2.u32 {%0,%1}, [%2];" : "=r"(v[0]), "=r"(v[1]) : "r"(ad(a, o)) : "memory"); }
DI uint4 ldsm_t(uint32_t a, int o) {
    uint4 v; asm volatile("ldmatrix.sync.aligned.m8n8.x4.trans.shared.b16 {%0,%1,%2,%3}, [%4];" : "=r"(v.x), "=r"(v.y), "=r"(v.z), "=r"(v.w) : "r"(ad(a, o)) : "memory"); return v;
}
DI uint2 lds64(uint32_t a, int o) { uint2 v; asm volatile("ld.shared.v2.u32 {%0,%1}, [%2];" : "=r"(v.x), "=r"(v.y) : "r"(ad(a, o)) : "memory"); return v; }
DI float2 lds64f(uint32_t a, int o) { const uint2 v = lds64(a, o); return make_float2(__uint_as_float(v.x), __uint_as_float(v.y)); }
DI uint32_t lds32(uint32_t a, int o) { uint32_t v; asm volatile("ld.shared.u32 %0, [%1];" : "=r"(v) : "r"(ad(a, o)) : "memory"); return v; }
DI float ldsf(uint32_t a, int o) { return __uint_as_float(lds32(a, o)); }
DI void sts32(uint32_t a, int o, uint32_t v) { asm volatile("st.shared.u32 [%0], %1;" :: "r"(ad(a, o)), "r"(v) : "memory"); }
DI void stsf(uint32_t a, int o, float v) { sts32(a, o, __float_as_uint(v)); }
DI void sts16(uint32_t a, int o, uint32_t v) { asm volatile("st.shared.u16 [%0], %1;" :: "r"(ad(a, o)), "h"((uint16_t)v) : "memory"); }
DI void sts64(uint32_t a, int o, uint32_t x, uint32_t y) { asm volatile("st.shared.v2.u32 [%0], {%1,%2};" :: "r"(ad(a, o)), "r"(x), "r"(y) : "memory"); }
DI void sts128(uint32_t a, int o, uint32_t x, uint32_t y, uint32_t z, uint32_t w) {
    asm volatile("st.shared.v4.u32 [%0], {%1,%2,%3,%4};" :: "r"(ad(a, o)), "r"(x), "r"(y), "r"(z), "r"(w) : "memory");
}
DI void sts128f_if(bool p, uint32_t a, int o, float x, float y, float z, float w) {
    asm volatile("{\n.reg .pred p;\nsetp.ne.u32 p, %5, 0;\n@p st.shared.v4.f32 [%0], {%1,%2,%3,%4};\n}" :: "r"(ad(a, o)), "f"(x), "f"(y), "f"(z), "f"(w), "r"((int)p) : "memory");
}
DI void sts32_if(bool p, uint32_t a, int o, uint32_t v) {
    asm volatile("{\n.reg .pred p;\nsetp.ne.u32 p, %2, 0;\n@p st.shared.u32 [%0], %1;\n}" :: "r"(ad(a, o)), "r"(v), "r"((int)p) : "memory");
}
DI uint32_t atoms_inc(uint32_t a, uint32_t lim) {
    uint32_t old; asm volatile("atom.relaxed.cta.shared.inc.u32 %0, [%1], %2;" : "=r"(old) : "r"(a), "r"(lim) : "memory"); return old;
}
DI void mma(float (&c)[4], uint32_t a0, uint32_t a1, uint32_t a2, uint32_t a3, uint32_t b0, uint32_t b1) {
    asm volatile("mma.sync.aligned.m16n8k16.row.col.f32.bf16.bf16.f32 {%0,%1,%2,%3}, {%4,%5,%6,%7}, {%8,%9}, {%0,%1,%2,%3};"
                 : "+f"(c[0]), "+f"(c[1]), "+f"(c[2]), "+f"(c[3]) : "r"(a0), "r"(a1), "r"(a2), "r"(a3), "r"(b0), "r"(b1));
}
DI void mma(float (&c)[4], const uint4& a, uint32_t b0, uint32_t b1) { mma(c, a.x, a.y, a.z, a.w, b0, b1); }
DI void zero4(float (&c)[4]) { c[0] = c[1] = c[2] = c[3] = 0.f; }
DI u64 ld_rlx(const void* p) {
    u64 a; asm volatile("ld.relaxed.gpu.global.u64 %0, [%1];" : "=l"(a) : "l"(p) : "memory"); return a;
}
DI void st_rlx(void* p, u64 a) { asm volatile("st.relaxed.gpu.global.u64 [%0], %1;" :: "l"(p), "l"(a) : "memory"); }
DI uint4 ldg128(const void* p) {
    uint4 v; asm volatile("ld.global.nc.L1::no_allocate.L2::cache_hint.v4.u32 {%0,%1,%2,%3}, [%4], %5;" : "=r"(v.x), "=r"(v.y), "=r"(v.z), "=r"(v.w) : "l"(p), "l"((u64)POL_FIRST << 32)); return v;
}
DI float bf_lo(uint32_t u) { return __uint_as_float(u << 16); }
DI float bf_hi(uint32_t u) { return __uint_as_float(u & 0xffff0000u); }
DI uint32_t pack_bf(float lo, float hi) {
    uint32_t r; asm("cvt.rn.bf16x2.f32 %0, %1, %2;" : "=r"(r) : "f"(hi), "f"(lo)); return r;
}
DI uint32_t pick(uint32_t a, uint32_t sel) { uint32_t r; asm("prmt.b32 %0, %1, 0, %2;" : "=r"(r) : "r"(a), "r"(sel)); return r; }
DI uint32_t bf2_amax(uint32_t a, uint32_t b) { uint32_t r; asm("max.NaN.xorsign.abs.bf16x2 %0, %1, %2;" : "=r"(r) : "r"(a), "r"(b)); return r; }
DI uint32_t bf2_amin(uint32_t a, uint32_t b) { uint32_t r; asm("min.xorsign.abs.bf16x2 %0, %1, %2;" : "=r"(r) : "r"(a), "r"(b)); return r; }
DI uint32_t bf2_mulv(uint32_t a, uint32_t b) { uint32_t r; asm volatile("mul.rn.bf16x2 %0, %2, %1;" : "=r"(r) : "r"(a), "r"(b)); return r; }
DI uint32_t bf2_mul(uint32_t a, uint32_t b) { uint32_t r; asm("mul.rn.bf16x2 %0, %1, %2;" : "=r"(r) : "r"(a), "r"(b)); return r; }
DI uint32_t bf2_fma(uint32_t a, uint32_t b, uint32_t c) { uint32_t r; asm("fma.rn.bf16x2 %0, %1, %2, %3;" : "=r"(r) : "r"(a), "r"(b), "r"(c)); return r; }
DI float ex2(float v) { float r; asm("ex2.approx.ftz.f32 %0, %1;" : "=f"(r) : "f"(v)); return r; }
DI float rcp(float v) { float r; asm("rcp.approx.ftz.f32 %0, %1;" : "=f"(r) : "f"(v)); return r; }
DI float rsq(float v) { float r; asm("rsqrt.approx.ftz.f32 %0, %1;" : "=f"(r) : "f"(v)); return r; }
DI void bar_sync(int id, int n) { asm volatile("bar.sync %0, %1;" :: "r"(id), "r"(n) : "memory"); }
DI uint32_t clk() { uint32_t c; asm volatile("mov.u32 %0, %clock;" : "=r"(c)); return c; }
DI uint32_t gtime() { uint32_t c; asm volatile("mov.u32 %0, %globaltimer_lo;" : "=r"(c)); return c; }
DI uint32_t pin(uint32_t v) { return __shfl_xor_sync(~0u, v, 0); }
DI float pinf(float v) { return __shfl_xor_sync(~0u, v, 0); }
template <class T> DI T* pinp(T* p) { return reinterpret_cast<T*>(__shfl_xor_sync(~0u, (u64)p, 0)); }
DI u64 mk64(uint32_t lo, uint32_t hi) { u64 r; asm("mov.b64 %0, {%1, %2};" : "=l"(r) : "r"(lo), "r"(hi)); return r; }
DI float shx(float v, int o) { return __shfl_xor_sync(~0u, v, o); }

DI u64 fx_pack(float v) {
    u64 r; asm("{\n.reg .u32 a, b;\n.reg .s64 w;\ncvt.rni.s64.f32 w, %1;\nmov.b64 {a, b}, w;\nprmt.b32 a, a, 1, 0x3214;\nmov.b64 %0, {a, b};\n}" : "=l"(r) : "f"(v)); return r;
}
DI float fx_scale(float meansq) {
    const int e = max(((int)(__float_as_uint(meansq) >> 23) - 127) >> 1, -14);
    return __uint_as_float((uint32_t)(127 + 32 - e) << 23);
}
DI float fx_inv(float scale) { return __uint_as_float((254u << 23) - __float_as_uint(scale)); }
DI uint32_t lo32(u64 w) { uint32_t l; asm("mov.b64 {%0, _}, %1;" : "=r"(l) : "l"(w)); return l; }
DI int hi32(u64 w) { int h; asm("mov.b64 {_, %0}, %1;" : "=r"(h) : "l"(w)); return h; }
DI float fx_val(u64 w) { return (float)hi32(w) * 4294967296.f + (float)lo32(w); }
DI void fx_poll(const unsigned char* ap, u64 (&w)[4]) {
    asm volatile("{\n.reg .pred p, q;\n.reg .u32 n, a, b, c, d;\nmov.u32 n, 0;\nLOOP:\n"
                 "ld.relaxed.gpu.global.u64 %0, [%4];\nld.relaxed.gpu.global.u64 %1, [%4+5120];\n"
                 "ld.relaxed.gpu.global.u64 %2, [%4+10240];\nld.relaxed.gpu.global.u64 %3, [%4+15360];\n"
                 "add.u32 n, n, 1;\nsetp.ge.u32 q, n, 0x100000;\n@q bra.uni DONE;\n"
                 "mov.b64 {a, _}, %0;\nmov.b64 {b, _}, %1;\nmov.b64 {c, _}, %2;\nmov.b64 {d, _}, %3;\n"
                 "lop3.b32 a, a, b, c, 0x80;\nlop3.b32 a, a, d, 32, 0x80;\nsetp.eq.u32 p, a, 0;\n"
                 "vote.sync.any.pred p, p, 0xffffffff;\n@p bra.uni LOOP;\nDONE:\n}"
                 : "=l"(w[0]), "=l"(w[1]), "=l"(w[2]), "=l"(w[3]) : "l"(ap) : "memory");
}
constexpr u64 FX2_INIT = 256ull + 32 - 96 * ((1ull << 28) + (1ull << 55)), FX2_NONE = 1ull + (1ull << 28) + (1ull << 55);
constexpr float FX2_MAGIC = 12582912.f + 524288.f;

DI void tma3(uint32_t dst, const CUtensorMap* tm, int c1, int c2, uint32_t bar, uint32_t pol) {
    asm volatile("cp.async.bulk.tensor.3d.shared::cluster.global.mbarrier::complete_tx::bytes.L2::cache_hint [%0], [%1, {%2, %3, %4}], [%5], %6;"
                 :: "r"(dst), "l"(tm), "r"(0), "r"(c1), "r"(c2), "r"(bar), "l"((u64)pol << 32) : "memory");
}
DI void tma3_pf(const CUtensorMap* tm, int c1, int c2, uint32_t pol) {
    asm volatile("cp.async.bulk.prefetch.tensor.3d.L2.global.tile.L2::cache_hint [%0, {%1, %2, %3}], %4;"
                 :: "l"(tm), "r"(0), "r"(c1), "r"(c2), "l"((u64)pol << 32) : "memory");
}
DI void bulk_pf(const void* p, uint32_t bytes, uint32_t pol) {
    asm volatile("cp.async.bulk.prefetch.L2.global.L2::cache_hint [%0], %1, %2;" :: "l"(p), "r"(bytes), "l"((u64)pol << 32) : "memory");
}
DI float warp_max(float v) {
    const int k = __float_as_int(v), m = __reduce_max_sync(~0u, k ^ ((k >> 31) & 0x7fffffff));
    return __int_as_float(m ^ ((m >> 31) & 0x7fffffff));
}
DI u64 ll_pack2(float a, float b, uint32_t tag) { return mk64(__byte_perm(__float_as_uint(a), tag, 0x3214), __float_as_uint(b)); }
DI float lof(u64 w) { return __uint_as_float(lo32(w)); }
DI float hif(u64 w) { return __int_as_float(hi32(w)); }
DI void ll_gather4(const u64* buf, uint32_t tag, u64 (&w)[4]) {
#pragma unroll 1
    for (int it = 0; it < SPIN; it++) {
        if (it) { w[0] = ld_rlx(buf); w[1] = ld_rlx(buf + 256); w[2] = ld_rlx(buf + 512); w[3] = ld_rlx(buf + 768); }
        if (!__any_sync(~0u, (((lo32(w[0]) ^ tag) | (lo32(w[1]) ^ tag)) | ((lo32(w[2]) ^ tag) | (lo32(w[3]) ^ tag))) & 255)) break;
    }
}
DI u64 lds_u64(uint32_t a, int o) { const uint2 v = lds64(a, o); return v.x | (u64)v.y << 32; }
DI float sum8(uint32_t a, int o, int pitch) {
    float s[8];
#pragma unroll
    for (int w = 0; w < 8; w++) s[w] = ldsf(a, o + w * pitch);
    return ((s[0] + s[1]) + (s[2] + s[3])) + ((s[4] + s[5]) + (s[6] + s[7]));
}
DI void ln_final(float& mean, float& rstd, float& msq) {
    float2 v[5];
#pragma unroll
    for (int w = 0; w < 5; w++) v[w] = lds64f(0, SM_STAT + w * 8);
    mean = (((v[0].x + v[1].x) + (v[2].x + v[3].x)) + v[4].x) * (1.f / D_MODEL);
    msq = (((v[0].y + v[1].y) + (v[2].y + v[3].y)) + v[4].y) * (1.f / D_MODEL);
    rstd = rsq(fmaxf(msq - mean * mean, 0.f) + 1e-5f);
}
constexpr float CS = 0.07216878364870322f * 1.4426950408889634f;
constexpr uint32_t ONES = 0x3f803f80u;

__global__ void __launch_bounds__(NTHR, 1) fused_kernel(const __grid_constant__ Params P) {
    extern __shared__ __align__(1024) unsigned char smem[];
    const int warp = __shfl_sync(~0u, threadIdx.x >> 5, 0), bx = blockIdx.x;
    const int cta = (((bx >> 1) & 15) + (bx >> 6) * 16) * 4 + ((bx >> 5) & 1) * 2 + (bx & 1);

    if (bx == NCTA) {
        if ((uint32_t)__cvta_generic_to_shared(smem) != SM_RING) __trap();
        const uint32_t ep = *(volatile unsigned*)&g_epoch;
        if (threadIdx.x == 0) {
#pragma unroll 1
            for (int it = 0; it < SPIN; it++) { if ((lo32(ld_rlx(&g_ll[0][192])) & 255) == ((ep * 8 + 1) & 255)) break; __nanosleep(200); }
            const uint32_t t0 = gtime();
#pragma unroll 1
            for (int it = 0; it < 1024; it++) { if (gtime() - t0 > HZD) break; __nanosleep(100); }
        }
        __syncthreads();
#pragma unroll 1
        for (int i = threadIdx.x; i < 4 * 80 * 8; i += NTHR)
        {
            const u64 v = (i / 640 & 1) && (i & 7) < 2 ? FX2_INIT : 0ull;
            *reinterpret_cast<ulonglong2*>(g_acc + (i >> 3) * ACC_PITCH + (i & 7) * 16) = make_ulonglong2(v, v);
        }
        __threadfence();
        __syncthreads();
        if (threadIdx.x == 0) asm volatile("st.relaxed.gpu.global.u32 [%0], %1;" :: "l"(&g_zflag), "r"(ep + 1) : "memory");
        return;
    }
    const uint32_t barw = SM_BAR + warp * 64;
    if (elect()) {
        if (warp < 3) sts32(0, SM_T0, gtime());
        else {
            mbar_init(barw + 56, 1);
            asm volatile("fence.mbarrier_init.release.cluster;" ::: "memory");
            mbar_expect(barw + 56, HT);
            tma3(SM_WQ - 3 * HT + warp * HT, &P.tm[TM_WQ], (cta >> 2) * 3, (cta & 3) * 160 - 96 + warp * 32, barw + 56, POL_FIRST);
        }
    }
    int tid = threadIdx.x, lane, g, t, c4;
    uint32_t selA, selB, offV0, offV2;
    auto derive = [&]() {
        lane = tid & 31; g = lane >> 2; t = lane & 3;
        c4 = (tid & 0xe1) + 16 * (t >> 1) + 2 * g;
        selA = (g & 2) ? 0x4444u : (g & 1) ? 0x1044u : 0x4410u;
        selB = (g & 2) ? ((g & 1) ? 0x1044u : 0x4410u) : 0x4444u;
        offV0 = (6 * t) * 128 + ((g ^ ((6 * t) & 7)) << 4);
        offV2 = (6 * t) * 128 + ((g ^ ((6 * t + 2) & 7)) << 4);
    };
    auto refresh = [&]() { tid = pin(tid); derive(); };
    auto refresh_late = [&]() { mbar_wait(SM_BAR + 3 * 64 + 56, 0); refresh(); };
    derive();
    const uint32_t zero = bx >> 16;
    const int j40 = (cta & 3) * 40;
    const bool mlp = (cta & 3) != 3;
    const int hu = ((cta >> 2) * 3 + (cta & 3)) * 16;
    uint2 xp = make_uint2(0, 0);
    uint32_t kc[192];
    const int rowc = (cta >> 2) * SK + (SK - WIN) + (cta & 3) * 64;
    const int roww = __shfl_sync(~0u, rowc + warp * 8, 0);
    const CUtensorMap* tmk = reinterpret_cast<const CUtensorMap*>(__shfl_sync(~0u, (u64)&P.tm[0] + (lane >> 5), 0));

    auto wait_due = [&](int i, int extra) {
        const uint32_t due = lds32(0, SM_T0) + PACE0 + extra + i * PACE;
#pragma unroll 1
        for (int it = 0; it < 4096; it++) if ((int)(gtime() - due) >= 0) break;
    };
    auto issue_wo = [&](int k) {
        wait_due(64, k * WOPACE);
        mbar_expect(SM_CBAR + 32 + k * 8, 4 * WOU);
        asm volatile("cp.async.bulk.tensor.4d.shared::cluster.global.mbarrier::complete_tx::bytes.L2::cache_hint [%0], [%1, {%2, %3, %4, %5}], [%6], %7;"
                     :: "r"(SM_RING + k * 4 * WOU), "l"(tmk + TM_WO4), "r"(0), "r"(5 * (cta & 3)), "r"((k >> 1) * 8), "r"((cta >> 2) * 8 + (k & 1) * 4),
                        "r"(SM_CBAR + 32 + k * 8), "l"((u64)POL_FIRST << 32) : "memory");
        if (k < 4 && mlp)
            asm volatile("cp.async.bulk.prefetch.tensor.4d.L2.global.tile.L2::cache_hint [%0, {%1, %2, %3, %4}], %5;"
                         :: "l"(tmk + TM_WOP), "r"(0), "r"(5 * (cta & 3)), "r"((k >> 1) * 8), "r"((cta >> 2) * 8 + (k & 1) * 4), "l"((u64)POL_NORMAL << 32) : "memory");
    };
    auto issue_kv = [&](int i, int slot, int bar) {
        const int row = rowc + (i & 30) * 128 + (i & 1) * 32;
        mbar_expect(SM_CBAR + bar * 8, HT);
        tma3(SM_RING + slot * HT, tmk + TM_K + (i >> 5), 0, row, SM_CBAR + bar * 8, POL_FIRST);
        if (i >= 32) tma3_pf(tmk + TM_VP, 0, row, POL_NORMAL);
    };
    auto ep8 = [&]() { return lds32(0, SM_EPOCH); };
    auto load_v3 = [&](uint4* v, uint32_t u, int o, bool odd) {
        if (!odd) { v[0] = lds128(ad(offV0, u), o); v[1] = lds128(ad(offV0 ^ 16, u), o + 128); v[2] = lds128(ad(offV2, u), o + 256); }
        else { v[0] = lds128(ad(offV2 ^ 16, u), o + 384); v[1] = lds128(ad(offV0 ^ 64, u), o + 512); v[2] = lds128(ad(offV0 ^ 80, u), o + 640); }
    };
    auto load_v = [&](uint4 (&v)[6], uint32_t u, int o) { load_v3(v, u, o, false); load_v3(v + 3, u, o, true); };
    const uint32_t wqw = warp * SUB, ksw = warp * HT;
    auto slot_o = [&](int s) { return s < 3 ? SM_WQ + s * 8 * SUB : SM_KS + (s - 3) * SUB; };
    auto slot_u = [&](int s) { return s < 3 ? wqw : ksw; };
    auto issue2 = [&](auto I, uint32_t dep) {
        constexpr int p = I.value, s = PL.slot[p];
        __syncwarp();
        if ((p < 16 || mlp) && elect()) {
            mbar_expect(barw + s * 8, (dep & zero) | (p < 16 ? SUB : 2 * WOU + 256));
            if constexpr (p < 16) tma3(slot_u(s) + slot_o(s), tmk + TM_V8, 0, roww + vunit(p) * 256, barw + s * 8, POL_FIRST);
            else {
                tma3(slot_u(s) + slot_o(s), tmk + TM_WO, 5 * (cta & 3), (cta >> 2) * DH + warp * 24, barw + s * 8, POL_FIRST);
                asm volatile("cp.async.bulk.shared::cluster.global.mbarrier::complete_tx::bytes [%0], [%1], 256, [%2];"
                             :: "r"(slot_u(s) + slot_o(s) + 2 * WOU), "l"(P.b2 + min(warp, 4) * 128), "r"(barw + s * 8) : "memory");
            }
        }
    };
    auto touch2 = [&]() {
        const char* p = reinterpret_cast<const char*>(P.v) + (size_t)(roww + vunit(2) * 256) * (DH * 2) + lane * 32;
#pragma unroll
        for (int i = 0; i < 3; i++) asm volatile("cp.async.ca.shared.global [%0], [%1], 4;" :: "r"(SM_JUNK), "l"(p + i * 1024) : "memory");
    };
    auto issue_help = [&]() {
        if (elect())
            tma3(SM_WQ + (warp == 7 ? 0 : warp == 6 ? 16 * SUB : 4 * SUB), tmk + (warp == 5 ? TM_V8 : TM_V), 0,
                 rowc + (warp == 6 ? vunit(2) * 256 : warp == 5 ? vunit(0) * 256 + 32 : vunit(0) * 256), warp == 5 ? SM_BAR + 4 * 64 : SM_CBAR - 32 + warp * 8, POL_FIRST);
    };
    auto issue_item1 = [&]() {
        if (elect()) {
            mbar_expect(SM_CBAR - 48 + warp * 8, HT);
            tma3(SM_WQ - 4 * HT + warp * HT, tmk + TM_V, 0, rowc - 192 + warp * 32 + vunit(1) * 256, SM_CBAR - 48 + warp * 8, POL_FIRST);
        }
    };
    const uint32_t prow = warp * 768;
    uint4 wq0[6], wqh[3];
    uint32_t xna;
    auto load_wq = [&]() {
        load_v(wq0, wqw, SM_WQ);
        const int r0 = 6 * t + 3 * (warp & 1);
#pragma unroll
        for (int j = 0; j < 3; j++) wqh[j] = lds128(ad(r0 * 128 + ((g ^ ((r0 + j) & 7)) << 4), (warp >> 1) * SUB), SM_WQ + 16 * SUB + j * 128);
        const int r = c4 - j40;
        xna = pin((tid < 160 && r >= 0 && r < 40) ? SM_VEC + r * 8 : 0u);
        selA = pin(selA); selB = pin(selB);
        offV0 = pin(offV0 + wqw); offV2 = pin(offV2 + wqw);
        tid = pin(tid);
    };
    float acc[3][4];
    auto mma3 = [&](const uint4* v, uint32_t pp, uint32_t hi) {
        const uint32_t b0 = pick(pp, selA | hi), b1 = pick(pp, selB | hi);
        mma(acc[0], v[0], b0, b1); mma(acc[1], v[1], b0, b1); mma(acc[2], v[2], b0, b1);
    };
    auto ln_part = [&]() {
        const float x0 = bf_lo(xp.x), x1 = bf_hi(xp.x), x2 = bf_lo(xp.y), x3 = bf_hi(xp.y);
        const float s1 = (x0 + x1) + (x2 + x3), s2 = (x0 * x0 + x1 * x1) + (x2 * x2 + x3 * x3);
        float ss = ((tid & 16) ? s2 : s1) + shx((tid & 16) ? s1 : s2, 16);
        ss += shx(ss, 8); ss += shx(ss, 4); ss += shx(ss, 2); ss += shx(ss, 1);
        sts32_if((tid & 15) == 0 && tid < 160, tid >> 2, SM_STAT, __float_as_uint(ss));
    };

    auto tick = [&](uint4& v) {
        asm volatile("{\n.reg .pred p;\nsetp.ne.u32 p, %4, 0;\n@p mma.sync.aligned.m16n8k16.row.col.f32.bf16.bf16.f32 {%0,%1,%2,%3}, {%0,%1,%2,%3}, {%0,%1}, {%0,%1,%2,%3};\n}"
                     : "+r"(v.x), "+r"(v.y), "+r"(v.z), "+r"(v.w) : "r"(zero));
    };

    auto q_stage = [&](auto L) {
        constexpr int layer = L.value;
        asm volatile("{\n.reg .pred p;\nsetp.ne.u32 p, %0, 0;\n@p st.shared.v2.u32 [%0], {%1,%2};\n}" :: "r"(xna), "r"(xp.x), "r"(xp.y) : "memory");
        uint4 wq1[6];
        load_v3(wq1, 0, SM_WQ + 8 * SUB, false);
        const uint32_t xra = (tid & 3) * 4;
        __syncthreads();
        uint32_t p0 = lds32(ad(xra, warp * 16), SM_VEC), ph = lds32(ad(xra, (warp >> 1) * 16), SM_VEC + 256), p1 = lds32(ad(xra, warp * 16), SM_VEC + 128);
        if (layer == 0 && (tid & 16)) p0 = p1 = ph = ONES;
#pragma unroll
        for (int j = 0; j < 3; j++) zero4(acc[j]);
        mma3(wq0, p0, 0); mma3(wq0 + 3, p0, 0x2222);
        load_v3(wq1 + 3, 0, SM_WQ + 8 * SUB, true);
        mma3(wqh, ph, (warp & 1) * 0x2222); mma3(wq1, p1, 0); mma3(wq1 + 3, p1, 0x2222);
        if (layer == 1) { lds128(kc + 8, prow + (tid & 31) * 16, SM_PART); lds64(kc + 180, prow + (tid & 31) * 8, SM_PART + 512); __syncwarp(); }
        const uint32_t qpa = ((layer == 0 && (tid & 2)) ? ksw - (SM_PART - SM_KS - 11264) : prow) + (tid & 28) * 8 + (tid & 1) * 16;
#pragma unroll
        for (int j = 0; j < 3; j++) sts128f_if(layer == 0 || !(tid & 2), qpa, SM_PART + j * 256, acc[j][0], acc[j][1], acc[j][2], acc[j][3]);
        u64* dst = &g_ll[cta][tid];
        const uint32_t tag = ep8() + 1 + 4 * layer;
        __syncthreads();
        if (warp < 6) {
            const float s = sum8(tid * 4, SM_PART, 768);
            st_rlx(dst, layer ? mk64(tag, __float_as_uint(s)) : ll_pack2(__uint_as_float(__float_as_uint(sum8(tid * 4, SM_KS + 11264, HT)) + 128), s, tag));
        } else if (layer == 1) { sts32(0, SM_T0, gtime()); issue_item1(); }
        refresh_late();
        ln_part();
        __syncthreads();
        sts64(prow + lane * 8, SM_PART, xp.x, xp.y);
        if (layer == 1) sts128(prow + lane * 16, SM_PART + 256, kc[8], kc[9], kc[10], kc[11]);
    };
    auto q_addr = [&]() { return (((tid >> 1) & 1) * 4 + ((tid >> 4) & 3)) * 48 + ((tid >> 6) * 2 + ((tid >> 3) & 1)) * 8 + ((tid >> 2) & 1) * 4 + (tid & 1) * 2; };
    auto score6 = [&](const uint4 (&v)[6], const uint32_t (&qf)[12]) {
        float d[2][4];
#pragma unroll
        for (int i = 0; i < 6; i++) { if (i < 2) zero4(d[i]); mma(d[i & 1], v[i], qf[2 * i], qf[2 * i + 1]); }
        return (d[0][0] + d[0][3]) + (d[1][0] + d[1][3]);
    };
    auto softmax = [&](auto L, const float (&S)[4]) {
        constexpr int layer = L.value;
        const float mrun = warp_max(fmaxf(fmaxf(S[0], S[1]), fmaxf(S[2], S[3])));
        const float p0 = ex2((S[0] - mrun) * CS), p1 = ex2((S[1] - mrun) * CS), p2 = ex2((S[2] - mrun) * CS), p3 = ex2((S[3] - mrun) * CS);
        const uint32_t pa = pack_bf(p0, p1), pb = pack_bf(p2, p3), pw = prow + t * 64 + g * 2;
        sts16(pw, SM_PART + 256, pa); sts16(pw, SM_PART + 272, pa >> 16); sts16(pw, SM_PART + 288, pb); sts16(pw, SM_PART + 304, pb >> 16);
        const uint32_t l = __reduce_add_sync(~0u, __float2uint_rn(((p0 + p1) + (p2 + p3)) * 16777216.f));
        st_rlx(&g_ll[cta][192 + warp], mk64(__byte_perm(l + 128, ep8() + 1 + 4 * layer, 0x3214), __float_as_uint(mrun)));
        __syncwarp();
#pragma unroll
        for (int j = 0; j < 3; j++) zero4(acc[j]);
    };
    auto pv = [&](const uint4 (&v)[6], uint32_t pp) { mma3(v, pp, 0); mma3(v + 3, pp, 0x2222); };

    auto head_look = [&]() {
        if (lane < 16) asm volatile("cp.async.cg.shared.global [%0], [%1], 16;" :: "r"(SM_PART + 512 + prow + lane * 16), "l"(&g_ll[cta ^ g][192 + 2 * t]) : "memory");
    };
    float fw;
    auto head_weight = [&](auto L) {
        const uint32_t tag = (ep8() + 1 + 4 * L.value) & 255;
        uint32_t l, m;
#pragma unroll 1
        for (int it = 0; it < SPIN; it++) {
            if (it) head_look();
            asm volatile("cp.async.wait_all;" ::: "memory");
            __syncwarp();
            asm volatile("ld.volatile.shared.v2.u32 {%0,%1}, [%2];" : "=r"(l), "=r"(m) : "r"(SM_PART + 512 + prow + lane * 8) : "memory");
            l ^= tag;
            if (!__any_sync(~0u, l & 255)) break;
        }
        const float f = ex2((__uint_as_float(m) - warp_max(__uint_as_float(m))) * CS);
        const uint32_t Lh = __reduce_add_sync(~0u, __float2uint_rn(f * (float)l * 0.03125f));
        fw = __shfl_sync(~0u, f, warp) * rcp((float)Lh) * (ldsf(0, SM_FXS) * 524288.f);
    };

    uint32_t wa[5], ya, oa, selC, selD, tag;
    uint4 z[5];
    unsigned char* ra;
    const u64* lp;
    auto load_u = [&](uint4 (&a)[5], uint32_t u, int o) {
#pragma unroll
        for (int k = 0; k < 5; k++) a[k] = lds128(ad(wa[k], u), o);
    };
    auto tail_prep1 = [&](auto L) {
        xp = lds64(prow + lane * 8, SM_PART);
        tag = (ep8() + 3 + 4 * L.value) & 255;
        ya = pin(prow + (8 * g + 4 * (t & 1)) * 4);
        oa = pin(((tid >> 5) * 12 + min(lane, 11)) * 8);
        lp = pinp(reinterpret_cast<const u64*>(reinterpret_cast<const char*>(&g_ll[cta][0]) + oa));
    };
    auto tail_prep2 = [&](auto L) {
#pragma unroll
        for (int k = 0; k < 5; k++) {
            const int row = (t & 1) + 2 * (t & 2) + 2 * (k < 4 ? k >> 1 : g >> 2), j = k < 4 ? 2 * (k & 1) + (g >> 2) : 4;
            wa[k] = pin(row * 320 + j * 64 + (((g & 3) ^ (((5 * row + j) >> 1) & 3)) << 4));
        }
        selA = pin(selA); selB = pin(selB);
        selC = selA | (g >> 2) * 0x2222; selD = selB | (g >> 2) * 0x2222;
    };
    auto red_addr = [&](auto L) {
        const int word = t * 160 + j40 + (tid >> 2);
        ra = pinp(g_acc + 2 * L.value * ACC_BYTES + (uint32_t)((word >> 3) * ACC_PITCH + (word & 7) * 8));
    };
    uint4 wf[8], w2r[8];
    uint32_t la, w2a, hpa, ha, *op;
    uint2 b2v;
    const unsigned char* ap;
    unsigned char* ap2;
    float inv1;
    auto load_w1 = [&]() {
#pragma unroll
        for (int j = 0; j < 8; j++) wf[j] = ldsm_t(la, SM_RING + j * 256);
    };
    auto load_w2 = [&]() {
#pragma unroll
        for (int i = 0; i < 8; i++) w2r[i] = lds128(w2a ^ ((i & 1) * 16), SM_W2 + (i >> 1) * 5120 + (i & 1) * 128);
    };
    auto load_b2 = [&]() { asm volatile("ld.global.nc.v2.u32 {%0,%1}, [%2];" : "=r"(b2v.x), "=r"(b2v.y) : "l"(P.b2 + 4 * min(c4, 159))); };
    auto mlp_prep = [&](auto L) {
        unsigned char* const accb = g_acc + 2 * L.value * ACC_BYTES;
        la = (tid >> 5) * 4096 + (64 * ((lane >> 2) & 1) + 4 * ((lane >> 1) & 1) + (lane & 1) + 2 * (lane >> 4)) * 32 + ((((lane >> 3) ^ (lane >> 1)) & 1) << 4);
        w2a = pin((10 * t + 2 * (tid >> 5)) * 128 + ((g ^ ((2 * t + 2 * (tid >> 5)) & 7)) << 4));
        hpa = pin((tid >> 5) * 64 + (t * 8 + g) * 4); ha = pin((lane & 15) * 4);
        if (L.value == 0) { selA = pin(selA); selB = pin(selB); tid = pin(tid); }
        ap = accb + (uint32_t)((c4 >> 3) * ACC_PITCH + (c4 & 7) * 8);
        ap2 = accb + ACC_BYTES + pin((c4 >> 2) * ACC_PITCH + (c4 & 3) * 8);
        if (L.value == 1) ap2 = pinp(ap2);
        inv1 = fx_inv(ldsf(0, SM_FXS));
        if (L.value == 1) { ap = pinp(ap); la = pin(la); op = pinp(reinterpret_cast<uint32_t*>(P.out) + 2 * c4); }
    };
    auto tail = [&](auto L) {
        constexpr int layer = L.value;
        uint32_t cq;
        auto park = [&]() { const int ln = pin(tid) & 31; sts128(prow + ln * 16, SM_PART, kc[8], kc[9], kc[10], kc[11]); sts64(prow + ln * 8, SM_PART + 512, kc[180], kc[181]); };
        {
#pragma unroll
            for (int j = 0; j < 3; j++) sts128f_if(!(tid & 2), ya, SM_PART + 256 * j, acc[j][0] * fw, acc[j][2] * fw, acc[j][1] * fw, acc[j][3] * fw);
            __syncthreads();
            float2 own;
            {
                float2 s[8];
#pragma unroll
                for (int w = 0; w < 8; w++) s[w] = lds64f(oa, SM_PART + w * 768);
                own.x = ((s[0].x + s[1].x) + (s[2].x + s[3].x)) + ((s[4].x + s[5].x) + (s[6].x + s[7].x));
                own.y = ((s[0].y + s[1].y) + (s[2].y + s[3].y)) + ((s[4].y + s[5].y) + (s[6].y + s[7].y));
                st_rlx(const_cast<u64*>(lp), ll_pack2(own.x, own.y, tag));
            }
            const uint32_t c0 = clk();
            if (layer == 0) refresh_late();
            uint4 v[5], u[5];
            if constexpr (layer == 0) {
                if (warp < 3) { if (elect()) issue_wo(3 + warp); __syncwarp(); }
                if (warp >= 4) touch2();
                tail_prep2(L);
                mbar_wait(SM_CBAR + 32 + (warp >> 2) * 8, 0);
                load_u(v, warp * WOU, SM_RING);
                __syncthreads();
            }
            constexpr int YP = layer ? SM_WQ : SM_PART;
            float y[3][4];
#pragma unroll
            for (int j = 0; j < 3; j++) zero4(y[j]);
            const u64 *l1 = reinterpret_cast<const u64*>((u64)lp ^ 4096), *l2 = reinterpret_cast<const u64*>((u64)lp ^ 2048), *l3 = reinterpret_cast<const u64*>((u64)lp ^ 6144);
            tick(layer ? z[0] : v[0]);
            if (layer) while (clk() - c0 < ODELAY);
            uint32_t w1due = 0;
            if (layer == 0) {
                const uint32_t now = gtime();
                w1due = lds32(0, SM_T0) + PACE0 + 69 * PACE + W1D;
                w1due = ((int)(now - w1due) > 0 ? now : w1due) + (warp - 3) * W1G;
            }
            u64 w1 = ld_rlx(l1), w2 = ld_rlx(l2), w3 = ld_rlx(l3);
            if constexpr (layer == 1) {
                if (mlp) mbar_wait(barw + 40, IC<PL.par[16]>::value);
                load_u(v, mlp ? ksw + slot_o(5) : SM_RING + warp * WOU, 0); load_u(u, mlp ? ksw + slot_o(5) + WOU : SM_RING + (8 + warp) * WOU, 0);
            }
            if (layer == 0 && warp >= 3 && mlp) {
#pragma unroll 1
                for (int it = 0; it < 4096; it++) { tick(v[0]); if ((int)(gtime() - w1due) >= 0) break; }
                if (elect()) {
                    mbar_expect(SM_CBAR + 56 + warp * 8, 4096);
                    asm volatile("cp.async.bulk.tensor.2d.shared::cluster.global.mbarrier::complete_tx::bytes.L2::cache_hint [%0], [%1, {%2, %3}], [%4], %5;"
                                 :: "r"(SM_RING + (warp - 3) * 4096), "l"(tmk + TM_W1), "r"(hu), "r"(warp * 128 - 384), "r"(SM_CBAR + 56 + warp * 8), "l"((u64)POL_FIRST << 32) : "memory");
                }
                __syncwarp();
            }
#pragma unroll 1
            for (int it = 0; it < SPIN; it++) {
                if (it) { w1 = ld_rlx(l1); w2 = ld_rlx(l2); w3 = ld_rlx(l3); }
                if (!__any_sync(~0u, ((lo32(w1) ^ tag) | (lo32(w2) ^ tag) | (lo32(w3) ^ tag)) & 255)) break;
            }
            const uint32_t od = pack_bf((own.x + __uint_as_float(lo32(w1) ^ tag)) + (__uint_as_float(lo32(w2) ^ tag) + __uint_as_float(lo32(w3) ^ tag)),
                                        (own.y + __int_as_float(hi32(w1))) + (__int_as_float(hi32(w2)) + __int_as_float(hi32(w3))));
            const uint32_t o0 = __shfl_sync(~0u, od, tid & 3), o1 = __shfl_sync(~0u, od, (tid & 3) + 4), o2 = __shfl_sync(~0u, od, (tid & 3) + 8);
            auto narrow = [&](const uint4 (&a)[5], uint32_t o) { mma(y[2], a[4], pick(o, selC), pick(o, selD)); };
            auto wide = [&](const uint4 (&a)[5], uint32_t o) {
                const uint32_t b0 = pick(o, selA), b1 = pick(o, selB), b2 = pick(o, selA | 0x2222), b3 = pick(o, selB | 0x2222);
                mma(y[0], a[0], b0, b1); mma(y[1], a[1], b0, b1); mma(y[0], a[2], b2, b3); mma(y[1], a[3], b2, b3);
            };
            narrow(v, o0); wide(v, o0);
            if constexpr (layer == 0) {
                mbar_wait(SM_CBAR + 48 + (warp >> 2) * 8, 0);
                load_u(u, warp * WOU, SM_RING + 8 * WOU);
                __syncwarp();
                if (mlp && elect() && atoms_inc(SM_CNT + 44, 7) == 7) { mbar_expect(SM_CBAR + 120, 20480); tma3(SM_W2, tmk + TM_W2, 0, hu, SM_CBAR + 120, POL_FIRST); }
                __syncwarp();
                narrow(u, o1); wide(u, o1);
                red_addr(L);
                mbar_wait(SM_CBAR + 64 + (warp >> 2) * 8, 0);
                load_u(z, warp * WOU, SM_RING + 16 * WOU);
                narrow(z, o2);
            } else { narrow(u, o1); narrow(z, o2); wide(u, o1); }
            wide(z, o2);
#pragma unroll
            for (int k = 0; k < 4; k++) y[2][k] += shx(y[2][k], 18);
            sts128f_if(!(tid & 18), ya, YP + 512, y[2][0], y[2][1], y[2][2], y[2][3]);
            sts128f_if(!(tid & 2), ya, YP, y[0][0], y[0][1], y[0][2], y[0][3]);
            sts128f_if(!(tid & 2), ya, YP + 256, y[1][0], y[1][1], y[1][2], y[1][3]);
            __syncthreads();
            if (warp < 5) {
                const float s = sum8(tid * 4, YP, 768);
                asm volatile("red.relaxed.gpu.global.add.u64 [%0], %1;" :: "l"(ra), "l"(fx_pack(s)) : "memory");
            }
            cq = clk();
            if (layer == 0) refresh_late();
        }
        if (layer == 1 && !mlp) return;
        if (warp < 5) {
            if (layer == 0) { mlp_prep(L); if (mlp) mbar_wait(SM_CBAR + 80 + warp * 8, 0); }
            load_w1();
            if (layer == 1) { load_w2(); b2v = lds64(ksw + (c4 & 31) * 8, SM_KS + 11264); }
            {
                u64 w[4];
                while (clk() - cq < (layer || mlp ? AR1D : AR1DN));
                fx_poll(ap, w);
                xp = make_uint2(pack_bf(bf_lo(xp.x) + fx_val(w[0]) * inv1, bf_hi(xp.x) + fx_val(w[1]) * inv1),
                                pack_bf(bf_lo(xp.y) + fx_val(w[2]) * inv1, bf_hi(xp.y) + fx_val(w[3]) * inv1));
            }
            {
                const bool ev = layer || !(tid & 4), od = layer || (tid & 4);
                const uint32_t e0 = ev ? xp.x : ONES, e1 = ev ? xp.y : ONES, o0 = od ? xp.x : ONES, o1 = od ? xp.y : ONES;
                float d[8][4];
#pragma unroll
                for (int j = 0; j < 8; j++) { zero4(d[j]); mma(d[j], wf[j], (j & 1) ? o0 : e0, (j & 1) ? o1 : e1); }
                float lo = d[0][0] + d[1][1], hi = d[0][2] + d[1][3];
#pragma unroll
                for (int m = 1; m < 4; m++)
                    asm("{\n.reg .pred p;\nsetp.eq.u32 p, %6, %7;\n@p add.f32 %0, %2, %3;\n@p add.f32 %1, %4, %5;\n}" : "+f"(lo), "+f"(hi)
                        : "f"(d[2 * m][0]), "f"(d[2 * m + 1][1]), "f"(d[2 * m][2]), "f"(d[2 * m + 1][3]), "r"(tid & 3), "r"(m));
                float dd = ((tid & 1) ? hi : lo) + shx((tid & 1) ? lo : hi, 1);
                dd += shx(dd, 2);
                ln_part();
                if (layer == 0) {
                    const float cl = ((d[0][1] + d[1][0]) + (d[2][1] + d[3][0])) + ((d[4][1] + d[5][0]) + (d[6][1] + d[7][0]));
                    const float ch = ((d[0][3] + d[1][2]) + (d[2][3] + d[3][2])) + ((d[4][3] + d[5][2]) + (d[6][3] + d[7][2]));
                    sts32_if(!(tid & 2), hpa, SM_C1, __float_as_uint((tid & 1) ? ch : cl));
                }
                sts32_if(!(tid & 2), hpa, SM_QU, __float_as_uint(dd));
            }
            const float b1v = ldsf(ha, SM_B1);
            float csum = layer ? ldsf(ha, SM_B1 + 64) : 0.f;
            bar_sync(1, layer ? 160 : 192);
            float mean, rstd, msq;
            ln_final(mean, rstd, msq);
            float hp[5];
#pragma unroll
            for (int w = 0; w < 5; w++) hp[w] = ldsf(ha, SM_QU + w * 64);
            if constexpr (layer == 0) {
                float c[5];
#pragma unroll
                for (int w = 0; w < 5; w++) c[w] = ldsf(ha, SM_C1 + w * 64);
                csum = ((c[0] + c[1]) + (c[2] + c[3])) + c[4];
                load_w2();
            }
            float hv = ((((hp[0] + hp[1]) + (hp[2] + hp[3])) + hp[4]) - mean * csum) * rstd + b1v;
            hv = hv * rcp(1.f + ex2(hv * (-2.302208198f - 0.1029432397f * hv * hv)));
            const uint32_t hd = pack_bf(hv, hv);
            float ym[4][4];
            const uint32_t hh[4] = {__shfl_sync(~0u, hd, tid & 3), __shfl_sync(~0u, hd, (tid & 3) + 4), __shfl_sync(~0u, hd, (tid & 3) + 8), __shfl_sync(~0u, hd, (tid & 3) + 12)};
#pragma unroll
            for (int i = 0; i < 4; i++) {
                const uint32_t b0 = pick(hh[i], selA), b1 = pick(hh[i], selB);
                if (i < 2) { zero4(ym[2 * i]); zero4(ym[2 * i + 1]); }
                mma(ym[2 * (i & 1)], w2r[2 * i], b0, b1); mma(ym[2 * (i & 1) + 1], w2r[2 * i + 1], b0, b1);
            }
            const float sc2 = __uint_as_float((uint32_t)(127 + 16 - max(((int)(__float_as_uint(msq) >> 23) - 127) >> 1, -100)) << 23);
            float y[4];
            uint32_t yb[4];
#pragma unroll
            for (int k = 0; k < 4; k++) { y[k] = ((tid & 2) ? ym[1][k] : ym[0][k]) + ((tid & 2) ? ym[3][k] : ym[2][k]); yb[k] = __float_as_uint(fmaf(y[k], sc2, FX2_MAGIC)); }
            const uint32_t big = !mlp ? 0 : (((yb[0] ^ 0x4b400000u) | (yb[1] ^ 0x4b400000u)) | ((yb[2] ^ 0x4b400000u) | (yb[3] ^ 0x4b400000u))) & FX2_MASK;
            u64 w[2], old[2];
#pragma unroll
            for (int k = 0; k < 2; k++) {
                w[k] = mk64(big ? 0 : yb[2 * k] * 512 + 0x80000001u, big ? 0 : yb[2 * k + 1] * 16 + 0x4c000000u);
                if (layer == 0) { if (mlp) asm volatile("red.relaxed.gpu.global.add.u64 [%0], %1;" :: "l"(ap2 + k * 40 * ACC_PITCH), "l"(w[k]) : "memory"); }
                else asm volatile("atom.relaxed.gpu.global.add.u64 %0, [%1], %2;" : "=l"(old[k]) : "l"(ap2 + k * 40 * ACC_PITCH), "l"(w[k]) : "memory");
            }
            const uint32_t c0 = clk();
            if (__any_sync(~0u, big)) {
                if (big) {
#pragma unroll
                    for (int k = 0; k < 4; k++)
                        asm volatile("red.relaxed.gpu.global.add.u64 [%0], %1;" :: "l"(ap2 + (k >> 1) * 40 * ACC_PITCH + 64 + (k & 1) * 32), "l"(fx_pack(y[k] * fx_scale(msq))) : "memory");
                    fence_gpu();
#pragma unroll
                    for (int k = 0; k < 2; k++) {
                        asm volatile("red.relaxed.gpu.global.and.b64 [%0], %1;" :: "l"(ap2 + k * 40 * ACC_PITCH), "l"(~256ull) : "memory");
                        w[k] = FX2_NONE;
                        asm volatile("atom.relaxed.gpu.global.add.u64 %0, [%1], %2;" : "=l"(old[k]) : "l"(ap2 + k * 40 * ACC_PITCH), "l"(FX2_NONE) : "memory");
                    }
                }
                __syncwarp();
            }
            if (layer == 0) { refresh(); load_b2(); park(); stsf(ha, SM_B1 + 64, csum); }
            stsf(0, SM_FXS, msq);
            const float inv32 = fx_inv(sc2) * 0.03125f;
            float xb[4] = {bf_lo(xp.x) + bf_lo(b2v.x) - 24.f * inv32, bf_hi(xp.x) + bf_hi(b2v.x), bf_lo(xp.y) + bf_lo(b2v.y) - 24.f * inv32, bf_hi(xp.y) + bf_hi(b2v.y)};
            auto add_wide = [&]() {
                fence_gpu();
                const float inv = fx_inv(fx_scale(ldsf(0, SM_FXS)));
#pragma unroll
                for (int k = 0; k < 4; k++) xb[k] += fx_val(ld_rlx(ap2 + (k >> 1) * 40 * ACC_PITCH + 64 + (k & 1) * 32)) * inv;
            };
            auto sum2 = [&](int k) {
                return pack_bf(xb[2 * k] + (float)(int)__funnelshift_r(lo32(w[k]), hi32(w[k]), 4) * inv32, xb[2 * k + 1] + (float)hi32(w[k]) * (inv32 + inv32));
            };
            if constexpr (layer == 1) {
#pragma unroll
                for (int k = 0; k < 4; k++) xb[k] = pinf(xb[k]);
                mbar_wait(SM_BAR + 3 * 64 + 56, 0);
#pragma unroll
                for (int k = 0; k < 2; k++) {
                    w[k] += old[k];
                    asm volatile("{\n.reg .pred p;\nsetp.eq.u32 p, %2, 0;\n@p st.global.u32 [%0], %1;\n}" :: "l"(op + k), "r"(sum2(k)), "r"(~lo32(w[k]) & 0x180) : "memory");
                }
                if (((lo32(w[0]) & ~(lo32(w[0]) >> 1)) | (lo32(w[1]) & ~(lo32(w[1]) >> 1))) & 128) {
                    add_wide();
                    if (w[0] & 128) op[0] = sum2(0);
                    if (w[1] & 128) op[1] = sum2(1);
                }
            } else {
                load_wq();
                __syncwarp();
                if (elect()) mbar_arrive(SM_BAR + 56);
#pragma unroll
                for (int k = 0; k < 4; k++) xb[k] = pinf(xb[k]);
                while (clk() - c0 < AR2D);
                uint32_t want = 0x180;
#pragma unroll 1
                for (int it = 0; it < SPIN; it++) {
                    if (it && !__any_sync(~0u, ~(lo32(w[0]) & lo32(w[1])) & 128)) { add_wide(); want = 128; }
                    w[0] = ld_rlx(ap2); w[1] = ld_rlx(ap2 + 40 * ACC_PITCH);
                    if (!__any_sync(~0u, ~(lo32(w[0]) & lo32(w[1])) & want)) break;
                }
                xp = make_uint2(sum2(0), sum2(1));
            }
        } else if constexpr (layer == 1) {
            if (warp == 7) {
                const uint32_t c1 = clk();
                while (clk() - c1 < KAD) tick(z[0]);
                if (zero) sts32(0, SM_JUNK, z[0].x);
            }
        } else {
            const uint32_t c0 = clk();
            load_wq();
            __syncwarp();
            if (elect()) mbar_arrive(SM_BAR + 56);
            if (warp == 5) {
                if (mlp) mbar_wait(SM_CBAR + 120, 0);
                asm volatile("bar.arrive 1, 192;" ::: "memory");
            }
            while (clk() - c0 < S6D + (warp - 5) * S6G) tick(wqh[0]);
            issue2(IC<0>{}, wq0[0].x | wq0[1].x | wq0[2].x | wq0[3].x | wq0[4].x | wq0[5].x);
            if (elect()) mbar_expect(warp == 5 ? SM_BAR + 4 * 64 : SM_CBAR - 32 + warp * 8, warp == 5 ? SUB : HT);
#pragma unroll 1
            for (int it = 0; it < SPIN; it++) { if (mbar_test(SM_BAR + 56, 0)) break; tick(wqh[0]); }
            const uint32_t c1 = clk();
            park();
            while (clk() - c1 < I0D) tick(wqh[0]);
            issue_help();
        }
    };

#pragma unroll 1
    for (uint32_t late = zero;; late = zero + 1) {
        if (late) {
            tail(IC<0>{});

            q_stage(IC<1>{});
            {
                const u64* qp = &g_ll[cta & ~3][tid];
                u64 w[4] = {0, 0, 0, 0};
                if (warp < 6) { w[0] = ld_rlx(qp); w[1] = ld_rlx(qp + 256); w[2] = ld_rlx(qp + 512); w[3] = ld_rlx(qp + 768); }
                mbar_wait(SM_BAR + 3 * 64 + 56, 0);
                const uint32_t ksl = ksw + lane * 16, qa = pin(q_addr()), qb0 = pin(lane < 8 ? lane * 48 : SM_ZQ - SM_VEC);
                uint32_t ks[96], qf[12];
                float mean, rstd, msq;
                ln_final(mean, rstd, msq);
                const float qc = pinf(-mean * rstd * ldsf(tid * 4, SM_CS));
#pragma unroll
                for (int k = 0; k < 6; k++) lds128(ks + 4 * k, ksl, SM_KS + k * 512);
                stsf(0, SM_FXS, fx_scale(msq));
                if (warp < 6) {
                    ll_gather4(qp, ep8() + 5, w);
                    const float q = ((hif(w[0]) + hif(w[1])) + (hif(w[2]) + hif(w[3]))) * rstd + qc;
                    const uint32_t qq = bf2_mul(pack_bf(q, q), 0x3f807180u);
                    sts16(qa, SM_VEC, qq); sts16(qa, SM_QU, qq >> 16);
                    sts32_if(!(fabsf(q) < 1048576.f), 0, SM_BIG, 1);
                    __syncwarp();
                    if (elect()) mbar_arrive(SM_QBAR);
                } else {
                    uint4 c = make_uint4(ks[0], ks[1], ks[2], ks[3]);
                    if (cta == 0 && tid == 255) g_epoch = (ep8() >> 3) + 1;
#pragma unroll 1
                    for (int it = 0; it < SPIN; it++) { if (mbar_test(SM_QBAR, 1)) break; tick(c); }
                    ks[0] = c.x; ks[1] = c.y; ks[2] = c.z; ks[3] = c.w;
                }
                issue2(IC<3>{}, ks[0] | ks[4] | ks[8] | ks[12] | ks[16] | ks[20]);
                mbar_wait(SM_QBAR, 1);
                auto load_q = [&](int u, int k) { lds128(qf + 4 * k, u == 0 ? qb0 : (tid & 24) == 8 * u ? (tid & 7) * 48 : SM_ZQ - SM_VEC, SM_VEC + k * 16); };
                load_q(0, 1); load_q(0, 2); load_q(0, 0);
                float D[4][4];
                uint4 vb[NPK + 2][6], v2[6];
                uint32_t xn = 0;
                const uint32_t t1 = __shfl_sync(~0u, lds32(0, SM_T0), 0);
                auto step = [&](auto Q) {
                    constexpr int st = Q.value, p = cord(st), s = PL.slot[p], n = PL.ld[st];
                    if constexpr (n > 0) {
                        if constexpr (st >= NPK) {
                            const uint32_t due = t1 + (P2A + n * P2B);
#pragma unroll 1
                            for (int it = 0; it < 4096; it++) if ((int)(gtime() - due) >= 0) break;
                        }
                        const uint4 (&u)[6] = vb[st - 1 < NPK ? st - 1 : NPK + ((st - 1) & 1)];
                        issue2(IC<n>{}, st > PVNOW ? 0 : u[0].x | u[1].x | u[2].x | u[3].x | u[4].x | u[5].x);
                    }
                    if constexpr (st == 14) {
#pragma unroll 1
                        for (int it = 0; it < 4096; it++) if ((int)(gtime() - t1) >= P2W) break;
                        issue2(IC<16>{}, 0);
                    }
                    if (p == 1) mbar_wait(SM_CBAR + (warp >> 2) * 8, 1);
                    else if (p == 0) mbar_wait(warp < 4 ? SM_CBAR + 24 : barw, warp < 4);
                    else mbar_wait(barw + s * 8, IC<PL.par[p]>::value);
                    load_v(vb[st < NPK ? st : NPK + (st & 1)], slot_u(s), slot_o(s));
                };
                static_for<0, 96>([&](auto I) {
                    constexpr int F = I.value, n = F / 6, i = n ? F % 6 : (F + 2) % 6;
                    const uint32_t* c = n == 0 ? (i < 2 ? ks + 3 * i : kc + 174 + 3 * i) : n < 6 ? ks + 18 * n - 12 + 3 * i : kc + 18 * (n - 6) + 3 * i;
                    const uint32_t hx = c[2] & 0x78787878u, ha = hx * (zero - 1) + c[2], hb = __funnelshift_r(hx, hx, 4);
                    if (F < 24 && F % 6 == 0) zero4(D[n]);
                    mma(D[n & 3], __byte_perm(c[0], ha, 0x5140), __byte_perm(c[0], ha, 0x7362), __byte_perm(c[1], hb, 0x5140), __byte_perm(c[1], hb, 0x7362), qf[2 * i], qf[2 * i + 1]);
                    if constexpr ((n & 3) == 3 && n < 15 && (i & 1)) load_q((n + 1) >> 2, i >> 1);
                    static_for<6, 24>([&](auto U) {
                        if constexpr (((U.value - 5) * 4 + 2) / 3 - 1 == F) {
                            lds128(ks + 4 * U.value, ksl, SM_KS + U.value * 512);
                            if constexpr (U.value % 6 == 5) { const uint32_t* k = ks + 4 * U.value - 17; issue2(IC<3 + U.value / 6>{}, k[0] | k[4] | k[8] | k[12] | k[16] | k[20]); }
                        }
                    });
                    if constexpr (F == 94) {
                        if (warp < 4) { mbar_wait(SM_CBAR + 16, 1); load_v(v2, wqw, slot_o(2)); }
                        else {
                            const char* p = reinterpret_cast<const char*>(P.v) + (size_t)(roww + vunit(2) * 256) * (DH * 2) + t * 768 + g * 16;
#pragma unroll
                            for (int k = 0; k < 6; k++)
                                asm volatile("ld.global.nc.v4.u32 {%0,%1,%2,%3}, [%4];" : "=r"(v2[k].x), "=r"(v2[k].y), "=r"(v2[k].z), "=r"(v2[k].w) : "l"(p + k * 128));
                        }
                        const uint2 x = lds64(0, SM_XN);
                        xn = x.y ? XCAP + 1 : x.x;
                        sts128(prow + lane * 16, SM_PART + 256, 0, 0, 0, 0);
                        __syncwarp();
#pragma unroll 1
                        for (uint32_t idx = lane; idx < (xn > XCAP ? 0 : xn); idx += 32) {
                            const uint32_t m = lds32(idx * 4, SM_XM);
                            if ((m >> 21) == warp) {
                                const uint4 r = lds128(idx * 16, SM_XR);
                                const uint32_t qo = ((m >> 16) & 3) * 48 + (m & 255);
                                const uint2 a = lds64(qo, SM_QU), b = lds64(qo, SM_QU + 192);
                                const float s = ((bf_lo(r.x) * bf_lo(a.x) + bf_hi(r.x) * bf_hi(a.x)) + (bf_lo(r.y) * bf_lo(b.x) + bf_hi(r.y) * bf_hi(b.x))) +
                                                ((bf_lo(r.z) * bf_lo(a.y) + bf_hi(r.z) * bf_hi(a.y)) + (bf_lo(r.w) * bf_lo(b.y) + bf_hi(r.w) * bf_hi(b.y)));
                                asm volatile("red.relaxed.cta.shared.add.f32 [%0], %1;" :: "r"(SM_PART + 256 + prow + ((m >> 18) & 7) * 64 + ((m >> 8) & 15) * 4), "f"(s) : "memory");
                            }
                        }
                        __syncwarp();
                    }
                    if constexpr (F == PK0 - 2) { refresh(); lds128(kc + 8, prow + lane * 16, SM_PART + 256); }
                    static_for<0, NPK>([&](auto Q) { if constexpr (F == (Q.value ? PK1 + (Q.value - 1) * PKD : PK0)) step(Q); });
                });
                float S[4];
                {
                    const uint32_t shp = lds32(tid * 4, SM_SH);
                    const uint4 cr = lds128(prow + lane * 16, SM_PART + 256);
                    const uint32_t c[4] = {cr.x, cr.y, cr.z, cr.w};
#pragma unroll
                    for (int j = 0; j < 4; j++) S[j] = (D[j][0] + D[j][3]) * __uint_as_float((((shp >> (8 * j)) & 255) + 27) << 23) + __uint_as_float(c[j]);
                }
                if (xn > XCAP) {
#pragma unroll
                    for (int k = 0; k < 3; k++) lds128(qf + 4 * k, (lane & 7) * 48, SM_QU + k * 16);
                    const char* kp = reinterpret_cast<const char*>(P.k) + (size_t)(roww + g) * (DH * 2) + t * 32;
#pragma unroll 1
                    for (int e = 6; e < 22; e++, kp += 256 * DH * 2) {
                        uint4 v[6];
#pragma unroll
                        for (int i = 0; i < 6; i++) v[i] = ldg128(kp + (i >> 1) * 128 + (i & 1) * 16);
                        const float s = score6(v, qf);
                        if (t == ((e >> 2) & 3)) { S[0] = S[1]; S[1] = S[2]; S[2] = S[3]; S[3] = s; }
                    }
                    if (t == 1) { const float a = S[0], b = S[1]; S[0] = S[2]; S[1] = S[3]; S[2] = a; S[3] = b; }
                }
                softmax(IC<1>{}, S);
                auto p_of = [&](int st) { return lds32(ad(t * 4, prow), SM_PART + 256 + ((vunit(cord(st)) + 6) & 15) * 16); };
                auto pv_at = [&](auto Q) { constexpr int st = Q.value; pv(vb[st < NPK ? st : NPK + (st & 1)], p_of(st)); };
                static_for<NPK, 15>([&](auto Q) {
                    constexpr int st = Q.value;
                    if constexpr (st == HWAT) head_look();
                    if constexpr (st == HWC) head_weight(IC<1>{});
                    if constexpr (st == PREP1) { tail_prep1(IC<1>{}); tail_prep2(IC<1>{}); red_addr(IC<1>{}); load_u(z, warp * WOU, SM_RING + 16 * WOU); }
                    if constexpr (st == PREP2) mlp_prep(IC<1>{});
                    uint32_t pp;
                    if constexpr (st >= PVNOW) pp = pin(p_of(st));
                    step(Q);
                    if constexpr (st - NPK < NPK) pv_at(IC<st - NPK>{});
                    if constexpr (st > NPK && st <= PVNOW) pv_at(IC<st - 1>{});
                    if constexpr (st == PV2) pv(v2, lds32(ad(t * 4, prow), SM_PART + 256 + ((vunit(2) + 6) & 15) * 16));
                    if constexpr (st >= PVNOW) pv(vb[NPK + (st & 1)], pp);
                });
            }
            tail(IC<1>{});
            if (!zero) return;
        }
        tid = threadIdx.x;
        derive();
        xp = make_uint2(0, 0);
        if (tid < 160) xp = *reinterpret_cast<const uint2*>(P.x + 4 * c4);
        else if (tid == 192) xp.x = *(volatile unsigned*)&g_epoch;
        else if (tid >= 224 && tid < 240 && mlp) xp.x = reinterpret_cast<const unsigned short*>(P.b1)[hu + lane];
        __syncwarp();
        if (elect()) {
#pragma unroll
            for (int i = 0; i < 7; i++) mbar_init(barw + i * 8, 1);
            if (warp < 4) mbar_arrive(barw);
            mbar_init(SM_CBAR + warp * 8, 1); mbar_init(SM_CBAR + 64 + warp * 8, 1);
            if (warp == 0) { mbar_init(SM_QBAR, 6); mbar_init(SM_BAR + 56, 8); }
            asm volatile("fence.mbarrier_init.release.cluster;" ::: "memory");
            sts64(warp * 8, SM_CNT, 0, 0);
            sts64(warp * 8, SM_ZQ, 0, 0);
        }
#pragma unroll
        for (int i = 12; i < 192; i++) asm volatile("mov.b32 %0, 0;" : "=r"(kc[i]));
        __syncwarp();
        if (warp < 3) { wait_due(warp, 0); if (elect()) issue_kv(warp, warp + 1, warp); }
        else mbar_wait(barw + 56, 0);
        if (tid == 192) sts32(0, SM_EPOCH, xp.x * 8);
        if (tid >= 224 && tid < 240) sts32(lane * 4, SM_B1, xp.x << 16);
        __syncthreads();
        if ((warp == 3 || warp == 4) && elect()) issue_kv(warp, warp == 4 ? 0 : 4, warp);

        load_wq();
        q_stage(IC<0>{});
        {
            int it = (warp >> 2) + 5, slot = (warp >> 2) + 1, bar = warp >> 2, par = 0;
            auto refill = [&](bool kv) {
                uint32_t old;
                asm volatile("{\n.reg .pred p;\nelect.sync _|p, 0xffffffff;\nmov.u32 %0, 0;\n@p atom.relaxed.cta.shared.inc.u32 %0, [%1], 3;\n}" : "=r"(old) : "r"(SM_CNT + slot * 8) : "memory");
                if (__any_sync(~0u, old == 3)) {
                    if (!kv && it >= 64) {
#pragma unroll 1
                        for (int k = 0; k < SPIN; k++) {
                            int f; asm volatile("ld.volatile.shared.u32 %0, [%1];" : "=r"(f) : "r"(SM_CNT + 4) : "memory");
                            if (f >= slot) break;
                        }
                        sts32(0, SM_CNT + 4, slot + 1);
                        if (elect()) issue_wo(slot);
                    } else {
                        wait_due(it, 0);
                        if (elect()) issue_kv(it, slot, bar < 5 ? bar + 5 : bar - 5);
                    }
                    __syncwarp();
                }
            };
            auto advance = [&]() { it += 2; slot += 2; if (slot >= 5) slot -= 5; bar += 2; if (bar >= 10) { bar -= 10; par ^= 1; } };
            {
                uint32_t offK[3], qf[12];
#pragma unroll
                for (int j = 0; j < 3; j++) offK[j] = pin(((tid >> 5) & 3) * SUB + 3 * g * 128 + (((2 * t) ^ ((3 * g + j) & 7)) << 4));
#pragma unroll
                for (int i = 0; i < 12; i++) qf[i] = kc[i] = 0;
                const uint32_t ksl = pin(ksw + lane * 16), sca = pin(prow + g * 64);
                int n0 = 0;
#pragma unroll 1
                for (int e = 0; e < 16; e++) {
                    mbar_wait(SM_CBAR + bar * 8, par);
                    uint4 v[6];
#pragma unroll
                    for (int i = 0; i < 6; i++) v[i] = lds128(ad(offK[i >> 1] ^ ((i & 1) * 16), slot * HT), SM_RING + (i >> 1) * 128);
                    refill(true);
                    advance();
                    if ((0xc20 | ((2 << NP) - 1)) >> e & 1) {
                        refresh();
                        static_for<0, NP>([&](auto E) {
                            if (e == E.value) {
#pragma unroll
                                for (int i = 0; i < 6; i++) {
                                    uint32_t* k = kc + 90 + 24 * E.value + 4 * i;
                                    asm volatile("mov.b32 %0, %4; mov.b32 %1, %5; mov.b32 %2, %6; mov.b32 %3, %7;" : "=r"(k[0]), "=r"(k[1]), "=r"(k[2]), "=r"(k[3]) : "r"(v[i].x), "r"(v[i].y), "r"(v[i].z), "r"(v[i].w));
                                }
                                if (E.value == NP - 2 && warp < 6) {
#pragma unroll
                                    for (int i = 0; i < 2; i++)
                                        asm volatile("cp.async.cg.shared.global [%0], [%1], 16;" :: "r"(ksl + SM_KS + 10240 + i * 512),
                                                     "l"(&g_ll[(cta & ~3) + 2 * i + (lane >> 4)][warp * 32 + (lane & 15) * 2]) : "memory");
                                }
                                if (E.value == NP - 1 && warp < 6) {
                                    asm volatile("cp.async.wait_all;" ::: "memory");
                                    __syncwarp();
                                    const uint32_t a = ksw + lane * 8;
                                    u64 w[4] = {lds_u64(a, SM_KS + 10240), lds_u64(a, SM_KS + 10496), lds_u64(a, SM_KS + 10752), lds_u64(a, SM_KS + 11008)};
                                    ll_gather4(&g_ll[cta & ~3][tid], ep8() + 1, w);
                                    const float cs = (lof(w[0] & ~255ull) + lof(w[1] & ~255ull)) + (lof(w[2] & ~255ull) + lof(w[3] & ~255ull));
                                    float q = (hif(w[0]) + hif(w[1])) + (hif(w[2]) + hif(w[3]));
                                    stsf(tid * 4, SM_CS, cs);
                                    float mean, rstd, msq;
                                    ln_final(mean, rstd, msq);
                                    stsf(0, SM_FXS, fx_scale(msq));
                                    q = (q - mean * cs) * rstd;
                                    sts16(q_addr(), SM_QU, pack_bf(q, q));
                                    __syncwarp();
                                    if (elect()) mbar_arrive(SM_QBAR);
#pragma unroll
                                    for (int i = 0; i < 12; i++) asm volatile("mov.b32 %0, 0;" : "=r"(kc[i]));
                                }
                            }
                        });
                        if (e == NP) {
                            mbar_wait(SM_QBAR, 0);
#pragma unroll
                            for (int k = 0; k < 3; k++) lds128(qf + 4 * k, (lane & 7) * 48, SM_QU + k * 16);
                            static_for<0, NP>([&](auto E) {
                                uint4 r[6];
#pragma unroll
                                for (int i = 0; i < 6; i++) { const uint32_t* k = kc + 90 + 24 * E.value + 4 * i; r[i] = make_uint4(k[0], k[1], k[2], k[3]); }
                                stsf(sca, SM_PART + 256 + (E.value + 6) * 4, score6(r, qf));
                            });
#pragma unroll
                            for (int i = 0; i < 24; i++) asm volatile("mov.b32 %0, 0;" : "=r"(kc[i]));
                        } else if (e == 5) {
#pragma unroll
                            for (int k = 0; k < 22; k++) lds128(kc + 4 * k, ksl, SM_KS + k * 512);
                            lds64(kc + 88, ksl, SM_KS + 22 * 512);
                            n0 = 0;
                        } else if (e == 10) {
#pragma unroll
                            for (int k = 0; k < 22; k++)
                                asm volatile("ld.shared.v4.b32 {%0,%1,%2,%3}, [%4];" : "=r"(kc[90 + 4 * k]), "=r"(kc[91 + 4 * k]), "=r"(kc[92 + 4 * k]), "=r"(kc[93 + 4 * k]) : "r"(ad(ksl, SM_KS + k * 512)) : "memory");
                            asm volatile("ld.shared.v2.b32 {%0,%1}, [%2];" : "=r"(kc[178]), "=r"(kc[179]) : "r"(ad(ksl, SM_KS + 22 * 512)) : "memory");
                            n0 = 0;
                        } else if (e == 11) {
                            lds64(kc + 180, ksl, SM_KS + 520); lds128(kc + 182, ksl, SM_KS + 1024); lds128(kc + 186, ksl, SM_KS + 1536); lds64(kc + 190, ksl, SM_KS + 2048);
                            n0 = 3;
                        }
                    }
                    const int n = (e + 6) & 15;
                    stsf(ad(sca, n * 4), SM_PART + 256, score6(v, qf));
                    uint32_t m = bf2_amax(bf2_amax(v[0].x, v[0].y), bf2_amax(v[0].z, v[0].w)), mn = bf2_amin(bf2_amin(v[0].x, v[0].y), bf2_amin(v[0].z, v[0].w));
#pragma unroll
                    for (int i = 1; i < 6; i++) m = bf2_amax(m, bf2_amax(bf2_amax(v[i].x, v[i].y), bf2_amax(v[i].z, v[i].w)));
                    m = max(m & 0x7fff, (m >> 16) & 0x7fff);
                    m = max(m, __shfl_xor_sync(~0u, m, 1)); m = max(m, __shfl_xor_sync(~0u, m, 2));
#pragma unroll
                    for (int i = 1; i < 6; i++) mn = bf2_amin(mn, bf2_amin(bf2_amin(v[i].x, v[i].y), bf2_amin(v[i].z, v[i].w)));
                    mn = min(mn & 0x7fff, (mn >> 16) & 0x7fff);
                    const int sh = min(max((int)(m >> 7) - 15, 0), 126);
                    asm volatile("st.shared.u8 [%0], %1;" :: "r"(ad(ad((tid >> 2) * 16, n), SM_SH)), "r"(sh) : "memory");
                    const uint32_t dn = (127 - sh) * 0x00800080u;
                    if (__any_sync(~0u, (int)(mn >> 7) <= sh || m >= (142 << 7))) {
                        if (m >= (142 << 7)) sts32(0, SM_BIG, 1);
                        const uint32_t up = (127 + 256 + sh) * 0x00800080u;
#pragma unroll
                        for (int i = 0; i < 6; i++) {
                            const uint32_t r0 = bf2_fma(bf2_mul(v[i].x, dn), up, v[i].x), r1 = bf2_fma(bf2_mul(v[i].y, dn), up, v[i].y);
                            const uint32_t r2 = bf2_fma(bf2_mul(v[i].z, dn), up, v[i].z), r3 = bf2_fma(bf2_mul(v[i].w, dn), up, v[i].w);
                            asm volatile("{\n.reg .pred p;\n.reg .u32 x, a;\nsetp.ne.u32 p, %0, 0;\nmov.u32 x, %7;\n@p atom.relaxed.cta.shared.inc.u32 x, [%6], 0x7fffffff;\n"
                                         "setp.lt.u32 p, x, %7;\nmad.lo.u32 a, x, 16, %8;\n@p st.shared.v4.u32 [a], {%1,%2,%3,%4};\n"
                                         "mad.lo.u32 a, x, 4, %9;\n@p st.shared.u32 [a], %5;\n}"
                                         :: "r"(r0 | r1 | r2 | r3), "r"(r0), "r"(r1), "r"(r2), "r"(r3), "r"(tid << 16 | n << 8 | i * 8), "r"(SM_XN), "n"(XCAP), "n"(SM_XR), "n"(SM_XM) : "memory");
                        }
                    }
                    const uint32_t ae = (n0 >> 1) * 512 + (n0 & 1) * 8, ao = ((n0 + 1) >> 1) * 512 + (~n0 & 1) * 8;
                    uint32_t o[18];
#pragma unroll
                    for (int i = 0; i < 6; i++) {
                        const uint32_t y0 = bf2_mulv(v[i].x, dn), y1 = bf2_mulv(v[i].y, dn), y2 = bf2_mulv(v[i].z, dn), y3 = bf2_mulv(v[i].w, dn);
                        o[3 * i] = __byte_perm(y0, y1, 0x6420); o[3 * i + 1] = __byte_perm(y2, y3, 0x6420);
                        const uint32_t hb = __byte_perm(y2, y3, 0x7531);
                        o[3 * i + 2] = __byte_perm(y0, y1, 0x7531) | __funnelshift_l(hb, hb, 4);
                        if (i & 1) {
#pragma unroll
                            for (int k = 3 * (i >> 1); k < 3 * (i >> 1) + 3; k++) sts64(ad(ksl, (k & 1) ? ao : ae), SM_KS + (k >> 1) * 512, o[2 * k], o[2 * k + 1]);
                        }
                    }
                    n0 += 9;
                }
                fence_async();
            }
            refresh();
            {
                const uint4 sc = lds128(prow + lane * 16, SM_PART + 256);
                const float S[4] = {__uint_as_float(sc.x), __uint_as_float(sc.y), __uint_as_float(sc.z), __uint_as_float(sc.w)};
                softmax(IC<0>{}, S);
            }
            fw = 0.f;
#pragma unroll 1
            for (int e = 0; e < 16; e++) {
                if ((1 << (PUBAT - 3) | 1 << PUBAT | 1 << ZCHK) >> e & 1) {
                    if (e == PUBAT - 3) head_look();
                    else if (e == PUBAT) {
                        head_weight(IC<0>{});
                        if (tid < 196) st_rlx(&g_ll[cta][tid + (tid >> 6 == 3) * 8], 0ull);
                    } else if (warp == 7) {
                        if ((bx & 15) == 0 && elect()) bulk_pf(P.b2, D_MODEL * 2, POL_NORMAL);
#pragma unroll 1
                        for (int k = 0; k < SPIN; k++) {
                            uint32_t v; asm volatile("ld.acquire.gpu.global.u32 %0, [%1];" : "=r"(v) : "l"(&g_zflag) : "memory");
                            if (__all_sync(~0u, v * 8 == ep8() + 8)) break;
                        }
                    }
                    __syncwarp();
                }
                const uint32_t pp = lds32(ad(t * 4, prow + ((e + 6) & 15) * 16), SM_PART + 256);
                mbar_wait(SM_CBAR + bar * 8, par);
                uint4 v[6];
                load_v(v, (warp & 3) * SUB + slot * HT, SM_RING);
                if (e < 15) refill(false);
                advance();
                pv(v, pp);
            }
        }
        tail_prep1(IC<0>{});
        __syncwarp();
    }
}

typedef CUresult (*EncodeFn)(CUtensorMap*, CUtensorMapDataType, cuuint32_t, void*, const cuuint64_t*, const cuuint64_t*, const cuuint32_t*,
                             const cuuint32_t*, CUtensorMapInterleave, CUtensorMapSwizzle, CUtensorMapL2promotion, CUtensorMapFloatOOBfill);

}

extern "C" void kernel_launch(void* const* d_in, const int* in_sizes, int n_in, void* d_out, int out_size) {
    (void)in_sizes; (void)n_in; (void)out_size;
    static EncodeFn enc = nullptr;
    if (!enc) {
        void* fn = nullptr;
        cudaDriverEntryPointQueryResult qr;
        cudaGetDriverEntryPoint("cuTensorMapEncodeTiled", &fn, cudaEnableDefault, &qr);
        enc = (EncodeFn)fn;
        cudaFuncSetAttribute(fused_kernel, cudaFuncAttributeMaxDynamicSharedMemorySize, SM_TOTAL);
    }
    Params P;
    const cuuint32_t ones[3] = {1, 1, 1};
    for (int m = TM_K; m <= TM_V8; m++) {
        const cuuint64_t dim[3] = {64, 3, (cuuint64_t)NHEAD * SK}, str[2] = {128, DH * 2};
        const cuuint32_t box[3] = {m == TM_VP ? 8u : 64u, 3, m == TM_V8 ? 8u : 32u};
        enc(&P.tm[m], CU_TENSOR_MAP_DATA_TYPE_BFLOAT16, 3, d_in[m == TM_K ? 1 : 2], dim, str, box, ones, CU_TENSOR_MAP_INTERLEAVE_NONE,
            m == TM_VP ? CU_TENSOR_MAP_SWIZZLE_NONE : CU_TENSOR_MAP_SWIZZLE_128B, CU_TENSOR_MAP_L2_PROMOTION_NONE, CU_TENSOR_MAP_FLOAT_OOB_FILL_NONE);
    }
    {
        const cuuint64_t dim[3] = {64, NHEAD * 3, D_MODEL}, str[2] = {128, NHEAD * DH * 2};
        const cuuint32_t box[3] = {64, 3, 32};
        enc(&P.tm[TM_WQ], CU_TENSOR_MAP_DATA_TYPE_BFLOAT16, 3, d_in[3], dim, str, box, ones, CU_TENSOR_MAP_INTERLEAVE_NONE,
            CU_TENSOR_MAP_SWIZZLE_128B, CU_TENSOR_MAP_L2_PROMOTION_NONE, CU_TENSOR_MAP_FLOAT_OOB_FILL_NONE);
    }
    {
        const cuuint64_t dim[2] = {DFF, D_MODEL}, str[1] = {DFF * 2};
        const cuuint32_t box[2] = {16, 128};
        enc(&P.tm[TM_W1], CU_TENSOR_MAP_DATA_TYPE_BFLOAT16, 2, d_in[6], dim, str, box, ones, CU_TENSOR_MAP_INTERLEAVE_NONE,
            CU_TENSOR_MAP_SWIZZLE_32B, CU_TENSOR_MAP_L2_PROMOTION_L2_128B, CU_TENSOR_MAP_FLOAT_OOB_FILL_NONE);
    }
    {
        const cuuint64_t dim[3] = {32, 20, NHEAD * DH}, str[2] = {64, D_MODEL * 2};
        const cuuint32_t box[3] = {32, 5, 16};
        enc(&P.tm[TM_WO], CU_TENSOR_MAP_DATA_TYPE_BFLOAT16, 3, d_in[4], dim, str, box, ones, CU_TENSOR_MAP_INTERLEAVE_NONE,
            CU_TENSOR_MAP_SWIZZLE_64B, CU_TENSOR_MAP_L2_PROMOTION_L2_128B, CU_TENSOR_MAP_FLOAT_OOB_FILL_NONE);
    }
    {
        const cuuint64_t dim[4] = {32, 20, 24, NHEAD * 8}, str[3] = {64, D_MODEL * 2, 24 * D_MODEL * 2};
        const cuuint32_t box[4] = {32, 5, 8, 4}, ones4[4] = {1, 1, 1, 1};
        enc(&P.tm[TM_WO4], CU_TENSOR_MAP_DATA_TYPE_BFLOAT16, 4, d_in[4], dim, str, box, ones4, CU_TENSOR_MAP_INTERLEAVE_NONE,
            CU_TENSOR_MAP_SWIZZLE_64B, CU_TENSOR_MAP_L2_PROMOTION_L2_128B, CU_TENSOR_MAP_FLOAT_OOB_FILL_NONE);
        const cuuint32_t thin[4] = {8, 5, 8, 4};
        enc(&P.tm[TM_WOP], CU_TENSOR_MAP_DATA_TYPE_BFLOAT16, 4, d_in[4], dim, str, thin, ones4, CU_TENSOR_MAP_INTERLEAVE_NONE,
            CU_TENSOR_MAP_SWIZZLE_NONE, CU_TENSOR_MAP_L2_PROMOTION_NONE, CU_TENSOR_MAP_FLOAT_OOB_FILL_NONE);
    }
    {
        const cuuint64_t dim[3] = {64, 10, DFF}, str[2] = {128, D_MODEL * 2};
        const cuuint32_t box[3] = {64, 10, 16};
        enc(&P.tm[TM_W2], CU_TENSOR_MAP_DATA_TYPE_BFLOAT16, 3, d_in[8], dim, str, box, ones, CU_TENSOR_MAP_INTERLEAVE_NONE,
            CU_TENSOR_MAP_SWIZZLE_128B, CU_TENSOR_MAP_L2_PROMOTION_NONE, CU_TENSOR_MAP_FLOAT_OOB_FILL_NONE);
    }
    P.x = (const __nv_bfloat16*)d_in[0];
    P.k = (const __nv_bfloat16*)d_in[1];
    P.v = (const __nv_bfloat16*)d_in[2];
    P.b1 = (const __nv_bfloat16*)d_in[7];
    P.b2 = (const __nv_bfloat16*)d_in[9];
    P.out = (__nv_bfloat16*)d_out;
    fused_kernel<<<NCTA + 1, NTHR, SM_TOTAL, cudaStreamPerThread>>>(P);
}
```

```cpp
#include <cuda_runtime.h>
#include <cuda_bf16.h>
#include <cuda.h>
#include <stdint.h>

#define DI __device__ __forceinline__

namespace {

constexpr int D_MODEL = 640, NHEAD = 32, SK = 32768, DH = 192, WIN = 4096, DFF = 1536;
constexpr int NCTA = 128, NTHR = 256;
constexpr int SUB = 8 * DH * 2;
constexpr int HT = 4 * SUB;
constexpr int WOU = 8 * 320;
constexpr int XCAP = 48;
constexpr int SM_RING = 1024;
constexpr int SM_W2 = SM_RING + 8 * WOU;
constexpr int SM_WQ = SM_RING + 5 * HT;
constexpr int SM_KS = SM_WQ + 5 * HT;
constexpr int SM_PART = SM_KS + 8 * HT;
constexpr int SM_BAR = SM_PART + 6144;
constexpr int SM_VEC = SM_BAR + 512;
constexpr int SM_QU = SM_VEC + 384;
constexpr int SM_ZQ = SM_QU + 384;
constexpr int SM_CS = SM_ZQ + 64;
constexpr int SM_XR = SM_CS + 768;
constexpr int SM_XM = SM_XR + XCAP * 16;
constexpr int SM_SH = SM_XM + XCAP * 4;
constexpr int SM_C1 = SM_SH + 1024;
constexpr int SM_B1 = SM_C1 + 320;
constexpr int SM_STAT = SM_B1 + 128;
constexpr int SM_QBAR = SM_STAT + 40;
constexpr int SM_CBAR = SM_QBAR + 8;
constexpr int SM_CNT = SM_CBAR + 128;
constexpr int SM_XN = SM_CNT + 56;
constexpr int SM_BIG = SM_XN + 4;
constexpr int SM_EPOCH = SM_BIG + 4;
constexpr int SM_FXS = SM_EPOCH + 4;
constexpr int SM_T0 = SM_FXS + 4;
constexpr int SM_JUNK = SM_T0 + 4;
constexpr int SM_TOTAL = 232448;
static_assert(SM_JUNK + 4 <= SM_RING + SM_TOTAL, "smem");

constexpr int SPIN = 1 << 20;
enum { TM_WQ = 0, TM_K = 1, TM_V = 2, TM_VP = 3, TM_V8 = 4, TM_WO = 5, TM_W1 = 6, TM_WO4 = 7, TM_W2 = 8, TM_WOP = 9 };
constexpr uint32_t POL_NORMAL = 0x16F00000u, POL_FIRST = 0x12F00000u;

constexpr int PACE = 485, PACE0 = 1700, WOPACE = 403, W1D = 100, W1G = 150, HZD = 9500;
constexpr int NP = 3, PUBAT = 8, ZCHK = 14;
constexpr int ODELAY = 200, AR1D = 600, AR1DN = 1000, AR2D = 600, S6D = 900, S6G = 200, I0D = 300, KAD = 900;
constexpr unsigned long long VORD = 0xba6594327180cdefull;
constexpr int ISS = 0xf9e, NPK = 4, PK0 = 34, PK1 = 52, PKD = 21, P2A = -400, P2B = 380, P2W = 5500;
constexpr int PREP1 = 10, PREP2 = 10, PV2 = 7, HWAT = 8, PVNOW = 11, HWC = 11;
constexpr uint32_t FX2_MASK = 0xfff00000u;

struct Plan { int slot[17], par[17], ld[15]; bool ok; };
__host__ __device__ constexpr int cord(int s) { return s < 2 ? s : s + 1; }
constexpr Plan make_plan() {
    Plan s{};
    int phase[7] = {}, freeat[7] = {}, it = 7;
    for (int p = 0; p < 7; p++) { s.slot[p] = p; phase[p] = p != 1; freeat[p] = -1; }
    s.ok = true;
    for (int st = 0; st < 15; st++) {
        if (ISS >> st & 1) {
            int best = -1;
            for (int c = 0; c < 7; c++) if (freeat[c] >= 0 && (c < 5 || it < 13) && (best < 0 || freeat[c] < freeat[best])) best = c;
            if (best < 0 || it > 15) { s.ok = false; return s; }
            s.slot[it] = best; freeat[best] = -1;
            s.par[it] = phase[best]++ & 1;
            s.ld[st] = it++;
        }
        if (cord(st) >= it || (st >= 12 && s.slot[cord(st)] >= 5)) s.ok = false;
        freeat[s.slot[cord(st)]] = st;
    }
    s.slot[16] = 5; s.par[16] = phase[5] & 1;
    return s;
}
constexpr Plan PL = make_plan();
static_assert(PL.ok && PK0 < 40, "bad pass-2 plan");
__host__ __device__ constexpr int vunit(int p) { return (int)(VORD >> (4 * p) & 15); }

template <int I> struct IC { static constexpr int value = I; };
template <int A, int B, class F> DI void static_for(F&& f) {
    if constexpr (A < B) { f(IC<A>{}); static_for<A + 1, B>(f); }
}

struct Params {
    CUtensorMap tm[10];
    const __nv_bfloat16 *x, *b1, *b2, *k, *v;
    __nv_bfloat16* out;
};

typedef unsigned long long u64;
constexpr int ACC_PITCH = 256;
constexpr int ACC_BYTES = 80 * ACC_PITCH;
__device__ __align__(1024) unsigned char g_acc[4 * ACC_BYTES];
__device__ __align__(8192) u64 g_ll[NCTA][256];
__device__ unsigned g_epoch;
__device__ __align__(128) unsigned g_zflag;

DI void mbar_wait(uint32_t bar, uint32_t parity) {
    asm volatile("{\n.reg .pred p, q;\n.reg .u32 n;\nmov.u32 n, 0;\n"
                 "LOOP:\nmbarrier.try_wait.parity.shared::cta.b64 p, [%0], %1;\n"
                 "add.u32 n, n, 1;\nsetp.lt.and.u32 q, n, 0x100000, !p;\n@q bra.uni LOOP;\n}"
                 :: "r"(bar), "r"(parity) : "memory");
}
DI bool mbar_test(uint32_t bar, uint32_t parity) {
    uint32_t done;
    asm volatile("{\n.reg .pred p;\nmbarrier.test_wait.parity.shared::cta.b64 p, [%1], %2;\nselp.u32 %0, 1, 0, p;\n}" : "=r"(done) : "r"(bar), "r"(parity) : "memory");
    return __any_sync(~0u, done);
}
DI bool elect() {
    uint32_t r;
    asm volatile("{\n.reg .pred p;\nelect.sync _|p, 0xffffffff;\nselp.u32 %0, 1, 0, p;\n}" : "=r"(r));
    return r != 0;
}
DI void mbar_init(uint32_t bar, uint32_t n) { asm volatile("mbarrier.init.shared::cta.b64 [%0], %1;" :: "r"(bar), "r"(n) : "memory"); }
DI void mbar_arrive(uint32_t bar) { asm volatile("mbarrier.arrive.shared::cta.b64 _, [%0];" :: "r"(bar) : "memory"); }
DI void mbar_expect(uint32_t bar, uint32_t bytes) {
    asm volatile("mbarrier.arrive.expect_tx.shared::cta.b64 _, [%0], %1;" :: "r"(bar), "r"(bytes) : "memory");
}
DI void fence_gpu() { asm volatile("fence.acq_rel.gpu;" ::: "memory"); }
DI void fence_async() { asm volatile("fence.proxy.async.shared::cta;" ::: "memory"); }
DI uint32_t ad(uint32_t a, uint32_t o) { uint32_t r; asm("add.u32 %0, %1, %2;" : "=r"(r) : "r"(a), "r"(o)); return r; }
DI uint4 lds128(uint32_t a, int o) {
    uint4 v; asm volatile("ld.shared.v4.u32 {%0,%1,%2,%3}, [%4];" : "=r"(v.x), "=r"(v.y), "=r"(v.z), "=r"(v.w) : "r"(ad(a, o)) : "memory"); return v;
}
DI void lds128(uint32_t* v, uint32_t a, int o) {
    asm volatile("ld.shared.v4.u32 {%0,%1,%2,%3}, [%4];" : "=r"(v[0]), "=r"(v[1]), "=r"(v[2]), "=r"(v[3]) : "r"(ad(a, o)) : "memory");
}
DI void lds64(uint32_t* v, uint32_t a, int o) { asm volatile("ld.shared.v2.u32 {%0,%1}, [%2];" : "=r"(v[0]), "=r"(v[1]) : "r"(ad(a, o)) : "memory"); }
DI uint4 ldsm_t(uint32_t a, int o) {
    uint4 v; asm volatile("ldmatrix.sync.aligned.m8n8.x4.trans.shared.b16 {%0,%1,%2,%3}, [%4];" : "=r"(v.x), "=r"(v.y), "=r"(v.z), "=r"(v.w) : "r"(ad(a, o)) : "memory"); return v;
}
DI uint2 lds64(uint32_t a, int o) { uint2 v; asm volatile("ld.shared.v2.u32 {%0,%1}, [%2];" : "=r"(v.x), "=r"(v.y) : "r"(ad(a, o)) : "memory"); return v; }
DI float2 lds64f(uint32_t a, int o) { const uint2 v = lds64(a, o); return make_float2(__uint_as_float(v.x), __uint_as_float(v.y)); }
DI uint32_t lds32(uint32_t a, int o) { uint32_t v; asm volatile("ld.shared.u32 %0, [%1];" : "=r"(v) : "r"(ad(a, o)) : "memory"); return v; }
DI float ldsf(uint32_t a, int o) { return __uint_as_float(lds32(a, o)); }
DI void sts32(uint32_t a, int o, uint32_t v) { asm volatile("st.shared.u32 [%0], %1;" :: "r"(ad(a, o)), "r"(v) : "memory"); }
DI void stsf(uint32_t a, int o, float v) { sts32(a, o, __float_as_uint(v)); }
DI void sts16(uint32_t a, int o, uint32_t v) { asm volatile("st.shared.u16 [%0], %1;" :: "r"(ad(a, o)), "h"((uint16_t)v) : "memory"); }
DI void sts64(uint32_t a, int o, uint32_t x, uint32_t y) { asm volatile("st.shared.v2.u32 [%0], {%1,%2};" :: "r"(ad(a, o)), "r"(x), "r"(y) : "memory"); }
DI void sts128(uint32_t a, int o, uint32_t x, uint32_t y, uint32_t z, uint32_t w) {
    asm volatile("st.shared.v4.u32 [%0], {%1,%2,%3,%4};" :: "r"(ad(a, o)), "r"(x), "r"(y), "r"(z), "r"(w) : "memory");
}
DI void sts128f_if(bool p, uint32_t a, int o, float x, float y, float z, float w) {
    asm volatile("{\n.reg .pred p;\nsetp.ne.u32 p, %5, 0;\n@p st.shared.v4.f32 [%0], {%1,%2,%3,%4};\n}" :: "r"(ad(a, o)), "f"(x), "f"(y), "f"(z), "f"(w), "r"((int)p) : "memory");
}
DI void sts32_if(bool p, uint32_t a, int o, uint32_t v) {
    asm volatile("{\n.reg .pred p;\nsetp.ne.u32 p, %2, 0;\n@p st.shared.u32 [%0], %1;\n}" :: "r"(ad(a, o)), "r"(v), "r"((int)p) : "memory");
}
DI uint32_t atoms_inc(uint32_t a, uint32_t lim) {
    uint32_t old; asm volatile("atom.relaxed.cta.shared.inc.u32 %0, [%1], %2;" : "=r"(old) : "r"(a), "r"(lim) : "memory"); return old;
}
DI void mma(float (&c)[4], uint32_t a0, uint32_t a1, uint32_t a2, uint32_t a3, uint32_t b0, uint32_t b1) {
    asm volatile("mma.sync.aligned.m16n8k16.row.col.f32.bf16.bf16.f32 {%0,%1,%2,%3}, {%4,%5,%6,%7}, {%8,%9}, {%0,%1,%2,%3};"
                 : "+f"(c[0]), "+f"(c[1]), "+f"(c[2]), "+f"(c[3]) : "r"(a0), "r"(a1), "r"(a2), "r"(a3), "r"(b0), "r"(b1));
}
DI void mma(float (&c)[4], const uint4& a, uint32_t b0, uint32_t b1) { mma(c, a.x, a.y, a.z, a.w, b0, b1); }
DI void zero4(float (&c)[4]) { c[0] = c[1] = c[2] = c[3] = 0.f; }
DI u64 ld_rlx(const void* p) {
    u64 a; asm volatile("ld.relaxed.gpu.global.u64 %0, [%1];" : "=l"(a) : "l"(p) : "memory"); return a;
}
DI void st_rlx(void* p, u64 a) { asm volatile("st.relaxed.gpu.global.u64 [%0], %1;" :: "l"(p), "l"(a) : "memory"); }
DI uint4 ldg128(const void* p) {
    uint4 v; asm volatile("ld.global.nc.L1::no_allocate.L2::cache_hint.v4.u32 {%0,%1,%2,%3}, [%4], %5;" : "=r"(v.x), "=r"(v.y), "=r"(v.z), "=r"(v.w) : "l"(p), "l"((u64)POL_FIRST << 32)); return v;
}
DI float bf_lo(uint32_t u) { return __uint_as_float(u << 16); }
DI float bf_hi(uint32_t u) { return __uint_as_float(u & 0xffff0000u); }
DI uint32_t pack_bf(float lo, float hi) {
    uint32_t r; asm("cvt.rn.bf16x2.f32 %0, %1, %2;" : "=r"(r) : "f"(hi), "f"(lo)); return r;
}
DI uint32_t pick(uint32_t a, uint32_t sel) { uint32_t r; asm("prmt.b32 %0, %1, 0, %2;" : "=r"(r) : "r"(a), "r"(sel)); return r; }
DI uint32_t bf2_amax(uint32_t a, uint32_t b) { uint32_t r; asm("max.NaN.xorsign.abs.bf16x2 %0, %1, %2;" : "=r"(r) : "r"(a), "r"(b)); return r; }
DI uint32_t bf2_amin(uint32_t a, uint32_t b) { uint32_t r; asm("min.xorsign.abs.bf16x2 %0, %1, %2;" : "=r"(r) : "r"(a), "r"(b)); return r; }
DI uint32_t bf2_mulv(uint32_t a, uint32_t b) { uint32_t r; asm volatile("mul.rn.bf16x2 %0, %2, %1;" : "=r"(r) : "r"(a), "r"(b)); return r; }
DI uint32_t bf2_mul(uint32_t a, uint32_t b) { uint32_t r; asm("mul.rn.bf16x2 %0, %1, %2;" : "=r"(r) : "r"(a), "r"(b)); return r; }
DI uint32_t bf2_fma(uint32_t a, uint32_t b, uint32_t c) { uint32_t r; asm("fma.rn.bf16x2 %0, %1, %2, %3;" : "=r"(r) : "r"(a), "r"(b), "r"(c)); return r; }
DI float ex2(float v) { float r; asm("ex2.approx.ftz.f32 %0, %1;" : "=f"(r) : "f"(v)); return r; }
DI float rcp(float v) { float r; asm("rcp.approx.ftz.f32 %0, %1;" : "=f"(r) : "f"(v)); return r; }
DI float rsq(float v) { float r; asm("rsqrt.approx.ftz.f32 %0, %1;" : "=f"(r) : "f"(v)); return r; }
DI void bar_sync(int id, int n) { asm volatile("bar.sync %0, %1;" :: "r"(id), "r"(n) : "memory"); }
DI uint32_t clk() { uint32_t c; asm volatile("mov.u32 %0, %clock;" : "=r"(c)); return c; }
DI uint32_t gtime() { uint32_t c; asm volatile("mov.u32 %0, %globaltimer_lo;" : "=r"(c)); return c; }
DI uint32_t pin(uint32_t v) { return __shfl_xor_sync(~0u, v, 0); }
DI float pinf(float v) { return __shfl_xor_sync(~0u, v, 0); }
template <class T> DI T* pinp(T* p) { return reinterpret_cast<T*>(__shfl_xor_sync(~0u, (u64)p, 0)); }
DI u64 mk64(uint32_t lo, uint32_t hi) { u64 r; asm("mov.b64 %0, {%1, %2};" : "=l"(r) : "r"(lo), "r"(hi)); return r; }
DI float shx(float v, int o) { return __shfl_xor_sync(~0u, v, o); }

DI u64 fx_pack(float v) {
    u64 r; asm("{\n.reg .u32 a, b;\n.reg .s64 w;\ncvt.rni.s64.f32 w, %1;\nmov.b64 {a, b}, w;\nprmt.b32 a, a, 1, 0x3214;\nmov.b64 %0, {a, b};\n}" : "=l"(r) : "f"(v)); return r;
}
DI float fx_scale(float meansq) {
    const int e = max(((int)(__float_as_uint(meansq) >> 23) - 127) >> 1, -14);
    return __uint_as_float((uint32_t)(127 + 32 - e) << 23);
}
DI float fx_inv(float scale) { return __uint_as_float((254u << 23) - __float_as_uint(scale)); }
DI uint32_t lo32(u64 w) { uint32_t l; asm("mov.b64 {%0, _}, %1;" : "=r"(l) : "l"(w)); return l; }
DI int hi32(u64 w) { int h; asm("mov.b64 {_, %0}, %1;" : "=r"(h) : "l"(w)); return h; }
DI float fx_val(u64 w) { return (float)hi32(w) * 4294967296.f + (float)lo32(w); }
DI void fx_poll(const unsigned char* ap, u64 (&w)[4]) {
    asm volatile("{\n.reg .pred p, q;\n.reg .u32 n, a, b, c, d;\nmov.u32 n, 0;\nLOOP:\n"
                 "ld.relaxed.gpu.global.u64 %0, [%4];\nld.relaxed.gpu.global.u64 %1, [%4+5120];\n"
                 "ld.relaxed.gpu.global.u64 %2, [%4+10240];\nld.relaxed.gpu.global.u64 %3, [%4+15360];\n"
                 "add.u32 n, n, 1;\nsetp.ge.u32 q, n, 0x100000;\n@q bra.uni DONE;\n"
                 "mov.b64 {a, _}, %0;\nmov.b64 {b, _}, %1;\nmov.b64 {c, _}, %2;\nmov.b64 {d, _}, %3;\n"
                 "lop3.b32 a, a, b, c, 0x80;\nlop3.b32 a, a, d, 32, 0x80;\nsetp.eq.u32 p, a, 0;\n"
                 "vote.sync.any.pred p, p, 0xffffffff;\n@p bra.uni LOOP;\nDONE:\n}"
                 : "=l"(w[0]), "=l"(w[1]), "=l"(w[2]), "=l"(w[3]) : "l"(ap) : "memory");
}
constexpr u64 FX2_INIT = 256ull + 32 - 96 * ((1ull << 28) + (1ull << 55)), FX2_NONE = 1ull + (1ull << 28) + (1ull << 55);
constexpr float FX2_MAGIC = 12582912.f + 524288.f;

DI void tma3(uint32_t dst, const CUtensorMap* tm, int c1, int c2, uint32_t bar, uint32_t pol) {
    asm volatile("cp.async.bulk.tensor.3d.shared::cluster.global.mbarrier::complete_tx::bytes.L2::cache_hint [%0], [%1, {%2, %3, %4}], [%5], %6;"
                 :: "r"(dst), "l"(tm), "r"(0), "r"(c1), "r"(c2), "r"(bar), "l"((u64)pol << 32) : "memory");
}
DI void tma3_pf(const CUtensorMap* tm, int c1, int c2, uint32_t pol) {
    asm volatile("cp.async.bulk.prefetch.tensor.3d.L2.global.tile.L2::cache_hint [%0, {%1, %2, %3}], %4;"
                 :: "l"(tm), "r"(0), "r"(c1), "r"(c2), "l"((u64)pol << 32) : "memory");
}
DI void bulk_pf(const void* p, uint32_t bytes, uint32_t pol) {
    asm volatile("cp.async.bulk.prefetch.L2.global.L2::cache_hint [%0], %1, %2;" :: "l"(p), "r"(bytes), "l"((u64)pol << 32) : "memory");
}
DI float warp_max(float v) {
    const int k = __float_as_int(v), m = __reduce_max_sync(~0u, k ^ ((k >> 31) & 0x7fffffff));
    return __int_as_float(m ^ ((m >> 31) & 0x7fffffff));
}
DI u64 ll_pack2(float a, float b, uint32_t tag) { return mk64(__byte_perm(__float_as_uint(a), tag, 0x3214), __float_as_uint(b)); }
DI float lof(u64 w) { return __uint_as_float(lo32(w)); }
DI float hif(u64 w) { return __int_as_float(hi32(w)); }
DI void ll_gather4(const u64* buf, uint32_t tag, u64 (&w)[4]) {
#pragma unroll 1
    for (int it = 0; it < SPIN; it++) {
        if (it) { w[0] = ld_rlx(buf); w[1] = ld_rlx(buf + 256); w[2] = ld_rlx(buf + 512); w[3] = ld_rlx(buf + 768); }
        if (!__any_sync(~0u, (((lo32(w[0]) ^ tag) | (lo32(w[1]) ^ tag)) | ((lo32(w[2]) ^ tag) | (lo32(w[3]) ^ tag))) & 255)) break;
    }
}
DI u64 lds_u64(uint32_t a, int o) { const uint2 v = lds64(a, o); return v.x | (u64)v.y << 32; }
DI float sum8(uint32_t a, int o, int pitch) {
    float s[8];
#pragma unroll
    for (int w = 0; w < 8; w++) s[w] = ldsf(a, o + w * pitch);
    return ((s[0] + s[1]) + (s[2] + s[3])) + ((s[4] + s[5]) + (s[6] + s[7]));
}
DI void ln_final(float& mean, float& rstd, float& msq) {
    float2 v[5];
#pragma unroll
    for (int w = 0; w < 5; w++) v[w] = lds64f(0, SM_STAT + w * 8);
    mean = (((v[0].x + v[1].x) + (v[2].x + v[3].x)) + v[4].x) * (1.f / D_MODEL);
    msq = (((v[0].y + v[1].y) + (v[2].y + v[3].y)) + v[4].y) * (1.f / D_MODEL);
    rstd = rsq(fmaxf(msq - mean * mean, 0.f) + 1e-5f);
}
constexpr float CS = 0.07216878364870322f * 1.4426950408889634f;
constexpr uint32_t ONES = 0x3f803f80u;

__global__ void __launch_bounds__(NTHR, 1) fused_kernel(const __grid_constant__ Params P) {
    extern __shared__ __align__(1024) unsigned char smem[];
    const int warp = __shfl_sync(~0u, threadIdx.x >> 5, 0), bx = blockIdx.x;
    const int cta = (((bx >> 1) & 15) + (bx >> 6) * 16) * 4 + ((bx >> 5) & 1) * 2 + (bx & 1);

    if (bx == NCTA) {
        if ((uint32_t)__cvta_generic_to_shared(smem) != SM_RING) __trap();
        const uint32_t ep = *(volatile unsigned*)&g_epoch;
        if (threadIdx.x == 0) {
#pragma unroll 1
            for (int it = 0; it < SPIN; it++) { if ((lo32(ld_rlx(&g_ll[0][192])) & 255) == ((ep * 8 + 1) & 255)) break; __nanosleep(200); }
            const uint32_t t0 = gtime();
#pragma unroll 1
            for (int it = 0; it < 1024; it++) { if (gtime() - t0 > HZD) break; __nanosleep(100); }
        }
        __syncthreads();
#pragma unroll 1
        for (int i = threadIdx.x; i < 4 * 80 * 8; i += NTHR)
        {
            const u64 v = (i / 640 & 1) && (i & 7) < 2 ? FX2_INIT : 0ull;
            *reinterpret_cast<ulonglong2*>(g_acc + (i >> 3) * ACC_PITCH + (i & 7) * 16) = make_ulonglong2(v, v);
        }
        __threadfence();
        __syncthreads();
        if (threadIdx.x == 0) asm volatile("st.relaxed.gpu.global.u32 [%0], %1;" :: "l"(&g_zflag), "r"(ep + 1) : "memory");
        return;
    }
    const uint32_t barw = SM_BAR + warp * 64;
    if (elect()) {
        if (warp < 3) sts32(0, SM_T0, gtime());
        else {
            mbar_init(barw + 56, 1);
            asm volatile("fence.mbarrier_init.release.cluster;" ::: "memory");
            mbar_expect(barw + 56, HT);
            tma3(SM_WQ - 3 * HT + warp * HT, &P.tm[TM_WQ], (cta >> 2) * 3, (cta & 3) * 160 - 96 + warp * 32, barw + 56, POL_FIRST);
        }
    }
    int tid = threadIdx.x, lane, g, t, c4;
    uint32_t selA, selB, offV0, offV2;
    auto derive = [&]() {
        lane = tid & 31; g = lane >> 2; t = lane & 3;
        c4 = (tid & 0xe1) + 16 * (t >> 1) + 2 * g;
        selA = (g & 2) ? 0x4444u : (g & 1) ? 0x1044u : 0x4410u;
        selB = (g & 2) ? ((g & 1) ? 0x1044u : 0x4410u) : 0x4444u;
        offV0 = (6 * t) * 128 + ((g ^ ((6 * t) & 7)) << 4);
        offV2 = (6 * t) * 128 + ((g ^ ((6 * t + 2) & 7)) << 4);
    };
    auto refresh = [&]() { tid = pin(tid); derive(); };
    auto refresh_late = [&]() { mbar_wait(SM_BAR + 3 * 64 + 56, 0); refresh(); };
    derive();
    const uint32_t zero = bx >> 16;
    const int j40 = (cta & 3) * 40;
    const bool mlp = (cta & 3) != 3;
    const int hu = ((cta >> 2) * 3 + (cta & 3)) * 16;
    uint2 xp = make_uint2(0, 0);
    uint32_t kc[192];
    const int rowc = (cta >> 2) * SK + (SK - WIN) + (cta & 3) * 64;
    const int roww = __shfl_sync(~0u, rowc + warp * 8, 0);
    const CUtensorMap* tmk = reinterpret_cast<const CUtensorMap*>(__shfl_sync(~0u, (u64)&P.tm[0] + (lane >> 5), 0));

    auto wait_due = [&](int i, int extra) {
        const uint32_t due = lds32(0, SM_T0) + PACE0 + extra + i * PACE;
#pragma unroll 1
        for (int it = 0; it < 4096; it++) if ((int)(gtime() - due) >= 0) break;
    };
    auto issue_wo = [&](int k) {
        wait_due(64, k * WOPACE);
        mbar_expect(SM_CBAR + 32 + k * 8, 4 * WOU);
        asm volatile("cp.async.bulk.tensor.4d.shared::cluster.global.mbarrier::complete_tx::bytes.L2::cache_hint [%0], [%1, {%2, %3, %4, %5}], [%6], %7;"
                     :: "r"(SM_RING + k * 4 * WOU), "l"(tmk + TM_WO4), "r"(0), "r"(5 * (cta & 3)), "r"((k >> 1) * 8), "r"((cta >> 2) * 8 + (k & 1) * 4),
                        "r"(SM_CBAR + 32 + k * 8), "l"((u64)POL_FIRST << 32) : "memory");
        if (k < 4 && mlp)
            asm volatile("cp.async.bulk.prefetch.tensor.4d.L2.global.tile.L2::cache_hint [%0, {%1, %2, %3, %4}], %5;"
                         :: "l"(tmk + TM_WOP), "r"(0), "r"(5 * (cta & 3)), "r"((k >> 1) * 8), "r"((cta >> 2) * 8 + (k & 1) * 4), "l"((u64)POL_NORMAL << 32) : "memory");
    };
    auto issue_kv = [&](int i, int slot, int bar) {
        const int row = rowc + (i & 30) * 128 + (i & 1) * 32;
        mbar_expect(SM_CBAR + bar * 8, HT);
        tma3(SM_RING + slot * HT, tmk + TM_K + (i >> 5), 0, row, SM_CBAR + bar * 8, POL_FIRST);
        if (i >= 32) tma3_pf(tmk + TM_VP, 0, row, POL_NORMAL);
    };
    auto ep8 = [&]() { return lds32(0, SM_EPOCH); };
    auto load_v3 = [&](uint4* v, uint32_t u, int o, bool odd) {
        if (!odd) { v[0] = lds128(ad(offV0, u), o); v[1] = lds128(ad(offV0 ^ 16, u), o + 128); v[2] = lds128(ad(offV2, u), o + 256); }
        else { v[0] = lds128(ad(offV2 ^ 16, u), o + 384); v[1] = lds128(ad(offV0 ^ 64, u), o + 512); v[2] = lds128(ad(offV0 ^ 80, u), o + 640); }
    };
    auto load_v = [&](uint4 (&v)[6], uint32_t u, int o) { load_v3(v, u, o, false); load_v3(v + 3, u, o, true); };
    const uint32_t wqw = warp * SUB, ksw = warp * HT;
    auto slot_o = [&](int s) { return s < 3 ? SM_WQ + s * 8 * SUB : SM_KS + (s - 3) * SUB; };
    auto slot_u = [&](int s) { return s < 3 ? wqw : ksw; };
    auto issue2 = [&](auto I, uint32_t dep) {
        constexpr int p = I.value, s = PL.slot[p];
        __syncwarp();
        if ((p < 16 || mlp) && elect()) {
            mbar_expect(barw + s * 8, (dep & zero) | (p < 16 ? SUB : 2 * WOU + 256));
            if constexpr (p < 16) tma3(slot_u(s) + slot_o(s), tmk + TM_V8, 0, roww + vunit(p) * 256, barw + s * 8, POL_FIRST);
            else {
                tma3(slot_u(s) + slot_o(s), tmk + TM_WO, 5 * (cta & 3), (cta >> 2) * DH + warp * 24, barw + s * 8, POL_FIRST);
                asm volatile("cp.async.bulk.shared::cluster.global.mbarrier::complete_tx::bytes [%0], [%1], 256, [%2];"
                             :: "r"(slot_u(s) + slot_o(s) + 2 * WOU), "l"(P.b2 + min(warp, 4) * 128), "r"(barw + s * 8) : "memory");
            }
        }
    };
    auto touch2 = [&]() {
        const char* p = reinterpret_cast<const char*>(P.v) + (size_t)(roww + vunit(2) * 256) * (DH * 2) + lane * 32;
#pragma unroll
        for (int i = 0; i < 3; i++) asm volatile("cp.async.ca.shared.global [%0], [%1], 4;" :: "r"(SM_JUNK), "l"(p + i * 1024) : "memory");
    };
    auto issue_help = [&]() {
        if (elect())
            tma3(SM_WQ + (warp == 7 ? 0 : warp == 6 ? 16 * SUB : 4 * SUB), tmk + (warp == 5 ? TM_V8 : TM_V), 0,
                 rowc + (warp == 6 ? vunit(2) * 256 : warp == 5 ? vunit(0) * 256 + 32 : vunit(0) * 256), warp == 5 ? SM_BAR + 4 * 64 : SM_CBAR - 32 + warp * 8, POL_FIRST);
    };
    auto issue_item1 = [&]() {
        if (elect()) {
            mbar_expect(SM_CBAR - 48 + warp * 8, HT);
            tma3(SM_WQ - 4 * HT + warp * HT, tmk + TM_V, 0, rowc - 192 + warp * 32 + vunit(1) * 256, SM_CBAR - 48 + warp * 8, POL_FIRST);
        }
    };
    const uint32_t prow = warp * 768;
    uint4 wq0[6], wqh[3];
    uint32_t xna;
    auto load_wq = [&]() {
        load_v(wq0, wqw, SM_WQ);
        const int r0 = 6 * t + 3 * (warp & 1);
#pragma unroll
        for (int j = 0; j < 3; j++) wqh[j] = lds128(ad(r0 * 128 + ((g ^ ((r0 + j) & 7)) << 4), (warp >> 1) * SUB), SM_WQ + 16 * SUB + j * 128);
        const int r = c4 - j40;
        xna = pin((tid < 160 && r >= 0 && r < 40) ? SM_VEC + r * 8 : 0u);
        selA = pin(selA); selB = pin(selB);
        offV0 = pin(offV0 + wqw); offV2 = pin(offV2 + wqw);
        tid = pin(tid);
    };
    float acc[3][4];
    auto mma3 = [&](const uint4* v, uint32_t pp, uint32_t hi) {
        const uint32_t b0 = pick(pp, selA | hi), b1 = pick(pp, selB | hi);
        mma(acc[0], v[0], b0, b1); mma(acc[1], v[1], b0, b1); mma(acc[2], v[2], b0, b1);
    };
    auto ln_part = [&]() {
        const float x0 = bf_lo(xp.x), x1 = bf_hi(xp.x), x2 = bf_lo(xp.y), x3 = bf_hi(xp.y);
        const float s1 = (x0 + x1) + (x2 + x3), s2 = (x0 * x0 + x1 * x1) + (x2 * x2 + x3 * x3);
        float ss = ((tid & 16) ? s2 : s1) + shx((tid & 16) ? s1 : s2, 16);
        ss += shx(ss, 8); ss += shx(ss, 4); ss += shx(ss, 2); ss += shx(ss, 1);
        sts32_if((tid & 15) == 0 && tid < 160, tid >> 2, SM_STAT, __float_as_uint(ss));
    };

    auto tick = [&](uint4& v) {
        asm volatile("{\n.reg .pred p;\nsetp.ne.u32 p, %4, 0;\n@p mma.sync.aligned.m16n8k16.row.col.f32.bf16.bf16.f32 {%0,%1,%2,%3}, {%0,%1,%2,%3}, {%0,%1}, {%0,%1,%2,%3};\n}"
                     : "+r"(v.x), "+r"(v.y), "+r"(v.z), "+r"(v.w) : "r"(zero));
    };

    auto q_stage = [&](auto L) {
        constexpr int layer = L.value;
        asm volatile("{\n.reg .pred p;\nsetp.ne.u32 p, %0, 0;\n@p st.shared.v2.u32 [%0], {%1,%2};\n}" :: "r"(xna), "r"(xp.x), "r"(xp.y) : "memory");
        uint4 wq1[6];
        load_v3(wq1, 0, SM_WQ + 8 * SUB, false);
        const uint32_t xra = (tid & 3) * 4;
        __syncthreads();
        uint32_t p0 = lds32(ad(xra, warp * 16), SM_VEC), ph = lds32(ad(xra, (warp >> 1) * 16), SM_VEC + 256), p1 = lds32(ad(xra, warp * 16), SM_VEC + 128);
        if (layer == 0 && (tid & 16)) p0 = p1 = ph = ONES;
#pragma unroll
        for (int j = 0; j < 3; j++) zero4(acc[j]);
        mma3(wq0, p0, 0); mma3(wq0 + 3, p0, 0x2222);
        load_v3(wq1 + 3, 0, SM_WQ + 8 * SUB, true);
        mma3(wqh, ph, (warp & 1) * 0x2222); mma3(wq1, p1, 0); mma3(wq1 + 3, p1, 0x2222);
        if (layer == 1) { lds128(kc + 8, prow + (tid & 31) * 16, SM_PART); lds64(kc + 180, prow + (tid & 31) * 8, SM_PART + 512); __syncwarp(); }
        const uint32_t qpa = ((layer == 0 && (tid & 2)) ? ksw - (SM_PART - SM_KS - 11264) : prow) + (tid & 28) * 8 + (tid & 1) * 16;
#pragma unroll
        for (int j = 0; j < 3; j++) sts128f_if(layer == 0 || !(tid & 2), qpa, SM_PART + j * 256, acc[j][0], acc[j][1], acc[j][2], acc[j][3]);
        u64* dst = &g_ll[cta][tid];
        const uint32_t tag = ep8() + 1 + 4 * layer;
        __syncthreads();
        if (warp < 6) {
            const float s = sum8(tid * 4, SM_PART, 768);
            st_rlx(dst, layer ? mk64(tag, __float_as_uint(s)) : ll_pack2(__uint_as_float(__float_as_uint(sum8(tid * 4, SM_KS + 11264, HT)) + 128), s, tag));
        } else if (layer == 1) { sts32(0, SM_T0, gtime()); issue_item1(); }
        refresh_late();
        ln_part();
        __syncthreads();
        sts64(prow + lane * 8, SM_PART, xp.x, xp.y);
        if (layer == 1) sts128(prow + lane * 16, SM_PART + 256, kc[8], kc[9], kc[10], kc[11]);
    };
    auto q_addr = [&]() { return (((tid >> 1) & 1) * 4 + ((tid >> 4) & 3)) * 48 + ((tid >> 6) * 2 + ((tid >> 3) & 1)) * 8 + ((tid >> 2) & 1) * 4 + (tid & 1) * 2; };
    auto score6 = [&](const uint4 (&v)[6], const uint32_t (&qf)[12]) {
        float d[2][4];
#pragma unroll
        for (int i = 0; i < 6; i++) { if (i < 2) zero4(d[i]); mma(d[i & 1], v[i], qf[2 * i], qf[2 * i + 1]); }
        return (d[0][0] + d[0][3]) + (d[1][0] + d[1][3]);
    };
    auto softmax = [&](auto L, const float (&S)[4]) {
        constexpr int layer = L.value;
        const float mrun = warp_max(fmaxf(fmaxf(S[0], S[1]), fmaxf(S[2], S[3])));
        const float p0 = ex2((S[0] - mrun) * CS), p1 = ex2((S[1] - mrun) * CS), p2 = ex2((S[2] - mrun) * CS), p3 = ex2((S[3] - mrun) * CS);
        const uint32_t pa = pack_bf(p0, p1), pb = pack_bf(p2, p3), pw = prow + t * 64 + g * 2;
        sts16(pw, SM_PART + 256, pa); sts16(pw, SM_PART + 272, pa >> 16); sts16(pw, SM_PART + 288, pb); sts16(pw, SM_PART + 304, pb >> 16);
        const uint32_t l = __reduce_add_sync(~0u, __float2uint_rn(((p0 + p1) + (p2 + p3)) * 16777216.f));
        st_rlx(&g_ll[cta][192 + warp], mk64(__byte_perm(l + 128, ep8() + 1 + 4 * layer, 0x3214), __float_as_uint(mrun)));
        __syncwarp();
#pragma unroll
        for (int j = 0; j < 3; j++) zero4(acc[j]);
    };
    auto pv = [&](const uint4 (&v)[6], uint32_t pp) { mma3(v, pp, 0); mma3(v + 3, pp, 0x2222); };

    auto head_look = [&]() {
        if (lane < 16) asm volatile("cp.async.cg.shared.global [%0], [%1], 16;" :: "r"(SM_PART + 512 + prow + lane * 16), "l"(&g_ll[cta ^ g][192 + 2 * t]) : "memory");
    };
    float fw;
    auto head_weight = [&](auto L) {
        const uint32_t tag = (ep8() + 1 + 4 * L.value) & 255;
        uint32_t l, m;
#pragma unroll 1
        for (int it = 0; it < SPIN; it++) {
            if (it) head_look();
            asm volatile("cp.async.wait_all;" ::: "memory");
            __syncwarp();
            asm volatile("ld.volatile.shared.v2.u32 {%0,%1}, [%2];" : "=r"(l), "=r"(m) : "r"(SM_PART + 512 + prow + lane * 8) : "memory");
            l ^= tag;
            if (!__any_sync(~0u, l & 255)) break;
        }
        const float f = ex2((__uint_as_float(m) - warp_max(__uint_as_float(m))) * CS);
        const uint32_t Lh = __reduce_add_sync(~0u, __float2uint_rn(f * (float)l * 0.03125f));
        fw = __shfl_sync(~0u, f, warp) * rcp((float)Lh) * (ldsf(0, SM_FXS) * 524288.f);
    };

    uint32_t wa[5], ya, oa, selC, selD, tag;
    uint4 z[5];
    unsigned char* ra;
    const u64* lp;
    auto load_u = [&](uint4 (&a)[5], uint32_t u, int o) {
#pragma unroll
        for (int k = 0; k < 5; k++) a[k] = lds128(ad(wa[k], u), o);
    };
    auto tail_prep1 = [&](auto L) {
        xp = lds64(prow + lane * 8, SM_PART);
        tag = (ep8() + 3 + 4 * L.value) & 255;
        ya = pin(prow + (8 * g + 4 * (t & 1)) * 4);
        oa = pin(((tid >> 5) * 12 + min(lane, 11)) * 8);
        lp = pinp(reinterpret_cast<const u64*>(reinterpret_cast<const char*>(&g_ll[cta][0]) + oa));
    };
    auto tail_prep2 = [&](auto L) {
#pragma unroll
        for (int k = 0; k < 5; k++) {
            const int row = (t & 1) + 2 * (t & 2) + 2 * (k < 4 ? k >> 1 : g >> 2), j = k < 4 ? 2 * (k & 1) + (g >> 2) : 4;
            wa[k] = pin(row * 320 + j * 64 + (((g & 3) ^ (((5 * row + j) >> 1) & 3)) << 4));
        }
        selA = pin(selA); selB = pin(selB);
        selC = selA | (g >> 2) * 0x2222; selD = selB | (g >> 2) * 0x2222;
    };
    auto red_addr = [&](auto L) {
        const int word = t * 160 + j40 + (tid >> 2);
        ra = pinp(g_acc + 2 * L.value * ACC_BYTES + (uint32_t)((word >> 3) * ACC_PITCH + (word & 7) * 8));
    };
    uint4 wf[8], w2r[8];
    uint32_t la, w2a, hpa, ha, *op;
    uint2 b2v;
    const unsigned char* ap;
    unsigned char* ap2;
    float inv1;
    auto load_w1 = [&]() {
#pragma unroll
        for (int j = 0; j < 8; j++) wf[j] = ldsm_t(la, SM_RING + j * 256);
    };
    auto load_w2 = [&]() {
#pragma unroll
        for (int i = 0; i < 8; i++) w2r[i] = lds128(w2a ^ ((i & 1) * 16), SM_W2 + (i >> 1) * 5120 + (i & 1) * 128);
    };
    auto load_b2 = [&]() { asm volatile("ld.global.nc.v2.u32 {%0,%1}, [%2];" : "=r"(b2v.x), "=r"(b2v.y) : "l"(P.b2 + 4 * min(c4, 159))); };
    auto mlp_prep = [&](auto L) {
        unsigned char* const accb = g_acc + 2 * L.value * ACC_BYTES;
        la = (tid >> 5) * 4096 + (64 * ((lane >> 2) & 1) + 4 * ((lane >> 1) & 1) + (lane & 1) + 2 * (lane >> 4)) * 32 + ((((lane >> 3) ^ (lane >> 1)) & 1) << 4);
        w2a = pin((10 * t + 2 * (tid >> 5)) * 128 + ((g ^ ((2 * t + 2 * (tid >> 5)) & 7)) << 4));
        hpa = pin((tid >> 5) * 64 + (t * 8 + g) * 4); ha = pin((lane & 15) * 4);
        if (L.value == 0) { selA = pin(selA); selB = pin(selB); tid = pin(tid); }
        ap = accb + (uint32_t)((c4 >> 3) * ACC_PITCH + (c4 & 7) * 8);
        ap2 = accb + ACC_BYTES + pin((c4 >> 2) * ACC_PITCH + (c4 & 3) * 8);
        if (L.value == 1) ap2 = pinp(ap2);
        inv1 = fx_inv(ldsf(0, SM_FXS));
        if (L.value == 1) { ap = pinp(ap); la = pin(la); op = pinp(reinterpret_cast<uint32_t*>(P.out) + 2 * c4); }
    };
    auto tail = [&](auto L) {
        constexpr int layer = L.value;
        uint32_t cq;
        auto park = [&]() { const int ln = pin(tid) & 31; sts128(prow + ln * 16, SM_PART, kc[8], kc[9], kc[10], kc[11]); sts64(prow + ln * 8, SM_PART + 512, kc[180], kc[181]); };
        {
#pragma unroll
            for (int j = 0; j < 3; j++) sts128f_if(!(tid & 2), ya, SM_PART + 256 * j, acc[j][0] * fw, acc[j][2] * fw, acc[j][1] * fw, acc[j][3] * fw);
            __syncthreads();
            float2 own;
            {
                float2 s[8];
#pragma unroll
                for (int w = 0; w < 8; w++) s[w] = lds64f(oa, SM_PART + w * 768);
                own.x = ((s[0].x + s[1].x) + (s[2].x + s[3].x)) + ((s[4].x + s[5].x) + (s[6].x + s[7].x));
                own.y = ((s[0].y + s[1].y) + (s[2].y + s[3].y)) + ((s[4].y + s[5].y) + (s[6].y + s[7].y));
                st_rlx(const_cast<u64*>(lp), ll_pack2(own.x, own.y, tag));
            }
            const uint32_t c0 = clk();
            if (layer == 0) refresh_late();
            uint4 v[5], u[5];
            if constexpr (layer == 0) {
                if (warp < 3) { if (elect()) issue_wo(3 + warp); __syncwarp(); }
                if (warp >= 4) touch2();
                tail_prep2(L);
                mbar_wait(SM_CBAR + 32 + (warp >> 2) * 8, 0);
                load_u(v, warp * WOU, SM_RING);
                __syncthreads();
            }
            constexpr int YP = layer ? SM_WQ : SM_PART;
            float y[3][4];
#pragma unroll
            for (int j = 0; j < 3; j++) zero4(y[j]);
            const u64 *l1 = reinterpret_cast<const u64*>((u64)lp ^ 4096), *l2 = reinterpret_cast<const u64*>((u64)lp ^ 2048), *l3 = reinterpret_cast<const u64*>((u64)lp ^ 6144);
            tick(layer ? z[0] : v[0]);
            if (layer) while (clk() - c0 < ODELAY);
            uint32_t w1due = 0;
            if (layer == 0) {
                const uint32_t now = gtime();
                w1due = lds32(0, SM_T0) + PACE0 + 69 * PACE + W1D;
                w1due = ((int)(now - w1due) > 0 ? now : w1due) + (warp - 3) * W1G;
            }
            u64 w1 = ld_rlx(l1), w2 = ld_rlx(l2), w3 = ld_rlx(l3);
            if constexpr (layer == 1) {
                if (mlp) mbar_wait(barw + 40, IC<PL.par[16]>::value);
                load_u(v, mlp ? ksw + slot_o(5) : SM_RING + warp * WOU, 0); load_u(u, mlp ? ksw + slot_o(5) + WOU : SM_RING + (8 + warp) * WOU, 0);
            }
            if (layer == 0 && warp >= 3 && mlp) {
#pragma unroll 1
                for (int it = 0; it < 4096; it++) { tick(v[0]); if ((int)(gtime() - w1due) >= 0) break; }
                if (elect()) {
                    mbar_expect(SM_CBAR + 56 + warp * 8, 4096);
                    asm volatile("cp.async.bulk.tensor.2d.shared::cluster.global.mbarrier::complete_tx::bytes.L2::cache_hint [%0], [%1, {%2, %3}], [%4], %5;"
                                 :: "r"(SM_RING + (warp - 3) * 4096), "l"(tmk + TM_W1), "r"(hu), "r"(warp * 128 - 384), "r"(SM_CBAR + 56 + warp * 8), "l"((u64)POL_FIRST << 32) : "memory");
                }
                __syncwarp();
            }
#pragma unroll 1
            for (int it = 0; it < SPIN; it++) {
                if (it) { w1 = ld_rlx(l1); w2 = ld_rlx(l2); w3 = ld_rlx(l3); }
                if (!__any_sync(~0u, ((lo32(w1) ^ tag) | (lo32(w2) ^ tag) | (lo32(w3) ^ tag)) & 255)) break;
            }
            const uint32_t od = pack_bf((own.x + __uint_as_float(lo32(w1) ^ tag)) + (__uint_as_float(lo32(w2) ^ tag) + __uint_as_float(lo32(w3) ^ tag)),
                                        (own.y + __int_as_float(hi32(w1))) + (__int_as_float(hi32(w2)) + __int_as_float(hi32(w3))));
            const uint32_t o0 = __shfl_sync(~0u, od, tid & 3), o1 = __shfl_sync(~0u, od, (tid & 3) + 4), o2 = __shfl_sync(~0u, od, (tid & 3) + 8);
            auto narrow = [&](const uint4 (&a)[5], uint32_t o) { mma(y[2], a[4], pick(o, selC), pick(o, selD)); };
            auto wide = [&](const uint4 (&a)[5], uint32_t o) {
                const uint32_t b0 = pick(o, selA), b1 = pick(o, selB), b2 = pick(o, selA | 0x2222), b3 = pick(o, selB | 0x2222);
                mma(y[0], a[0], b0, b1); mma(y[1], a[1], b0, b1); mma(y[0], a[2], b2, b3); mma(y[1], a[3], b2, b3);
            };
            narrow(v, o0); wide(v, o0);
            if constexpr (layer == 0) {
                mbar_wait(SM_CBAR + 48 + (warp >> 2) * 8, 0);
                load_u(u, warp * WOU, SM_RING + 8 * WOU);
                __syncwarp();
                if (mlp && elect() && atoms_inc(SM_CNT + 44, 7) == 7) { mbar_expect(SM_CBAR + 120, 20480); tma3(SM_W2, tmk + TM_W2, 0, hu, SM_CBAR + 120, POL_FIRST); }
                __syncwarp();
                narrow(u, o1); wide(u, o1);
                red_addr(L);
                mbar_wait(SM_CBAR + 64 + (warp >> 2) * 8, 0);
                load_u(z, warp * WOU, SM_RING + 16 * WOU);
                narrow(z, o2);
            } else { narrow(u, o1); narrow(z, o2); wide(u, o1); }
            wide(z, o2);
#pragma unroll
            for (int k = 0; k < 4; k++) y[2][k] += shx(y[2][k], 18);
            sts128f_if(!(tid & 18), ya, YP + 512, y[2][0], y[2][1], y[2][2], y[2][3]);
            sts128f_if(!(tid & 2), ya, YP, y[0][0], y[0][1], y[0][2], y[0][3]);
            sts128f_if(!(tid & 2), ya, YP + 256, y[1][0], y[1][1], y[1][2], y[1][3]);
            __syncthreads();
            if (warp < 5) {
                const float s = sum8(tid * 4, YP, 768);
                asm volatile("red.relaxed.gpu.global.add.u64 [%0], %1;" :: "l"(ra), "l"(fx_pack(s)) : "memory");
            }
            cq = clk();
            if (layer == 0) refresh_late();
        }
        if (layer == 1 && !mlp) return;
        if (warp < 5) {
            if (layer == 0) { mlp_prep(L); if (mlp) mbar_wait(SM_CBAR + 80 + warp * 8, 0); }
            load_w1();
            if (layer == 1) { load_w2(); b2v = lds64(ksw + (c4 & 31) * 8, SM_KS + 11264); }
            {
                u64 w[4];
                while (clk() - cq < (layer || mlp ? AR1D : AR1DN));
                fx_poll(ap, w);
                xp = make_uint2(pack_bf(bf_lo(xp.x) + fx_val(w[0]) * inv1, bf_hi(xp.x) + fx_val(w[1]) * inv1),
                                pack_bf(bf_lo(xp.y) + fx_val(w[2]) * inv1, bf_hi(xp.y) + fx_val(w[3]) * inv1));
            }
            {
                const bool ev = layer || !(tid & 4), od = layer || (tid & 4);
                const uint32_t e0 = ev ? xp.x : ONES, e1 = ev ? xp.y : ONES, o0 = od ? xp.x : ONES, o1 = od ? xp.y : ONES;
                float d[8][4];
#pragma unroll
                for (int j = 0; j < 8; j++) { zero4(d[j]); mma(d[j], wf[j], (j & 1) ? o0 : e0, (j & 1) ? o1 : e1); }
                float lo = d[0][0] + d[1][1], hi = d[0][2] + d[1][3];
#pragma unroll
                for (int m = 1; m < 4; m++)
                    asm("{\n.reg .pred p;\nsetp.eq.u32 p, %6, %7;\n@p add.f32 %0, %2, %3;\n@p add.f32 %1, %4, %5;\n}" : "+f"(lo), "+f"(hi)
                        : "f"(d[2 * m][0]), "f"(d[2 * m + 1][1]), "f"(d[2 * m][2]), "f"(d[2 * m + 1][3]), "r"(tid & 3), "r"(m));
                float dd = ((tid & 1) ? hi : lo) + shx((tid & 1) ? lo : hi, 1);
                dd += shx(dd, 2);
                ln_part();
                if (layer == 0) {
                    const float cl = ((d[0][1] + d[1][0]) + (d[2][1] + d[3][0])) + ((d[4][1] + d[5][0]) + (d[6][1] + d[7][0]));
                    const float ch = ((d[0][3] + d[1][2]) + (d[2][3] + d[3][2])) + ((d[4][3] + d[5][2]) + (d[6][3] + d[7][2]));
                    sts32_if(!(tid & 2), hpa, SM_C1, __float_as_uint((tid & 1) ? ch : cl));
                }
                sts32_if(!(tid & 2), hpa, SM_QU, __float_as_uint(dd));
            }
            const float b1v = ldsf(ha, SM_B1);
            float csum = layer ? ldsf(ha, SM_B1 + 64) : 0.f;
            bar_sync(1, layer ? 160 : 192);
            float mean, rstd, msq;
            ln_final(mean, rstd, msq);
            float hp[5];
#pragma unroll
            for (int w = 0; w < 5; w++) hp[w] = ldsf(ha, SM_QU + w * 64);
            if constexpr (layer == 0) {
                float c[5];
#pragma unroll
                for (int w = 0; w < 5; w++) c[w] = ldsf(ha, SM_C1 + w * 64);
                csum = ((c[0] + c[1]) + (c[2] + c[3])) + c[4];
                load_w2();
            }
            float hv = ((((hp[0] + hp[1]) + (hp[2] + hp[3])) + hp[4]) - mean * csum) * rstd + b1v;
            hv = hv * rcp(1.f + ex2(hv * (-2.302208198f - 0.1029432397f * hv * hv)));
            const uint32_t hd = pack_bf(hv, hv);
            float ym[4][4];
            const uint32_t hh[4] = {__shfl_sync(~0u, hd, tid & 3), __shfl_sync(~0u, hd, (tid & 3) + 4), __shfl_sync(~0u, hd, (tid & 3) + 8), __shfl_sync(~0u, hd, (tid & 3) + 12)};
#pragma unroll
            for (int i = 0; i < 4; i++) {
                const uint32_t b0 = pick(hh[i], selA), b1 = pick(hh[i], selB);
                if (i < 2) { zero4(ym[2 * i]); zero4(ym[2 * i + 1]); }
                mma(ym[2 * (i & 1)], w2r[2 * i], b0, b1); mma(ym[2 * (i & 1) + 1], w2r[2 * i + 1], b0, b1);
            }
            const float sc2 = __uint_as_float((uint32_t)(127 + 16 - max(((int)(__float_as_uint(msq) >> 23) - 127) >> 1, -100)) << 23);
            float y[4];
            uint32_t yb[4];
#pragma unroll
            for (int k = 0; k < 4; k++) { y[k] = ((tid & 2) ? ym[1][k] : ym[0][k]) + ((tid & 2) ? ym[3][k] : ym[2][k]); yb[k] = __float_as_uint(fmaf(y[k], sc2, FX2_MAGIC)); }
            const uint32_t big = !mlp ? 0 : (((yb[0] ^ 0x4b400000u) | (yb[1] ^ 0x4b400000u)) | ((yb[2] ^ 0x4b400000u) | (yb[3] ^ 0x4b400000u))) & FX2_MASK;
            u64 w[2], old[2];
#pragma unroll
            for (int k = 0; k < 2; k++) {
                w[k] = mk64(big ? 0 : yb[2 * k] * 512 + 0x80000001u, big ? 0 : yb[2 * k + 1] * 16 + 0x4c000000u);
                if (layer == 0) { if (mlp) asm volatile("red.relaxed.gpu.global.add.u64 [%0], %1;" :: "l"(ap2 + k * 40 * ACC_PITCH), "l"(w[k]) : "memory"); }
                else asm volatile("atom.relaxed.gpu.global.add.u64 %0, [%1], %2;" : "=l"(old[k]) : "l"(ap2 + k * 40 * ACC_PITCH), "l"(w[k]) : "memory");
            }
            const uint32_t c0 = clk();
            if (__any_sync(~0u, big)) {
                if (big) {
#pragma unroll
                    for (int k = 0; k < 4; k++)
                        asm volatile("red.relaxed.gpu.global.add.u64 [%0], %1;" :: "l"(ap2 + (k >> 1) * 40 * ACC_PITCH + 64 + (k & 1) * 32), "l"(fx_pack(y[k] * fx_scale(msq))) : "memory");
                    fence_gpu();
#pragma unroll
                    for (int k = 0; k < 2; k++) {
                        asm volatile("red.relaxed.gpu.global.and.b64 [%0], %1;" :: "l"(ap2 + k * 40 * ACC_PITCH), "l"(~256ull) : "memory");
                        w[k] = FX2_NONE;
                        asm volatile("atom.relaxed.gpu.global.add.u64 %0, [%1], %2;" : "=l"(old[k]) : "l"(ap2 + k * 40 * ACC_PITCH), "l"(FX2_NONE) : "memory");
                    }
                }
                __syncwarp();
            }
            if (layer == 0) { refresh(); load_b2(); park(); stsf(ha, SM_B1 + 64, csum); }
            stsf(0, SM_FXS, msq);
            const float inv32 = fx_inv(sc2) * 0.03125f;
            float xb[4] = {bf_lo(xp.x) + bf_lo(b2v.x) - 24.f * inv32, bf_hi(xp.x) + bf_hi(b2v.x), bf_lo(xp.y) + bf_lo(b2v.y) - 24.f * inv32, bf_hi(xp.y) + bf_hi(b2v.y)};
            auto add_wide = [&]() {
                fence_gpu();
                const float inv = fx_inv(fx_scale(ldsf(0, SM_FXS)));
#pragma unroll
                for (int k = 0; k < 4; k++) xb[k] += fx_val(ld_rlx(ap2 + (k >> 1) * 40 * ACC_PITCH + 64 + (k & 1) * 32)) * inv;
            };
            auto sum2 = [&](int k) {
                return pack_bf(xb[2 * k] + (float)(int)__funnelshift_r(lo32(w[k]), hi32(w[k]), 4) * inv32, xb[2 * k + 1] + (float)hi32(w[k]) * (inv32 + inv32));
            };
            if constexpr (layer == 1) {
#pragma unroll
                for (int k = 0; k < 4; k++) xb[k] = pinf(xb[k]);
                mbar_wait(SM_BAR + 3 * 64 + 56, 0);
#pragma unroll
                for (int k = 0; k < 2; k++) {
                    w[k] += old[k];
                    asm volatile("{\n.reg .pred p;\nsetp.eq.u32 p, %2, 0;\n@p st.global.u32 [%0], %1;\n}" :: "l"(op + k), "r"(sum2(k)), "r"(~lo32(w[k]) & 0x180) : "memory");
                }
                if (((lo32(w[0]) & ~(lo32(w[0]) >> 1)) | (lo32(w[1]) & ~(lo32(w[1]) >> 1))) & 128) {
                    add_wide();
                    if (w[0] & 128) op[0] = sum2(0);
                    if (w[1] & 128) op[1] = sum2(1);
                }
            } else {
                load_wq();
                __syncwarp();
                if (elect()) mbar_arrive(SM_BAR + 56);
#pragma unroll
                for (int k = 0; k < 4; k++) xb[k] = pinf(xb[k]);
                while (clk() - c0 < AR2D);
                uint32_t want = 0x180;
#pragma unroll 1
                for (int it = 0; it < SPIN; it++) {
                    if (it && !__any_sync(~0u, ~(lo32(w[0]) & lo32(w[1])) & 128)) { add_wide(); want = 128; }
                    w[0] = ld_rlx(ap2); w[1] = ld_rlx(ap2 + 40 * ACC_PITCH);
                    if (!__any_sync(~0u, ~(lo32(w[0]) & lo32(w[1])) & want)) break;
                }
                xp = make_uint2(sum2(0), sum2(1));
            }
        } else if constexpr (layer == 1) {
            if (warp == 7) {
                const uint32_t c1 = clk();
                while (clk() - c1 < KAD) tick(z[0]);
                if (zero) sts32(0, SM_JUNK, z[0].x);
            }
        } else {
            const uint32_t c0 = clk();
            load_wq();
            __syncwarp();
            if (elect()) mbar_arrive(SM_BAR + 56);
            if (warp == 5) {
                if (mlp) mbar_wait(SM_CBAR + 120, 0);
                asm volatile("bar.arrive 1, 192;" ::: "memory");
            }
            while (clk() - c0 < S6D + (warp - 5) * S6G) tick(wqh[0]);
            issue2(IC<0>{}, wq0[0].x | wq0[1].x | wq0[2].x | wq0[3].x | wq0[4].x | wq0[5].x);
            if (elect()) mbar_expect(warp == 5 ? SM_BAR + 4 * 64 : SM_CBAR - 32 + warp * 8, warp == 5 ? SUB : HT);
#pragma unroll 1
            for (int it = 0; it < SPIN; it++) { if (mbar_test(SM_BAR + 56, 0)) break; tick(wqh[0]); }
            const uint32_t c1 = clk();
            park();
            while (clk() - c1 < I0D) tick(wqh[0]);
            issue_help();
        }
    };

#pragma unroll 1
    for (uint32_t late = zero;; late = zero + 1) {
        if (late) {
            tail(IC<0>{});

            q_stage(IC<1>{});
            {
                const u64* qp = &g_ll[cta & ~3][tid];
                u64 w[4] = {0, 0, 0, 0};
                if (warp < 6) { w[0] = ld_rlx(qp); w[1] = ld_rlx(qp + 256); w[2] = ld_rlx(qp + 512); w[3] = ld_rlx(qp + 768); }
                mbar_wait(SM_BAR + 3 * 64 + 56, 0);
                const uint32_t ksl = ksw + lane * 16, qa = pin(q_addr()), qb0 = pin(lane < 8 ? lane * 48 : SM_ZQ - SM_VEC);
                uint32_t ks[96], qf[12];
                float mean, rstd, msq;
                ln_final(mean, rstd, msq);
                const float qc = pinf(-mean * rstd * ldsf(tid * 4, SM_CS));
#pragma unroll
                for (int k = 0; k < 6; k++) lds128(ks + 4 * k, ksl, SM_KS + k * 512);
                stsf(0, SM_FXS, fx_scale(msq));
                if (warp < 6) {
                    ll_gather4(qp, ep8() + 5, w);
                    const float q = ((hif(w[0]) + hif(w[1])) + (hif(w[2]) + hif(w[3]))) * rstd + qc;
                    const uint32_t qq = bf2_mul(pack_bf(q, q), 0x3f807180u);
                    sts16(qa, SM_VEC, qq); sts16(qa, SM_QU, qq >> 16);
                    sts32_if(!(fabsf(q) < 1048576.f), 0, SM_BIG, 1);
                    __syncwarp();
                    if (elect()) mbar_arrive(SM_QBAR);
                } else {
                    uint4 c = make_uint4(ks[0], ks[1], ks[2], ks[3]);
                    if (cta == 0 && tid == 255) g_epoch = (ep8() >> 3) + 1;
#pragma unroll 1
                    for (int it = 0; it < SPIN; it++) { if (mbar_test(SM_QBAR, 1)) break; tick(c); }
                    ks[0] = c.x; ks[1] = c.y; ks[2] = c.z; ks[3] = c.w;
                }
                issue2(IC<3>{}, ks[0] | ks[4] | ks[8] | ks[12] | ks[16] | ks[20]);
                mbar_wait(SM_QBAR, 1);
                auto load_q = [&](int u, int k) { lds128(qf + 4 * k, u == 0 ? qb0 : (tid & 24) == 8 * u ? (tid & 7) * 48 : SM_ZQ - SM_VEC, SM_VEC + k * 16); };
                load_q(0, 1); load_q(0, 2); load_q(0, 0);
                float D[4][4];
                uint4 vb[NPK + 2][6], v2[6];
                uint32_t xn = 0;
                const uint32_t t1 = __shfl_sync(~0u, lds32(0, SM_T0), 0);
                auto step = [&](auto Q) {
                    constexpr int st = Q.value, p = cord(st), s = PL.slot[p], n = PL.ld[st];
                    if constexpr (n > 0) {
                        if constexpr (st >= NPK) {
                            const uint32_t due = t1 + (P2A + n * P2B);
#pragma unroll 1
                            for (int it = 0; it < 4096; it++) if ((int)(gtime() - due) >= 0) break;
                        }
                        const uint4 (&u)[6] = vb[st - 1 < NPK ? st - 1 : NPK + ((st - 1) & 1)];
                        issue2(IC<n>{}, st > PVNOW ? 0 : u[0].x | u[1].x | u[2].x | u[3].x | u[4].x | u[5].x);
                    }
                    if constexpr (st == 14) {
#pragma unroll 1
                        for (int it = 0; it < 4096; it++) if ((int)(gtime() - t1) >= P2W) break;
                        issue2(IC<16>{}, 0);
                    }
                    if (p == 1) mbar_wait(SM_CBAR + (warp >> 2) * 8, 1);
                    else if (p == 0) mbar_wait(warp < 4 ? SM_CBAR + 24 : barw, warp < 4);
                    else mbar_wait(barw + s * 8, IC<PL.par[p]>::value);
                    load_v(vb[st < NPK ? st : NPK + (st & 1)], slot_u(s), slot_o(s));
                };
                static_for<0, 96>([&](auto I) {
                    constexpr int F = I.value, n = F / 6, i = n ? F % 6 : (F + 2) % 6;
                    const uint32_t* c = n == 0 ? (i < 2 ? ks + 3 * i : kc + 174 + 3 * i) : n < 6 ? ks + 18 * n - 12 + 3 * i : kc + 18 * (n - 6) + 3 * i;
                    const uint32_t hx = c[2] & 0x78787878u, ha = hx * (zero - 1) + c[2], hb = __funnelshift_r(hx, hx, 4);
                    if (F < 24 && F % 6 == 0) zero4(D[n]);
                    mma(D[n & 3], __byte_perm(c[0], ha, 0x5140), __byte_perm(c[0], ha, 0x7362), __byte_perm(c[1], hb, 0x5140), __byte_perm(c[1], hb, 0x7362), qf[2 * i], qf[2 * i + 1]);
                    if constexpr ((n & 3) == 3 && n < 15 && (i & 1)) load_q((n + 1) >> 2, i >> 1);
                    static_for<6, 24>([&](auto U) {
                        if constexpr (((U.value - 5) * 4 + 2) / 3 - 1 == F) {
                            lds128(ks + 4 * U.value, ksl, SM_KS + U.value * 512);
                            if constexpr (U.value % 6 == 5) { const uint32_t* k = ks + 4 * U.value - 17; issue2(IC<3 + U.value / 6>{}, k[0] | k[4] | k[8] | k[12] | k[16] | k[20]); }
                        }
                    });
                    if constexpr (F == 94) {
                        if (warp < 4) { mbar_wait(SM_CBAR + 16, 1); load_v(v2, wqw, slot_o(2)); }
                        else {
                            const char* p = reinterpret_cast<const char*>(P.v) + (size_t)(roww + vunit(2) * 256) * (DH * 2) + t * 768 + g * 16;
#pragma unroll
                            for (int k = 0; k < 6; k++)
                                asm volatile("ld.global.nc.v4.u32 {%0,%1,%2,%3}, [%4];" : "=r"(v2[k].x), "=r"(v2[k].y), "=r"(v2[k].z), "=r"(v2[k].w) : "l"(p + k * 128));
                        }
                        const uint2 x = lds64(0, SM_XN);
                        xn = x.y ? XCAP + 1 : x.x;
                        sts128(prow + lane * 16, SM_PART + 256, 0, 0, 0, 0);
                        __syncwarp();
#pragma unroll 1
                        for (uint32_t idx = lane; idx < (xn > XCAP ? 0 : xn); idx += 32) {
                            const uint32_t m = lds32(idx * 4, SM_XM);
                            if ((m >> 21) == warp) {
                                const uint4 r = lds128(idx * 16, SM_XR);
                                const uint32_t qo = ((m >> 16) & 3) * 48 + (m & 255);
                                const uint2 a = lds64(qo, SM_QU), b = lds64(qo, SM_QU + 192);
                                const float s = ((bf_lo(r.x) * bf_lo(a.x) + bf_hi(r.x) * bf_hi(a.x)) + (bf_lo(r.y) * bf_lo(b.x) + bf_hi(r.y) * bf_hi(b.x))) +
                                                ((bf_lo(r.z) * bf_lo(a.y) + bf_hi(r.z) * bf_hi(a.y)) + (bf_lo(r.w) * bf_lo(b.y) + bf_hi(r.w) * bf_hi(b.y)));
                                asm volatile("red.relaxed.cta.shared.add.f32 [%0], %1;" :: "r"(SM_PART + 256 + prow + ((m >> 18) & 7) * 64 + ((m >> 8) & 15) * 4), "f"(s) : "memory");
                            }
                        }
                        __syncwarp();
                    }
                    if constexpr (F == PK0 - 2) { refresh(); lds128(kc + 8, prow + lane * 16, SM_PART + 256); }
                    static_for<0, NPK>([&](auto Q) { if constexpr (F == (Q.value ? PK1 + (Q.value - 1) * PKD : PK0)) step(Q); });
                });
                float S[4];
                {
                    const uint32_t shp = lds32(tid * 4, SM_SH);
                    const uint4 cr = lds128(prow + lane * 16, SM_PART + 256);
                    const uint32_t c[4] = {cr.x, cr.y, cr.z, cr.w};
#pragma unroll
                    for (int j = 0; j < 4; j++) S[j] = (D[j][0] + D[j][3]) * __uint_as_float((((shp >> (8 * j)) & 255) + 27) << 23) + __uint_as_float(c[j]);
                }
                if (xn > XCAP) {
#pragma unroll
                    for (int k = 0; k < 3; k++) lds128(qf + 4 * k, (lane & 7) * 48, SM_QU + k * 16);
                    const char* kp = reinterpret_cast<const char*>(P.k) + (size_t)(roww + g) * (DH * 2) + t * 32;
#pragma unroll 1
                    for (int e = 6; e < 22; e++, kp += 256 * DH * 2) {
                        uint4 v[6];
#pragma unroll
                        for (int i = 0; i < 6; i++) v[i] = ldg128(kp + (i >> 1) * 128 + (i & 1) * 16);
                        const float s = score6(v, qf);
                        if (t == ((e >> 2) & 3)) { S[0] = S[1]; S[1] = S[2]; S[2] = S[3]; S[3] = s; }
                    }
                    if (t == 1) { const float a = S[0], b = S[1]; S[0] = S[2]; S[1] = S[3]; S[2] = a; S[3] = b; }
                }
                softmax(IC<1>{}, S);
                auto p_of = [&](int st) { return lds32(ad(t * 4, prow), SM_PART + 256 + ((vunit(cord(st)) + 6) & 15) * 16); };
                auto pv_at = [&](auto Q) { constexpr int st = Q.value; pv(vb[st < NPK ? st : NPK + (st & 1)], p_of(st)); };
                static_for<NPK, 15>([&](auto Q) {
                    constexpr int st = Q.value;
                    if constexpr (st == HWAT) head_look();
                    if constexpr (st == HWC) head_weight(IC<1>{});
                    if constexpr (st == PREP1) { tail_prep1(IC<1>{}); tail_prep2(IC<1>{}); red_addr(IC<1>{}); load_u(z, warp * WOU, SM_RING + 16 * WOU); }
                    if constexpr (st == PREP2) mlp_prep(IC<1>{});
                    uint32_t pp;
                    if constexpr (st >= PVNOW) pp = pin(p_of(st));
                    step(Q);
                    if constexpr (st - NPK < NPK) pv_at(IC<st - NPK>{});
                    if constexpr (st > NPK && st <= PVNOW) pv_at(IC<st - 1>{});
                    if constexpr (st == PV2) pv(v2, lds32(ad(t * 4, prow), SM_PART + 256 + ((vunit(2) + 6) & 15) * 16));
                    if constexpr (st >= PVNOW) pv(vb[NPK + (st & 1)], pp);
                });
            }
            tail(IC<1>{});
            if (!zero) return;
        }
        tid = threadIdx.x;
        derive();
        xp = make_uint2(0, 0);
        if (tid < 160) xp = *reinterpret_cast<const uint2*>(P.x + 4 * c4);
        else if (tid == 192) xp.x = *(volatile unsigned*)&g_epoch;
        else if (tid >= 224 && tid < 240 && mlp) xp.x = reinterpret_cast<const unsigned short*>(P.b1)[hu + lane];
        __syncwarp();
        if (elect()) {
#pragma unroll
            for (int i = 0; i < 7; i++) mbar_init(barw + i * 8, 1);
            if (warp < 4) mbar_arrive(barw);
            mbar_init(SM_CBAR + warp * 8, 1); mbar_init(SM_CBAR + 64 + warp * 8, 1);
            if (warp == 0) { mbar_init(SM_QBAR, 6); mbar_init(SM_BAR + 56, 8); }
            asm volatile("fence.mbarrier_init.release.cluster;" ::: "memory");
            sts64(warp * 8, SM_CNT, 0, 0);
            sts64(warp * 8, SM_ZQ, 0, 0);
        }
#pragma unroll
        for (int i = 12; i < 192; i++) asm volatile("mov.b32 %0, 0;" : "=r"(kc[i]));
        __syncwarp();
        if (warp < 3) { wait_due(warp, 0); if (elect()) issue_kv(warp, warp + 1, warp); }
        else mbar_wait(barw + 56, 0);
        if (tid == 192) sts32(0, SM_EPOCH, xp.x * 8);
        if (tid >= 224 && tid < 240) sts32(lane * 4, SM_B1, xp.x << 16);
        __syncthreads();
        if ((warp == 3 || warp == 4) && elect()) issue_kv(warp, warp == 4 ? 0 : 4, warp);

        load_wq();
        q_stage(IC<0>{});
        {
            int it = (warp >> 2) + 5, slot = (warp >> 2) + 1, bar = warp >> 2, par = 0;
            auto refill = [&](bool kv) {
                uint32_t old;
                asm volatile("{\n.reg .pred p;\nelect.sync _|p, 0xffffffff;\nmov.u32 %0, 0;\n@p atom.relaxed.cta.shared.inc.u32 %0, [%1], 3;\n}" : "=r"(old) : "r"(SM_CNT + slot * 8) : "memory");
                if (__any_sync(~0u, old == 3)) {
                    if (!kv && it >= 64) {
#pragma unroll 1
                        for (int k = 0; k < SPIN; k++) {
                            int f; asm volatile("ld.volatile.shared.u32 %0, [%1];" : "=r"(f) : "r"(SM_CNT + 4) : "memory");
                            if (f >= slot) break;
                        }
                        sts32(0, SM_CNT + 4, slot + 1);
                        if (elect()) issue_wo(slot);
                    } else {
                        wait_due(it, 0);
                        if (elect()) issue_kv(it, slot, bar < 5 ? bar + 5 : bar - 5);
                    }
                    __syncwarp();
                }
            };
            auto advance = [&]() { it += 2; slot += 2; if (slot >= 5) slot -= 5; bar += 2; if (bar >= 10) { bar -= 10; par ^= 1; } };
            {
                uint32_t offK[3], qf[12];
#pragma unroll
                for (int j = 0; j < 3; j++) offK[j] = pin(((tid >> 5) & 3) * SUB + 3 * g * 128 + (((2 * t) ^ ((3 * g + j) & 7)) << 4));
#pragma unroll
                for (int i = 0; i < 12; i++) qf[i] = kc[i] = 0;
                const uint32_t ksl = pin(ksw + lane * 16), sca = pin(prow + g * 64);
                int n0 = 0;
#pragma unroll 1
                for (int e = 0; e < 16; e++) {
                    mbar_wait(SM_CBAR + bar * 8, par);
                    uint4 v[6];
#pragma unroll
                    for (int i = 0; i < 6; i++) v[i] = lds128(ad(offK[i >> 1] ^ ((i & 1) * 16), slot * HT), SM_RING + (i >> 1) * 128);
                    refill(true);
                    advance();
                    if ((0xc20 | ((2 << NP) - 1)) >> e & 1) {
                        refresh();
                        static_for<0, NP>([&](auto E) {
                            if (e == E.value) {
#pragma unroll
                                for (int i = 0; i < 6; i++) {
                                    uint32_t* k = kc + 90 + 24 * E.value + 4 * i;
                                    asm volatile("mov.b32 %0, %4; mov.b32 %1, %5; mov.b32 %2, %6; mov.b32 %3, %7;" : "=r"(k[0]), "=r"(k[1]), "=r"(k[2]), "=r"(k[3]) : "r"(v[i].x), "r"(v[i].y), "r"(v[i].z), "r"(v[i].w));
                                }
                                if (E.value == NP - 2 && warp < 6) {
#pragma unroll
                                    for (int i = 0; i < 2; i++)
                                        asm volatile("cp.async.cg.shared.global [%0], [%1], 16;" :: "r"(ksl + SM_KS + 10240 + i * 512),
                                                     "l"(&g_ll[(cta & ~3) + 2 * i + (lane >> 4)][warp * 32 + (lane & 15) * 2]) : "memory");
                                }
                                if (E.value == NP - 1 && warp < 6) {
                                    asm volatile("cp.async.wait_all;" ::: "memory");
                                    __syncwarp();
                                    const uint32_t a = ksw + lane * 8;
                                    u64 w[4] = {lds_u64(a, SM_KS + 10240), lds_u64(a, SM_KS + 10496), lds_u64(a, SM_KS + 10752), lds_u64(a, SM_KS + 11008)};
                                    ll_gather4(&g_ll[cta & ~3][tid], ep8() + 1, w);
                                    const float cs = (lof(w[0] & ~255ull) + lof(w[1] & ~255ull)) + (lof(w[2] & ~255ull) + lof(w[3] & ~255ull));
                                    float q = (hif(w[0]) + hif(w[1])) + (hif(w[2]) + hif(w[3]));
                                    stsf(tid * 4, SM_CS, cs);
                                    float mean, rstd, msq;
                                    ln_final(mean, rstd, msq);
                                    stsf(0, SM_FXS, fx_scale(msq));
                                    q = (q - mean * cs) * rstd;
                                    sts16(q_addr(), SM_QU, pack_bf(q, q));
                                    __syncwarp();
                                    if (elect()) mbar_arrive(SM_QBAR);
#pragma unroll
                                    for (int i = 0; i < 12; i++) asm volatile("mov.b32 %0, 0;" : "=r"(kc[i]));
                                }
                            }
                        });
                        if (e == NP) {
                            mbar_wait(SM_QBAR, 0);
#pragma unroll
                            for (int k = 0; k < 3; k++) lds128(qf + 4 * k, (lane & 7) * 48, SM_QU + k * 16);
                            static_for<0, NP>([&](auto E) {
                                uint4 r[6];
#pragma unroll
                                for (int i = 0; i < 6; i++) { const uint32_t* k = kc + 90 + 24 * E.value + 4 * i; r[i] = make_uint4(k[0], k[1], k[2], k[3]); }
                                stsf(sca, SM_PART + 256 + (E.value + 6) * 4, score6(r, qf));
                            });
#pragma unroll
                            for (int i = 0; i < 24; i++) asm volatile("mov.b32 %0, 0;" : "=r"(kc[i]));
                        } else if (e == 5) {
#pragma unroll
                            for (int k = 0; k < 22; k++) lds128(kc + 4 * k, ksl, SM_KS + k * 512);
                            lds64(kc + 88, ksl, SM_KS + 22 * 512);
                            n0 = 0;
                        } else if (e == 10) {
#pragma unroll
                            for (int k = 0; k < 22; k++)
                                asm volatile("ld.shared.v4.b32 {%0,%1,%2,%3}, [%4];" : "=r"(kc[90 + 4 * k]), "=r"(kc[91 + 4 * k]), "=r"(kc[92 + 4 * k]), "=r"(kc[93 + 4 * k]) : "r"(ad(ksl, SM_KS + k * 512)) : "memory");
                            asm volatile("ld.shared.v2.b32 {%0,%1}, [%2];" : "=r"(kc[178]), "=r"(kc[179]) : "r"(ad(ksl, SM_KS + 22 * 512)) : "memory");
                            n0 = 0;
                        } else if (e == 11) {
                            lds64(kc + 180, ksl, SM_KS + 520); lds128(kc + 182, ksl, SM_KS + 1024); lds128(kc + 186, ksl, SM_KS + 1536); lds64(kc + 190, ksl, SM_KS + 2048);
                            n0 = 3;
                        }
                    }
                    const int n = (e + 6) & 15;
                    stsf(ad(sca, n * 4), SM_PART + 256, score6(v, qf));
                    uint32_t m = bf2_amax(bf2_amax(v[0].x, v[0].y), bf2_amax(v[0].z, v[0].w)), mn = bf2_amin(bf2_amin(v[0].x, v[0].y), bf2_amin(v[0].z, v[0].w));
#pragma unroll
                    for (int i = 1; i < 6; i++) m = bf2_amax(m, bf2_amax(bf2_amax(v[i].x, v[i].y), bf2_amax(v[i].z, v[i].w)));
                    m = max(m & 0x7fff, (m >> 16) & 0x7fff);
                    m = max(m, __shfl_xor_sync(~0u, m, 1)); m = max(m, __shfl_xor_sync(~0u, m, 2));
#pragma unroll
                    for (int i = 1; i < 6; i++) mn = bf2_amin(mn, bf2_amin(bf2_amin(v[i].x, v[i].y), bf2_amin(v[i].z, v[i].w)));
                    mn = min(mn & 0x7fff, (mn >> 16) & 0x7fff);
                    const int sh = min(max((int)(m >> 7) - 15, 0), 126);
                    asm volatile("st.shared.u8 [%0], %1;" :: "r"(ad(ad((tid >> 2) * 16, n), SM_SH)), "r"(sh) : "memory");
                    const uint32_t dn = (127 - sh) * 0x00800080u;
                    if (__any_sync(~0u, (int)(mn >> 7) <= sh || m >= (142 << 7))) {
                        if (m >= (142 << 7)) sts32(0, SM_BIG, 1);
                        const uint32_t up = (127 + 256 + sh) * 0x00800080u;
#pragma unroll
                        for (int i = 0; i < 6; i++) {
                            const uint32_t r0 = bf2_fma(bf2_mul(v[i].x, dn), up, v[i].x), r1 = bf2_fma(bf2_mul(v[i].y, dn), up, v[i].y);
                            const uint32_t r2 = bf2_fma(bf2_mul(v[i].z, dn), up, v[i].z), r3 = bf2_fma(bf2_mul(v[i].w, dn), up, v[i].w);
                            asm volatile("{\n.reg .pred p;\n.reg .u32 x, a;\nsetp.ne.u32 p, %0, 0;\nmov.u32 x, %7;\n@p atom.relaxed.cta.shared.inc.u32 x, [%6], 0x7fffffff;\n"
                                         "setp.lt.u32 p, x, %7;\nmad.lo.u32 a, x, 16, %8;\n@p st.shared.v4.u32 [a], {%1,%2,%3,%4};\n"
                                         "mad.lo.u32 a, x, 4, %9;\n@p st.shared.u32 [a], %5;\n}"
                                         :: "r"(r0 | r1 | r2 | r3), "r"(r0), "r"(r1), "r"(r2), "r"(r3), "r"(tid << 16 | n << 8 | i * 8), "r"(SM_XN), "n"(XCAP), "n"(SM_XR), "n"(SM_XM) : "memory");
                        }
                    }
                    const uint32_t ae = (n0 >> 1) * 512 + (n0 & 1) * 8, ao = ((n0 + 1) >> 1) * 512 + (~n0 & 1) * 8;
                    uint32_t o[18];
#pragma unroll
                    for (int i = 0; i < 6; i++) {
                        const uint32_t y0 = bf2_mulv(v[i].x, dn), y1 = bf2_mulv(v[i].y, dn), y2 = bf2_mulv(v[i].z, dn), y3 = bf2_mulv(v[i].w, dn);
                        o[3 * i] = __byte_perm(y0, y1, 0x6420); o[3 * i + 1] = __byte_perm(y2, y3, 0x6420);
                        const uint32_t hb = __byte_perm(y2, y3, 0x7531);
                        o[3 * i + 2] = __byte_perm(y0, y1, 0x7531) | __funnelshift_l(hb, hb, 4);
                        if (i & 1) {
#pragma unroll
                            for (int k = 3 * (i >> 1); k < 3 * (i >> 1) + 3; k++) sts64(ad(ksl, (k & 1) ? ao : ae), SM_KS + (k >> 1) * 512, o[2 * k], o[2 * k + 1]);
                        }
                    }
                    n0 += 9;
                }
                fence_async();
            }
            refresh();
            {
                const uint4 sc = lds128(prow + lane * 16, SM_PART + 256);
                const float S[4] = {__uint_as_float(sc.x), __uint_as_float(sc.y), __uint_as_float(sc.z), __uint_as_float(sc.w)};
                softmax(IC<0>{}, S);
            }
            fw = 0.f;
#pragma unroll 1
            for (int e = 0; e < 16; e++) {
                if ((1 << (PUBAT - 3) | 1 << PUBAT | 1 << ZCHK) >> e & 1) {
                    if (e == PUBAT - 3) head_look();
                    else if (e == PUBAT) {
                        head_weight(IC<0>{});
                        if (tid < 196) st_rlx(&g_ll[cta][tid + (tid >> 6 == 3) * 8], 0ull);
                    } else if (warp == 7) {
                        if ((bx & 15) == 0 && elect()) bulk_pf(P.b2, D_MODEL * 2, POL_NORMAL);
#pragma unroll 1
                        for (int k = 0; k < SPIN; k++) {
                            uint32_t v; asm volatile("ld.acquire.gpu.global.u32 %0, [%1];" : "=r"(v) : "l"(&g_zflag) : "memory");
                            if (__all_sync(~0u, v * 8 == ep8() + 8)) break;
                        }
                    }
                    __syncwarp();
                }
                const uint32_t pp = lds32(ad(t * 4, prow + ((e + 6) & 15) * 16), SM_PART + 256);
                mbar_wait(SM_CBAR + bar * 8, par);
                uint4 v[6];
                load_v(v, (warp & 3) * SUB + slot * HT, SM_RING);
                if (e < 15) refill(false);
                advance();
                pv(v, pp);
            }
        }
        tail_prep1(IC<0>{});
        __syncwarp();
    }
}

typedef CUresult (*EncodeFn)(CUtensorMap*, CUtensorMapDataType, cuuint32_t, void*, const cuuint64_t*, const cuuint64_t*, const cuuint32_t*,
                             const cuuint32_t*, CUtensorMapInterleave, CUtensorMapSwizzle, CUtensorMapL2promotion, CUtensorMapFloatOOBfill);

}

extern "C" void kernel_launch(void* const* d_in, const int* in_sizes, int n_in, void* d_out, int out_size) {
    (void)in_sizes; (void)n_in; (void)out_size;
    static EncodeFn enc = nullptr;
    if (!enc) {
        void* fn = nullptr;
        cudaDriverEntryPointQueryResult qr;
        cudaGetDriverEntryPoint("cuTensorMapEncodeTiled", &fn, cudaEnableDefault, &qr);
        enc = (EncodeFn)fn;
        cudaFuncSetAttribute(fused_kernel, cudaFuncAttributeMaxDynamicSharedMemorySize, SM_TOTAL);
    }
    Params P;
    const cuuint32_t ones[3] = {1, 1, 1};
    for (int m = TM_K; m <= TM_V8; m++) {
        const cuuint64_t dim[3] = {64, 3, (cuuint64_t)NHEAD * SK}, str[2] = {128, DH * 2};
        const cuuint32_t box[3] = {m == TM_VP ? 8u : 64u, 3, m == TM_V8 ? 8u : 32u};
        enc(&P.tm[m], CU_TENSOR_MAP_DATA_TYPE_BFLOAT16, 3, d_in[m == TM_K ? 1 : 2], dim, str, box, ones, CU_TENSOR_MAP_INTERLEAVE_NONE,
            m == TM_VP ? CU_TENSOR_MAP_SWIZZLE_NONE : CU_TENSOR_MAP_SWIZZLE_128B, CU_TENSOR_MAP_L2_PROMOTION_NONE, CU_TENSOR_MAP_FLOAT_OOB_FILL_NONE);
    }
    {
        const cuuint64_t dim[3] = {64, NHEAD * 3, D_MODEL}, str[2] = {128, NHEAD * DH * 2};
        const cuuint32_t box[3] = {64, 3, 32};
        enc(&P.tm[TM_WQ], CU_TENSOR_MAP_DATA_TYPE_BFLOAT16, 3, d_in[3], dim, str, box, ones, CU_TENSOR_MAP_INTERLEAVE_NONE,
            CU_TENSOR_MAP_SWIZZLE_128B, CU_TENSOR_MAP_L2_PROMOTION_NONE, CU_TENSOR_MAP_FLOAT_OOB_FILL_NONE);
    }
    {
        const cuuint64_t dim[2] = {DFF, D_MODEL}, str[1] = {DFF * 2};
        const cuuint32_t box[2] = {16, 128};
        enc(&P.tm[TM_W1], CU_TENSOR_MAP_DATA_TYPE_BFLOAT16, 2, d_in[6], dim, str, box, ones, CU_TENSOR_MAP_INTERLEAVE_NONE,
            CU_TENSOR_MAP_SWIZZLE_32B, CU_TENSOR_MAP_L2_PROMOTION_L2_128B, CU_TENSOR_MAP_FLOAT_OOB_FILL_NONE);
    }
    {
        const cuuint64_t dim[3] = {32, 20, NHEAD * DH}, str[2] = {64, D_MODEL * 2};
        const cuuint32_t box[3] = {32, 5, 16};
        enc(&P.tm[TM_WO], CU_TENSOR_MAP_DATA_TYPE_BFLOAT16, 3, d_in[4], dim, str, box, ones, CU_TENSOR_MAP_INTERLEAVE_NONE,
            CU_TENSOR_MAP_SWIZZLE_64B, CU_TENSOR_MAP_L2_PROMOTION_L2_128B, CU_TENSOR_MAP_FLOAT_OOB_FILL_NONE);
    }
    {
        const cuuint64_t dim[4] = {32, 20, 24, NHEAD * 8}, str[3] = {64, D_MODEL * 2, 24 * D_MODEL * 2};
        const cuuint32_t box[4] = {32, 5, 8, 4}, ones4[4] = {1, 1, 1, 1};
        enc(&P.tm[TM_WO4], CU_TENSOR_MAP_DATA_TYPE_BFLOAT16, 4, d_in[4], dim, str, box, ones4, CU_TENSOR_MAP_INTERLEAVE_NONE,
            CU_TENSOR_MAP_SWIZZLE_64B, CU_TENSOR_MAP_L2_PROMOTION_L2_128B, CU_TENSOR_MAP_FLOAT_OOB_FILL_NONE);
        const cuuint32_t thin[4] = {8, 5, 8, 4};
        enc(&P.tm[TM_WOP], CU_TENSOR_MAP_DATA_TYPE_BFLOAT16, 4, d_in[4], dim, str, thin, ones4, CU_TENSOR_MAP_INTERLEAVE_NONE,
            CU_TENSOR_MAP_SWIZZLE_NONE, CU_TENSOR_MAP_L2_PROMOTION_NONE, CU_TENSOR_MAP_FLOAT_OOB_FILL_NONE);
    }
    {
        const cuuint64_t dim[3] = {64, 10, DFF}, str[2] = {128, D_MODEL * 2};
        const cuuint32_t box[3] = {64, 10, 16};
        enc(&P.tm[TM_W2], CU_TENSOR_MAP_DATA_TYPE_BFLOAT16, 3, d_in[8], dim, str, box, ones, CU_TENSOR_MAP_INTERLEAVE_NONE,
            CU_TENSOR_MAP_SWIZZLE_128B, CU_TENSOR_MAP_L2_PROMOTION_NONE, CU_TENSOR_MAP_FLOAT_OOB_FILL_NONE);
    }
    P.x = (const __nv_bfloat16*)d_in[0];
    P.k = (const __nv_bfloat16*)d_in[1];
    P.v = (const __nv_bfloat16*)d_in[2];
    P.b1 = (const __nv_bfloat16*)d_in[7];
    P.b2 = (const __nv_bfloat16*)d_in[9];
    P.out = (__nv_bfloat16*)d_out;
    fused_kernel<<<NCTA + 1, NTHR, SM_TOTAL, cudaStreamPerThread>>>(P);
}
```

```cpp
#include <cuda_runtime.h>
#include <cuda_bf16.h>
#include <cuda.h>
#include <stdint.h>

#define DI __device__ __forceinline__

namespace {

constexpr int D_MODEL = 640, NHEAD = 32, SK = 32768, DH = 192, WIN = 4096, DFF = 1536;
constexpr int NCTA = 128, NTHR = 256;
constexpr int SUB = 8 * DH * 2;
constexpr int HT = 4 * SUB;
constexpr int WOU = 8 * 320;
constexpr int XCAP = 48;
constexpr int SM_RING = 1024;
constexpr int SM_W2 = SM_RING + 8 * WOU;
constexpr int SM_WQ = SM_RING + 5 * HT;
constexpr int SM_KS = SM_WQ + 5 * HT;
constexpr int SM_PART = SM_KS + 8 * HT;
constexpr int SM_BAR = SM_PART + 6144;
constexpr int SM_VEC = SM_BAR + 512;
constexpr int SM_QU = SM_VEC + 384;
constexpr int SM_ZQ = SM_QU + 384;
constexpr int SM_CS = SM_ZQ + 64;
constexpr int SM_XR = SM_CS + 768;
constexpr int SM_XM = SM_XR + XCAP * 16;
constexpr int SM_SH = SM_XM + XCAP * 4;
constexpr int SM_C1 = SM_SH + 1024;
constexpr int SM_B1 = SM_C1 + 320;
constexpr int SM_STAT = SM_B1 + 128;
constexpr int SM_QBAR = SM_STAT + 40;
constexpr int SM_CBAR = SM_QBAR + 8;
constexpr int SM_CNT = SM_CBAR + 128;
constexpr int SM_XN = SM_CNT + 56;
constexpr int SM_BIG = SM_XN + 4;
constexpr int SM_EPOCH = SM_BIG + 4;
constexpr int SM_FXS = SM_EPOCH + 4;
constexpr int SM_T0 = SM_FXS + 4;
constexpr int SM_JUNK = SM_T0 + 4;
constexpr int SM_TOTAL = 232448;
static_assert(SM_JUNK + 4 <= SM_RING + SM_TOTAL, "smem");

constexpr int SPIN = 1 << 20;
enum { TM_WQ = 0, TM_K = 1, TM_V = 2, TM_VP = 3, TM_V8 = 4, TM_WO = 5, TM_W1 = 6, TM_WO4 = 7, TM_W2 = 8, TM_WOP = 9 };
constexpr uint32_t POL_NORMAL = 0x16F00000u, POL_FIRST = 0x12F00000u;

constexpr int PACE = 485, PACE0 = 1700, WOPACE = 403, W1D = 200, W1G = 150, HZD = 9500;
constexpr int NP = 3, PUBAT = 8, ZCHK = 14;
constexpr int ODELAY = 200, AR1D = 600, AR1DN = 1000, AR2D = 600, S6D = 900, S6G = 200, I0D = 300, KAD = 900;
constexpr unsigned long long VORD = 0xba6594327180cdefull;
constexpr int ISS = 0xf9e, NPK = 4, PK0 = 34, PK1 = 52, PKD = 21, P2A = -400, P2B = 380, P2W = 5500;
constexpr int PREP1 = 10, PREP2 = 10, PV2 = 7, HWAT = 8, PVNOW = 11, HWC = 11;
constexpr uint32_t FX2_MASK = 0xfff00000u;

struct Plan { int slot[17], par[17], ld[15]; bool ok; };
__host__ __device__ constexpr int cord(int s) { return s < 2 ? s : s + 1; }
constexpr Plan make_plan() {
    Plan s{};
    int phase[7] = {}, freeat[7] = {}, it = 7;
    for (int p = 0; p < 7; p++) { s.slot[p] = p; phase[p] = p != 1; freeat[p] = -1; }
    s.ok = true;
    for (int st = 0; st < 15; st++) {
        if (ISS >> st & 1) {
            int best = -1;
            for (int c = 0; c < 7; c++) if (freeat[c] >= 0 && (c < 5 || it < 13) && (best < 0 || freeat[c] < freeat[best])) best = c;
            if (best < 0 || it > 15) { s.ok = false; return s; }
            s.slot[it] = best; freeat[best] = -1;
            s.par[it] = phase[best]++ & 1;
            s.ld[st] = it++;
        }
        if (cord(st) >= it || (st >= 12 && s.slot[cord(st)] >= 5)) s.ok = false;
        freeat[s.slot[cord(st)]] = st;
    }
    s.slot[16] = 5; s.par[16] = phase[5] & 1;
    return s;
}
constexpr Plan PL = make_plan();
static_assert(PL.ok && PK0 < 40, "bad pass-2 plan");
__host__ __device__ constexpr int vunit(int p) { return (int)(VORD >> (4 * p) & 15); }

template <int I> struct IC { static constexpr int value = I; };
template <int A, int B, class F> DI void static_for(F&& f) {
    if constexpr (A < B) { f(IC<A>{}); static_for<A + 1, B>(f); }
}

struct Params {
    CUtensorMap tm[10];
    const __nv_bfloat16 *x, *b1, *b2, *k, *v;
    __nv_bfloat16* out;
};

typedef unsigned long long u64;
constexpr int ACC_PITCH = 256;
constexpr int ACC_BYTES = 80 * ACC_PITCH;
__device__ __align__(1024) unsigned char g_acc[4 * ACC_BYTES];
__device__ __align__(8192) u64 g_ll[NCTA][256];
__device__ unsigned g_epoch;
__device__ __align__(128) unsigned g_zflag;

DI void mbar_wait(uint32_t bar, uint32_t parity) {
    asm volatile("{\n.reg .pred p, q;\n.reg .u32 n;\nmov.u32 n, 0;\n"
                 "LOOP:\nmbarrier.try_wait.parity.shared::cta.b64 p, [%0], %1;\n"
                 "add.u32 n, n, 1;\nsetp.lt.and.u32 q, n, 0x100000, !p;\n@q bra.uni LOOP;\n}"
                 :: "r"(bar), "r"(parity) : "memory");
}
DI bool mbar_test(uint32_t bar, uint32_t parity) {
    uint32_t done;
    asm volatile("{\n.reg .pred p;\nmbarrier.test_wait.parity.shared::cta.b64 p, [%1], %2;\nselp.u32 %0, 1, 0, p;\n}" : "=r"(done) : "r"(bar), "r"(parity) : "memory");
    return __any_sync(~0u, done);
}
DI bool elect() {
    uint32_t r;
    asm volatile("{\n.reg .pred p;\nelect.sync _|p, 0xffffffff;\nselp.u32 %0, 1, 0, p;\n}" : "=r"(r));
    return r != 0;
}
DI void mbar_init(uint32_t bar, uint32_t n) { asm volatile("mbarrier.init.shared::cta.b64 [%0], %1;" :: "r"(bar), "r"(n) : "memory"); }
DI void mbar_arrive(uint32_t bar) { asm volatile("mbarrier.arrive.shared::cta.b64 _, [%0];" :: "r"(bar) : "memory"); }
DI void mbar_expect(uint32_t bar, uint32_t bytes) {
    asm volatile("mbarrier.arrive.expect_tx.shared::cta.b64 _, [%0], %1;" :: "r"(bar), "r"(bytes) : "memory");
}
DI void fence_gpu() { asm volatile("fence.acq_rel.gpu;" ::: "memory"); }
DI void fence_async() { asm volatile("fence.proxy.async.shared::cta;" ::: "memory"); }
DI uint32_t ad(uint32_t a, uint32_t o) { uint32_t r; asm("add.u32 %0, %1, %2;" : "=r"(r) : "r"(a), "r"(o)); return r; }
DI uint4 lds128(uint32_t a, int o) {
    uint4 v; asm volatile("ld.shared.v4.u32 {%0,%1,%2,%3}, [%4];" : "=r"(v.x), "=r"(v.y), "=r"(v.z), "=r"(v.w) : "r"(ad(a, o)) : "memory"); return v;
}
DI void lds128(uint32_t* v, uint32_t a, int o) {
    asm volatile("ld.shared.v4.u32 {%0,%1,%2,%3}, [%4];" : "=r"(v[0]), "=r"(v[1]), "=r"(v[2]), "=r"(v[3]) : "r"(ad(a, o)) : "memory");
}
DI void lds64(uint32_t* v, uint32_t a, int o) { asm volatile("ld.shared.v2.u32 {%0,%1}, [%2];" : "=r"(v[0]), "=r"(v[1]) : "r"(ad(a, o)) : "memory"); }
DI uint4 ldsm_t(uint32_t a, int o) {
    uint4 v; asm volatile("ldmatrix.sync.aligned.m8n8.x4.trans.shared.b16 {%0,%1,%2,%3}, [%4];" : "=r"(v.x), "=r"(v.y), "=r"(v.z), "=r"(v.w) : "r"(ad(a, o)) : "memory"); return v;
}
DI uint2 lds64(uint32_t a, int o) { uint2 v; asm volatile("ld.shared.v2.u32 {%0,%1}, [%2];" : "=r"(v.x), "=r"(v.y) : "r"(ad(a, o)) : "memory"); return v; }
DI float2 lds64f(uint32_t a, int o) { const uint2 v = lds64(a, o); return make_float2(__uint_as_float(v.x), __uint_as_float(v.y)); }
DI uint32_t lds32(uint32_t a, int o) { uint32_t v; asm volatile("ld.shared.u32 %0, [%1];" : "=r"(v) : "r"(ad(a, o)) : "memory"); return v; }
DI float ldsf(uint32_t a, int o) { return __uint_as_float(lds32(a, o)); }
DI void sts32(uint32_t a, int o, uint32_t v) { asm volatile("st.shared.u32 [%0], %1;" :: "r"(ad(a, o)), "r"(v) : "memory"); }
DI void stsf(uint32_t a, int o, float v) { sts32(a, o, __float_as_uint(v)); }
DI void sts16(uint32_t a, int o, uint32_t v) { asm volatile("st.shared.u16 [%0], %1;" :: "r"(ad(a, o)), "h"((uint16_t)v) : "memory"); }
DI void sts64(uint32_t a, int o, uint32_t x, uint32_t y) { asm volatile("st.shared.v2.u32 [%0], {%1,%2};" :: "r"(ad(a, o)), "r"(x), "r"(y) : "memory"); }
DI void sts128(uint32_t a, int o, uint32_t x, uint32_t y, uint32_t z, uint32_t w) {
    asm volatile("st.shared.v4.u32 [%0], {%1,%2,%3,%4};" :: "r"(ad(a, o)), "r"(x), "r"(y), "r"(z), "r"(w) : "memory");
}
DI void sts128f_if(bool p, uint32_t a, int o, float x, float y, float z, float w) {
    asm volatile("{\n.reg .pred p;\nsetp.ne.u32 p, %5, 0;\n@p st.shared.v4.f32 [%0], {%1,%2,%3,%4};\n}" :: "r"(ad(a, o)), "f"(x), "f"(y), "f"(z), "f"(w), "r"((int)p) : "memory");
}
DI void sts32_if(bool p, uint32_t a, int o, uint32_t v) {
    asm volatile("{\n.reg .pred p;\nsetp.ne.u32 p, %2, 0;\n@p st.shared.u32 [%0], %1;\n}" :: "r"(ad(a, o)), "r"(v), "r"((int)p) : "memory");
}
DI uint32_t atoms_inc(uint32_t a, uint32_t lim) {
    uint32_t old; asm volatile("atom.relaxed.cta.shared.inc.u32 %0, [%1], %2;" : "=r"(old) : "r"(a), "r"(lim) : "memory"); return old;
}
DI void mma(float (&c)[4], uint32_t a0, uint32_t a1, uint32_t a2, uint32_t a3, uint32_t b0, uint32_t b1) {
    asm volatile("mma.sync.aligned.m16n8k16.row.col.f32.bf16.bf16.f32 {%0,%1,%2,%3}, {%4,%5,%6,%7}, {%8,%9}, {%0,%1,%2,%3};"
                 : "+f"(c[0]), "+f"(c[1]), "+f"(c[2]), "+f"(c[3]) : "r"(a0), "r"(a1), "r"(a2), "r"(a3), "r"(b0), "r"(b1));
}
DI void mma(float (&c)[4], const uint4& a, uint32_t b0, uint32_t b1) { mma(c, a.x, a.y, a.z, a.w, b0, b1); }
DI void zero4(float (&c)[4]) { c[0] = c[1] = c[2] = c[3] = 0.f; }
DI u64 ld_rlx(const void* p) {
    u64 a; asm volatile("ld.relaxed.gpu.global.u64 %0, [%1];" : "=l"(a) : "l"(p) : "memory"); return a;
}
DI void st_rlx(void* p, u64 a) { asm volatile("st.relaxed.gpu.global.u64 [%0], %1;" :: "l"(p), "l"(a) : "memory"); }
DI uint4 ldg128(const void* p) {
    uint4 v; asm volatile("ld.global.nc.L1::no_allocate.L2::cache_hint.v4.u32 {%0,%1,%2,%3}, [%4], %5;" : "=r"(v.x), "=r"(v.y), "=r"(v.z), "=r"(v.w) : "l"(p), "l"((u64)POL_FIRST << 32)); return v;
}
DI float bf_lo(uint32_t u) { return __uint_as_float(u << 16); }
DI float bf_hi(uint32_t u) { return __uint_as_float(u & 0xffff0000u); }
DI uint32_t pack_bf(float lo, float hi) {
    uint32_t r; asm("cvt.rn.bf16x2.f32 %0, %1, %2;" : "=r"(r) : "f"(hi), "f"(lo)); return r;
}
DI uint32_t pick(uint32_t a, uint32_t sel) { uint32_t r; asm("prmt.b32 %0, %1, 0, %2;" : "=r"(r) : "r"(a), "r"(sel)); return r; }
DI uint32_t bf2_amax(uint32_t a, uint32_t b) { uint32_t r; asm("max.NaN.xorsign.abs.bf16x2 %0, %1, %2;" : "=r"(r) : "r"(a), "r"(b)); return r; }
DI uint32_t bf2_amin(uint32_t a, uint32_t b) { uint32_t r; asm("min.xorsign.abs.bf16x2 %0, %1, %2;" : "=r"(r) : "r"(a), "r"(b)); return r; }
DI uint32_t bf2_mulv(uint32_t a, uint32_t b) { uint32_t r; asm volatile("mul.rn.bf16x2 %0, %2, %1;" : "=r"(r) : "r"(a), "r"(b)); return r; }
DI uint32_t bf2_mul(uint32_t a, uint32_t b) { uint32_t r; asm("mul.rn.bf16x2 %0, %1, %2;" : "=r"(r) : "r"(a), "r"(b)); return r; }
DI uint32_t bf2_fma(uint32_t a, uint32_t b, uint32_t c) { uint32_t r; asm("fma.rn.bf16x2 %0, %1, %2, %3;" : "=r"(r) : "r"(a), "r"(b), "r"(c)); return r; }
DI float ex2(float v) { float r; asm("ex2.approx.ftz.f32 %0, %1;" : "=f"(r) : "f"(v)); return r; }
DI float rcp(float v) { float r; asm("rcp.approx.ftz.f32 %0, %1;" : "=f"(r) : "f"(v)); return r; }
DI float rsq(float v) { float r; asm("rsqrt.approx.ftz.f32 %0, %1;" : "=f"(r) : "f"(v)); return r; }
DI void bar_sync(int id, int n) { asm volatile("bar.sync %0, %1;" :: "r"(id), "r"(n) : "memory"); }
DI uint32_t clk() { uint32_t c; asm volatile("mov.u32 %0, %clock;" : "=r"(c)); return c; }
DI uint32_t gtime() { uint32_t c; asm volatile("mov.u32 %0, %globaltimer_lo;" : "=r"(c)); return c; }
DI uint32_t pin(uint32_t v) { return __shfl_xor_sync(~0u, v, 0); }
DI float pinf(float v) { return __shfl_xor_sync(~0u, v, 0); }
template <class T> DI T* pinp(T* p) { return reinterpret_cast<T*>(__shfl_xor_sync(~0u, (u64)p, 0)); }
DI u64 mk64(uint32_t lo, uint32_t hi) { u64 r; asm("mov.b64 %0, {%1, %2};" : "=l"(r) : "r"(lo), "r"(hi)); return r; }
DI float shx(float v, int o) { return __shfl_xor_sync(~0u, v, o); }

DI u64 fx_pack(float v) {
    u64 r; asm("{\n.reg .u32 a, b;\n.reg .s64 w;\ncvt.rni.s64.f32 w, %1;\nmov.b64 {a, b}, w;\nprmt.b32 a, a, 1, 0x3214;\nmov.b64 %0, {a, b};\n}" : "=l"(r) : "f"(v)); return r;
}
DI float fx_scale(float meansq) {
    const int e = max(((int)(__float_as_uint(meansq) >> 23) - 127) >> 1, -14);
    return __uint_as_float((uint32_t)(127 + 32 - e) << 23);
}
DI float fx_inv(float scale) { return __uint_as_float((254u << 23) - __float_as_uint(scale)); }
DI uint32_t lo32(u64 w) { uint32_t l; asm("mov.b64 {%0, _}, %1;" : "=r"(l) : "l"(w)); return l; }
DI int hi32(u64 w) { int h; asm("mov.b64 {_, %0}, %1;" : "=r"(h) : "l"(w)); return h; }
DI float fx_val(u64 w) { return (float)hi32(w) * 4294967296.f + (float)lo32(w); }
DI void fx_poll(const unsigned char* ap, u64 (&w)[4]) {
    asm volatile("{\n.reg .pred p, q;\n.reg .u32 n, a, b, c, d;\nmov.u32 n, 0;\nLOOP:\n"
                 "ld.relaxed.gpu.global.u64 %0, [%4];\nld.relaxed.gpu.global.u64 %1, [%4+5120];\n"
                 "ld.relaxed.gpu.global.u64 %2, [%4+10240];\nld.relaxed.gpu.global.u64 %3, [%4+15360];\n"
                 "add.u32 n, n, 1;\nsetp.ge.u32 q, n, 0x100000;\n@q bra.uni DONE;\n"
                 "mov.b64 {a, _}, %0;\nmov.b64 {b, _}, %1;\nmov.b64 {c, _}, %2;\nmov.b64 {d, _}, %3;\n"
                 "lop3.b32 a, a, b, c, 0x80;\nlop3.b32 a, a, d, 32, 0x80;\nsetp.eq.u32 p, a, 0;\n"
                 "vote.sync.any.pred p, p, 0xffffffff;\n@p bra.uni LOOP;\nDONE:\n}"
                 : "=l"(w[0]), "=l"(w[1]), "=l"(w[2]), "=l"(w[3]) : "l"(ap) : "memory");
}
constexpr u64 FX2_INIT = 256ull + 32 - 96 * ((1ull << 28) + (1ull << 55)), FX2_NONE = 1ull + (1ull << 28) + (1ull << 55);
constexpr float FX2_MAGIC = 12582912.f + 524288.f;

DI void tma3(uint32_t dst, const CUtensorMap* tm, int c1, int c2, uint32_t bar, uint32_t pol) {
    asm volatile("cp.async.bulk.tensor.3d.shared::cluster.global.mbarrier::complete_tx::bytes.L2::cache_hint [%0], [%1, {%2, %3, %4}], [%5], %6;"
                 :: "r"(dst), "l"(tm), "r"(0), "r"(c1), "r"(c2), "r"(bar), "l"((u64)pol << 32) : "memory");
}
DI void tma3_pf(const CUtensorMap* tm, int c1, int c2, uint32_t pol) {
    asm volatile("cp.async.bulk.prefetch.tensor.3d.L2.global.tile.L2::cache_hint [%0, {%1, %2, %3}], %4;"
                 :: "l"(tm), "r"(0), "r"(c1), "r"(c2), "l"((u64)pol << 32) : "memory");
}
DI void bulk_pf(const void* p, uint32_t bytes, uint32_t pol) {
    asm volatile("cp.async.bulk.prefetch.L2.global.L2::cache_hint [%0], %1, %2;" :: "l"(p), "r"(bytes), "l"((u64)pol << 32) : "memory");
}
DI float warp_max(float v) {
    const int k = __float_as_int(v), m = __reduce_max_sync(~0u, k ^ ((k >> 31) & 0x7fffffff));
    return __int_as_float(m ^ ((m >> 31) & 0x7fffffff));
}
DI u64 ll_pack2(float a, float b, uint32_t tag) { return mk64(__byte_perm(__float_as_uint(a), tag, 0x3214), __float_as_uint(b)); }
DI float lof(u64 w) { return __uint_as_float(lo32(w)); }
DI float hif(u64 w) { return __int_as_float(hi32(w)); }
DI void ll_gather4(const u64* buf, uint32_t tag, u64 (&w)[4]) {
#pragma unroll 1
    for (int it = 0; it < SPIN; it++) {
        if (it) { w[0] = ld_rlx(buf); w[1] = ld_rlx(buf + 256); w[2] = ld_rlx(buf + 512); w[3] = ld_rlx(buf + 768); }
        if (!__any_sync(~0u, (((lo32(w[0]) ^ tag) | (lo32(w[1]) ^ tag)) | ((lo32(w[2]) ^ tag) | (lo32(w[3]) ^ tag))) & 255)) break;
    }
}
DI u64 lds_u64(uint32_t a, int o) { const uint2 v = lds64(a, o); return v.x | (u64)v.y << 32; }
DI float sum8(uint32_t a, int o, int pitch) {
    float s[8];
#pragma unroll
    for (int w = 0; w < 8; w++) s[w] = ldsf(a, o + w * pitch);
    return ((s[0] + s[1]) + (s[2] + s[3])) + ((s[4] + s[5]) + (s[6] + s[7]));
}
DI void ln_final(float& mean, float& rstd, float& msq) {
    float2 v[5];
#pragma unroll
    for (int w = 0; w < 5; w++) v[w] = lds64f(0, SM_STAT + w * 8);
    mean = (((v[0].x + v[1].x) + (v[2].x + v[3].x)) + v[4].x) * (1.f / D_MODEL);
    msq = (((v[0].y + v[1].y) + (v[2].y + v[3].y)) + v[4].y) * (1.f / D_MODEL);
    rstd = rsq(fmaxf(msq - mean * mean, 0.f) + 1e-5f);
}
constexpr float CS = 0.07216878364870322f * 1.4426950408889634f;
constexpr uint32_t ONES = 0x3f803f80u;

__global__ void __launch_bounds__(NTHR, 1) fused_kernel(const __grid_constant__ Params P) {
    extern __shared__ __align__(1024) unsigned char smem[];
    const int warp = __shfl_sync(~0u, threadIdx.x >> 5, 0), bx = blockIdx.x;
    const int cta = (((bx >> 1) & 15) + (bx >> 6) * 16) * 4 + ((bx >> 5) & 1) * 2 + (bx & 1);

    if (bx == NCTA) {
        if ((uint32_t)__cvta_generic_to_shared(smem) != SM_RING) __trap();
        const uint32_t ep = *(volatile unsigned*)&g_epoch;
        if (threadIdx.x == 0) {
#pragma unroll 1
            for (int it = 0; it < SPIN; it++) { if ((lo32(ld_rlx(&g_ll[0][192])) & 255) == ((ep * 8 + 1) & 255)) break; __nanosleep(200); }
            const uint32_t t0 = gtime();
#pragma unroll 1
            for (int it = 0; it < 1024; it++) { if (gtime() - t0 > HZD) break; __nanosleep(100); }
        }
        __syncthreads();
#pragma unroll 1
        for (int i = threadIdx.x; i < 4 * 80 * 8; i += NTHR)
        {
            const u64 v = (i / 640 & 1) && (i & 7) < 2 ? FX2_INIT : 0ull;
            *reinterpret_cast<ulonglong2*>(g_acc + (i >> 3) * ACC_PITCH + (i & 7) * 16) = make_ulonglong2(v, v);
        }
        __threadfence();
        __syncthreads();
        if (threadIdx.x == 0) asm volatile("st.relaxed.gpu.global.u32 [%0], %1;" :: "l"(&g_zflag), "r"(ep + 1) : "memory");
        return;
    }
    const uint32_t barw = SM_BAR + warp * 64;
    if (elect()) {
        if (warp < 3) sts32(0, SM_T0, gtime());
        else {
            mbar_init(barw + 56, 1);
            asm volatile("fence.mbarrier_init.release.cluster;" ::: "memory");
            mbar_expect(barw + 56, HT);
            tma3(SM_WQ - 3 * HT + warp * HT, &P.tm[TM_WQ], (cta >> 2) * 3, (cta & 3) * 160 - 96 + warp * 32, barw + 56, POL_FIRST);
        }
    }
    int tid = threadIdx.x, lane, g, t, c4;
    uint32_t selA, selB, offV0, offV2;
    auto derive = [&]() {
        lane = tid & 31; g = lane >> 2; t = lane & 3;
        c4 = (tid & 0xe1) + 16 * (t >> 1) + 2 * g;
        selA = (g & 2) ? 0x4444u : (g & 1) ? 0x1044u : 0x4410u;
        selB = (g & 2) ? ((g & 1) ? 0x1044u : 0x4410u) : 0x4444u;
        offV0 = (6 * t) * 128 + ((g ^ ((6 * t) & 7)) << 4);
        offV2 = (6 * t) * 128 + ((g ^ ((6 * t + 2) & 7)) << 4);
    };
    auto refresh = [&]() { tid = pin(tid); derive(); };
    auto refresh_late = [&]() { mbar_wait(SM_BAR + 3 * 64 + 56, 0); refresh(); };
    derive();
    const uint32_t zero = bx >> 16;
    const int j40 = (cta & 3) * 40;
    const bool mlp = (cta & 3) != 3;
    const int hu = ((cta >> 2) * 3 + (cta & 3)) * 16;
    uint2 xp = make_uint2(0, 0);
    uint32_t kc[192];
    const int rowc = (cta >> 2) * SK + (SK - WIN) + (cta & 3) * 64;
    const int roww = __shfl_sync(~0u, rowc + warp * 8, 0);
    const CUtensorMap* tmk = reinterpret_cast<const CUtensorMap*>(__shfl_sync(~0u, (u64)&P.tm[0] + (lane >> 5), 0));

    auto wait_due = [&](int i, int extra) {
        const uint32_t due = lds32(0, SM_T0) + PACE0 + extra + i * PACE;
#pragma unroll 1
        for (int it = 0; it < 4096; it++) if ((int)(gtime() - due) >= 0) break;
    };
    auto issue_wo = [&](int k) {
        wait_due(64, k * WOPACE);
        mbar_expect(SM_CBAR + 32 + k * 8, 4 * WOU);
        asm volatile("cp.async.bulk.tensor.4d.shared::cluster.global.mbarrier::complete_tx::bytes.L2::cache_hint [%0], [%1, {%2, %3, %4, %5}], [%6], %7;"
                     :: "r"(SM_RING + k * 4 * WOU), "l"(tmk + TM_WO4), "r"(0), "r"(5 * (cta & 3)), "r"((k >> 1) * 8), "r"((cta >> 2) * 8 + (k & 1) * 4),
                        "r"(SM_CBAR + 32 + k * 8), "l"((u64)POL_FIRST << 32) : "memory");
        if (k < 4 && mlp)
            asm volatile("cp.async.bulk.prefetch.tensor.4d.L2.global.tile.L2::cache_hint [%0, {%1, %2, %3, %4}], %5;"
                         :: "l"(tmk + TM_WOP), "r"(0), "r"(5 * (cta & 3)), "r"((k >> 1) * 8), "r"((cta >> 2) * 8 + (k & 1) * 4), "l"((u64)POL_NORMAL << 32) : "memory");
    };
    auto issue_kv = [&](int i, int slot, int bar) {
        const int row = rowc + (i & 30) * 128 + (i & 1) * 32;
        mbar_expect(SM_CBAR + bar * 8, HT);
        tma3(SM_RING + slot * HT, tmk + TM_K + (i >> 5), 0, row, SM_CBAR + bar * 8, POL_FIRST);
        if (i >= 32) tma3_pf(tmk + TM_VP, 0, row, POL_NORMAL);
    };
    auto ep8 = [&]() { return lds32(0, SM_EPOCH); };
    auto load_v3 = [&](uint4* v, uint32_t u, int o, bool odd) {
        if (!odd) { v[0] = lds128(ad(offV0, u), o); v[1] = lds128(ad(offV0 ^ 16, u), o + 128); v[2] = lds128(ad(offV2, u), o + 256); }
        else { v[0] = lds128(ad(offV2 ^ 16, u), o + 384); v[1] = lds128(ad(offV0 ^ 64, u), o + 512); v[2] = lds128(ad(offV0 ^ 80, u), o + 640); }
    };
    auto load_v = [&](uint4 (&v)[6], uint32_t u, int o) { load_v3(v, u, o, false); load_v3(v + 3, u, o, true); };
    const uint32_t wqw = warp * SUB, ksw = warp * HT;
    auto slot_o = [&](int s) { return s < 3 ? SM_WQ + s * 8 * SUB : SM_KS + (s - 3) * SUB; };
    auto slot_u = [&](int s) { return s < 3 ? wqw : ksw; };
    auto issue2 = [&](auto I, uint32_t dep) {
        constexpr int p = I.value, s = PL.slot[p];
        __syncwarp();
        if ((p < 16 || mlp) && elect()) {
            mbar_expect(barw + s * 8, (dep & zero) | (p < 16 ? SUB : 2 * WOU + 256));
            if constexpr (p < 16) tma3(slot_u(s) + slot_o(s), tmk + TM_V8, 0, roww + vunit(p) * 256, barw + s * 8, POL_FIRST);
            else {
                tma3(slot_u(s) + slot_o(s), tmk + TM_WO, 5 * (cta & 3), (cta >> 2) * DH + warp * 24, barw + s * 8, POL_FIRST);
                asm volatile("cp.async.bulk.shared::cluster.global.mbarrier::complete_tx::bytes [%0], [%1], 256, [%2];"
                             :: "r"(slot_u(s) + slot_o(s) + 2 * WOU), "l"(P.b2 + min(warp, 4) * 128), "r"(barw + s * 8) : "memory");
            }
        }
    };
    auto touch2 = [&]() {
        const char* p = reinterpret_cast<const char*>(P.v) + (size_t)(roww + vunit(2) * 256) * (DH * 2) + lane * 32;
#pragma unroll
        for (int i = 0; i < 3; i++) asm volatile("cp.async.ca.shared.global [%0], [%1], 4;" :: "r"(SM_JUNK), "l"(p + i * 1024) : "memory");
    };
    auto issue_help = [&]() {
        if (elect())
            tma3(SM_WQ + (warp == 7 ? 0 : warp == 6 ? 16 * SUB : 4 * SUB), tmk + (warp == 5 ? TM_V8 : TM_V), 0,
                 rowc + (warp == 6 ? vunit(2) * 256 : warp == 5 ? vunit(0) * 256 + 32 : vunit(0) * 256), warp == 5 ? SM_BAR + 4 * 64 : SM_CBAR - 32 + warp * 8, POL_FIRST);
    };
    auto issue_item1 = [&]() {
        if (elect()) {
            mbar_expect(SM_CBAR - 48 + warp * 8, HT);
            tma3(SM_WQ - 4 * HT + warp * HT, tmk + TM_V, 0, rowc - 192 + warp * 32 + vunit(1) * 256, SM_CBAR - 48 + warp * 8, POL_FIRST);
        }
    };
    const uint32_t prow = warp * 768;
    uint4 wq0[6], wqh[3];
    uint32_t xna;
    auto load_wq = [&]() {
        load_v(wq0, wqw, SM_WQ);
        const int r0 = 6 * t + 3 * (warp & 1);
#pragma unroll
        for (int j = 0; j < 3; j++) wqh[j] = lds128(ad(r0 * 128 + ((g ^ ((r0 + j) & 7)) << 4), (warp >> 1) * SUB), SM_WQ + 16 * SUB + j * 128);
        const int r = c4 - j40;
        xna = pin((tid < 160 && r >= 0 && r < 40) ? SM_VEC + r * 8 : 0u);
        selA = pin(selA); selB = pin(selB);
        offV0 = pin(offV0 + wqw); offV2 = pin(offV2 + wqw);
        tid = pin(tid);
    };
    float acc[3][4];
    auto mma3 = [&](const uint4* v, uint32_t pp, uint32_t hi) {
        const uint32_t b0 = pick(pp, selA | hi), b1 = pick(pp, selB | hi);
        mma(acc[0], v[0], b0, b1); mma(acc[1], v[1], b0, b1); mma(acc[2], v[2], b0, b1);
    };
    auto ln_part = [&]() {
        const float x0 = bf_lo(xp.x), x1 = bf_hi(xp.x), x2 = bf_lo(xp.y), x3 = bf_hi(xp.y);
        const float s1 = (x0 + x1) + (x2 + x3), s2 = (x0 * x0 + x1 * x1) + (x2 * x2 + x3 * x3);
        float ss = ((tid & 16) ? s2 : s1) + shx((tid & 16) ? s1 : s2, 16);
        ss += shx(ss, 8); ss += shx(ss, 4); ss += shx(ss, 2); ss += shx(ss, 1);
        sts32_if((tid & 15) == 0 && tid < 160, tid >> 2, SM_STAT, __float_as_uint(ss));
    };

    auto tick = [&](uint4& v) {
        asm volatile("{\n.reg .pred p;\nsetp.ne.u32 p, %4, 0;\n@p mma.sync.aligned.m16n8k16.row.col.f32.bf16.bf16.f32 {%0,%1,%2,%3}, {%0,%1,%2,%3}, {%0,%1}, {%0,%1,%2,%3};\n}"
                     : "+r"(v.x), "+r"(v.y), "+r"(v.z), "+r"(v.w) : "r"(zero));
    };

    auto q_stage = [&](auto L) {
        constexpr int layer = L.value;
        asm volatile("{\n.reg .pred p;\nsetp.ne.u32 p, %0, 0;\n@p st.shared.v2.u32 [%0], {%1,%2};\n}" :: "r"(xna), "r"(xp.x), "r"(xp.y) : "memory");
        uint4 wq1[6];
        load_v3(wq1, 0, SM_WQ + 8 * SUB, false);
        const uint32_t xra = (tid & 3) * 4;
        __syncthreads();
        uint32_t p0 = lds32(ad(xra, warp * 16), SM_VEC), ph = lds32(ad(xra, (warp >> 1) * 16), SM_VEC + 256), p1 = lds32(ad(xra, warp * 16), SM_VEC + 128);
        if (layer == 0 && (tid & 16)) p0 = p1 = ph = ONES;
#pragma unroll
        for (int j = 0; j < 3; j++) zero4(acc[j]);
        mma3(wq0, p0, 0); mma3(wq0 + 3, p0, 0x2222);
        load_v3(wq1 + 3, 0, SM_WQ + 8 * SUB, true);
        mma3(wqh, ph, (warp & 1) * 0x2222); mma3(wq1, p1, 0); mma3(wq1 + 3, p1, 0x2222);
        if (layer == 1) { lds128(kc + 8, prow + (tid & 31) * 16, SM_PART); lds64(kc + 180, prow + (tid & 31) * 8, SM_PART + 512); __syncwarp(); }
        const uint32_t qpa = ((layer == 0 && (tid & 2)) ? ksw - (SM_PART - SM_KS - 11264) : prow) + (tid & 28) * 8 + (tid & 1) * 16;
#pragma unroll
        for (int j = 0; j < 3; j++) sts128f_if(layer == 0 || !(tid & 2), qpa, SM_PART + j * 256, acc[j][0], acc[j][1], acc[j][2], acc[j][3]);
        u64* dst = &g_ll[cta][tid];
        const uint32_t tag = ep8() + 1 + 4 * layer;
        __syncthreads();
        if (warp < 6) {
            const float s = sum8(tid * 4, SM_PART, 768);
            st_rlx(dst, layer ? mk64(tag, __float_as_uint(s)) : ll_pack2(__uint_as_float(__float_as_uint(sum8(tid * 4, SM_KS + 11264, HT)) + 128), s, tag));
        } else if (layer == 1) { sts32(0, SM_T0, gtime()); issue_item1(); }
        refresh_late();
        ln_part();
        __syncthreads();
        sts64(prow + lane * 8, SM_PART, xp.x, xp.y);
        if (layer == 1) sts128(prow + lane * 16, SM_PART + 256, kc[8], kc[9], kc[10], kc[11]);
    };
    auto q_addr = [&]() { return (((tid >> 1) & 1) * 4 + ((tid >> 4) & 3)) * 48 + ((tid >> 6) * 2 + ((tid >> 3) & 1)) * 8 + ((tid >> 2) & 1) * 4 + (tid & 1) * 2; };
    auto score6 = [&](const uint4 (&v)[6], const uint32_t (&qf)[12]) {
        float d[2][4];
#pragma unroll
        for (int i = 0; i < 6; i++) { if (i < 2) zero4(d[i]); mma(d[i & 1], v[i], qf[2 * i], qf[2 * i + 1]); }
        return (d[0][0] + d[0][3]) + (d[1][0] + d[1][3]);
    };
    auto softmax = [&](auto L, const float (&S)[4]) {
        constexpr int layer = L.value;
        const float mrun = warp_max(fmaxf(fmaxf(S[0], S[1]), fmaxf(S[2], S[3])));
        const float p0 = ex2((S[0] - mrun) * CS), p1 = ex2((S[1] - mrun) * CS), p2 = ex2((S[2] - mrun) * CS), p3 = ex2((S[3] - mrun) * CS);
        const uint32_t pa = pack_bf(p0, p1), pb = pack_bf(p2, p3), pw = prow + t * 64 + g * 2;
        sts16(pw, SM_PART + 256, pa); sts16(pw, SM_PART + 272, pa >> 16); sts16(pw, SM_PART + 288, pb); sts16(pw, SM_PART + 304, pb >> 16);
        const uint32_t l = __reduce_add_sync(~0u, __float2uint_rn(((p0 + p1) + (p2 + p3)) * 16777216.f));
        st_rlx(&g_ll[cta][192 + warp], mk64(__byte_perm(l + 128, ep8() + 1 + 4 * layer, 0x3214), __float_as_uint(mrun)));
        __syncwarp();
#pragma unroll
        for (int j = 0; j < 3; j++) zero4(acc[j]);
    };
    auto pv = [&](const uint4 (&v)[6], uint32_t pp) { mma3(v, pp, 0); mma3(v + 3, pp, 0x2222); };

    auto head_look = [&]() {
        if (lane < 16) asm volatile("cp.async.cg.shared.global [%0], [%1], 16;" :: "r"(SM_PART + 512 + prow + lane * 16), "l"(&g_ll[cta ^ g][192 + 2 * t]) : "memory");
    };
    float fw;
    auto head_weight = [&](auto L) {
        const uint32_t tag = (ep8() + 1 + 4 * L.value) & 255;
        uint32_t l, m;
#pragma unroll 1
        for (int it = 0; it < SPIN; it++) {
            if (it) head_look();
            asm volatile("cp.async.wait_all;" ::: "memory");
            __syncwarp();
            asm volatile("ld.volatile.shared.v2.u32 {%0,%1}, [%2];" : "=r"(l), "=r"(m) : "r"(SM_PART + 512 + prow + lane * 8) : "memory");
            l ^= tag;
            if (!__any_sync(~0u, l & 255)) break;
        }
        const float f = ex2((__uint_as_float(m) - warp_max(__uint_as_float(m))) * CS);
        const uint32_t Lh = __reduce_add_sync(~0u, __float2uint_rn(f * (float)l * 0.03125f));
        fw = __shfl_sync(~0u, f, warp) * rcp((float)Lh) * (ldsf(0, SM_FXS) * 524288.f);
    };

    uint32_t wa[5], ya, oa, selC, selD, tag;
    uint4 z[5];
    unsigned char* ra;
    const u64* lp;
    auto load_u = [&](uint4 (&a)[5], uint32_t u, int o) {
#pragma unroll
        for (int k = 0; k < 5; k++) a[k] = lds128(ad(wa[k], u), o);
    };
    auto tail_prep1 = [&](auto L) {
        xp = lds64(prow + lane * 8, SM_PART);
        tag = (ep8() + 3 + 4 * L.value) & 255;
        ya = pin(prow + (8 * g + 4 * (t & 1)) * 4);
        oa = pin(((tid >> 5) * 12 + min(lane, 11)) * 8);
        lp = pinp(reinterpret_cast<const u64*>(reinterpret_cast<const char*>(&g_ll[cta][0]) + oa));
    };
    auto tail_prep2 = [&](auto L) {
#pragma unroll
        for (int k = 0; k < 5; k++) {
            const int row = (t & 1) + 2 * (t & 2) + 2 * (k < 4 ? k >> 1 : g >> 2), j = k < 4 ? 2 * (k & 1) + (g >> 2) : 4;
            wa[k] = pin(row * 320 + j * 64 + (((g & 3) ^ (((5 * row + j) >> 1) & 3)) << 4));
        }
        selA = pin(selA); selB = pin(selB);
        selC = selA | (g >> 2) * 0x2222; selD = selB | (g >> 2) * 0x2222;
    };
    auto red_addr = [&](auto L) {
        const int word = t * 160 + j40 + (tid >> 2);
        ra = pinp(g_acc + 2 * L.value * ACC_BYTES + (uint32_t)((word >> 3) * ACC_PITCH + (word & 7) * 8));
    };
    uint4 wf[8], w2r[8];
    uint32_t la, w2a, hpa, ha, *op;
    uint2 b2v;
    const unsigned char* ap;
    unsigned char* ap2;
    float inv1;
    auto load_w1 = [&]() {
#pragma unroll
        for (int j = 0; j < 8; j++) wf[j] = ldsm_t(la, SM_RING + j * 256);
    };
    auto load_w2 = [&]() {
#pragma unroll
        for (int i = 0; i < 8; i++) w2r[i] = lds128(w2a ^ ((i & 1) * 16), SM_W2 + (i >> 1) * 5120 + (i & 1) * 128);
    };
    auto load_b2 = [&]() { asm volatile("ld.global.nc.v2.u32 {%0,%1}, [%2];" : "=r"(b2v.x), "=r"(b2v.y) : "l"(P.b2 + 4 * min(c4, 159))); };
    auto mlp_prep = [&](auto L) {
        unsigned char* const accb = g_acc + 2 * L.value * ACC_BYTES;
        la = (tid >> 5) * 4096 + (64 * ((lane >> 2) & 1) + 4 * ((lane >> 1) & 1) + (lane & 1) + 2 * (lane >> 4)) * 32 + ((((lane >> 3) ^ (lane >> 1)) & 1) << 4);
        w2a = pin((10 * t + 2 * (tid >> 5)) * 128 + ((g ^ ((2 * t + 2 * (tid >> 5)) & 7)) << 4));
        hpa = pin((tid >> 5) * 64 + (t * 8 + g) * 4); ha = pin((lane & 15) * 4);
        if (L.value == 0) { selA = pin(selA); selB = pin(selB); tid = pin(tid); }
        ap = accb + (uint32_t)((c4 >> 3) * ACC_PITCH + (c4 & 7) * 8);
        ap2 = accb + ACC_BYTES + pin((c4 >> 2) * ACC_PITCH + (c4 & 3) * 8);
        if (L.value == 1) ap2 = pinp(ap2);
        inv1 = fx_inv(ldsf(0, SM_FXS));
        if (L.value == 1) { ap = pinp(ap); la = pin(la); op = pinp(reinterpret_cast<uint32_t*>(P.out) + 2 * c4); }
    };
    auto tail = [&](auto L) {
        constexpr int layer = L.value;
        uint32_t cq;
        auto park = [&]() { const int ln = pin(tid) & 31; sts128(prow + ln * 16, SM_PART, kc[8], kc[9], kc[10], kc[11]); sts64(prow + ln * 8, SM_PART + 512, kc[180], kc[181]); };
        {
#pragma unroll
            for (int j = 0; j < 3; j++) sts128f_if(!(tid & 2), ya, SM_PART + 256 * j, acc[j][0] * fw, acc[j][2] * fw, acc[j][1] * fw, acc[j][3] * fw);
            __syncthreads();
            float2 own;
            {
                float2 s[8];
#pragma unroll
                for (int w = 0; w < 8; w++) s[w] = lds64f(oa, SM_PART + w * 768);
                own.x = ((s[0].x + s[1].x) + (s[2].x + s[3].x)) + ((s[4].x + s[5].x) + (s[6].x + s[7].x));
                own.y = ((s[0].y + s[1].y) + (s[2].y + s[3].y)) + ((s[4].y + s[5].y) + (s[6].y + s[7].y));
                st_rlx(const_cast<u64*>(lp), ll_pack2(own.x, own.y, tag));
            }
            const uint32_t c0 = clk();
            if (layer == 0) refresh_late();
            uint4 v[5], u[5];
            if constexpr (layer == 0) {
                if (warp < 3) { if (elect()) issue_wo(3 + warp); __syncwarp(); }
                if (warp >= 4) touch2();
                tail_prep2(L);
                mbar_wait(SM_CBAR + 32 + (warp >> 2) * 8, 0);
                load_u(v, warp * WOU, SM_RING);
                __syncthreads();
            }
            constexpr int YP = layer ? SM_WQ : SM_PART;
            float y[5][4];
#pragma unroll
            for (int j = 0; j < 5; j++) zero4(y[j]);
            const u64 *l1 = reinterpret_cast<const u64*>((u64)lp ^ 4096), *l2 = reinterpret_cast<const u64*>((u64)lp ^ 2048), *l3 = reinterpret_cast<const u64*>((u64)lp ^ 6144);
            tick(layer ? z[0] : v[0]);
            if (layer) while (clk() - c0 < ODELAY);
            uint32_t w1due = 0;
            if (layer == 0) {
                const uint32_t now = gtime();
                w1due = lds32(0, SM_T0) + PACE0 + 69 * PACE + W1D;
                w1due = ((int)(now - w1due) > 0 ? now : w1due) + (warp - 3) * W1G;
            }
            u64 w1 = ld_rlx(l1), w2 = ld_rlx(l2), w3 = ld_rlx(l3);
            if constexpr (layer == 1) {
                if (mlp) mbar_wait(barw + 40, IC<PL.par[16]>::value);
                load_u(v, mlp ? ksw + slot_o(5) : SM_RING + warp * WOU, 0); load_u(u, mlp ? ksw + slot_o(5) + WOU : SM_RING + (8 + warp) * WOU, 0);
            }
            if (layer == 0 && warp >= 3 && mlp) {
#pragma unroll 1
                for (int it = 0; it < 4096; it++) { tick(v[0]); if ((int)(gtime() - w1due) >= 0) break; }
                if (elect()) {
                    mbar_expect(SM_CBAR + 56 + warp * 8, 4096);
                    asm volatile("cp.async.bulk.tensor.2d.shared::cluster.global.mbarrier::complete_tx::bytes.L2::cache_hint [%0], [%1, {%2, %3}], [%4], %5;"
                                 :: "r"(SM_RING + (warp - 3) * 4096), "l"(tmk + TM_W1), "r"(hu), "r"(warp * 128 - 384), "r"(SM_CBAR + 56 + warp * 8), "l"((u64)POL_FIRST << 32) : "memory");
                }
                __syncwarp();
            }
#pragma unroll 1
            for (int it = 0; it < SPIN; it++) {
                if (it) { w1 = ld_rlx(l1); w2 = ld_rlx(l2); w3 = ld_rlx(l3); }
                if (!__any_sync(~0u, ((lo32(w1) ^ tag) | (lo32(w2) ^ tag) | (lo32(w3) ^ tag)) & 255)) break;
            }
            const uint32_t od = pack_bf((own.x + __uint_as_float(lo32(w1) ^ tag)) + (__uint_as_float(lo32(w2) ^ tag) + __uint_as_float(lo32(w3) ^ tag)),
                                        (own.y + __int_as_float(hi32(w1))) + (__int_as_float(hi32(w2)) + __int_as_float(hi32(w3))));
            const uint32_t o0 = __shfl_sync(~0u, od, tid & 3), o1 = __shfl_sync(~0u, od, (tid & 3) + 4), o2 = __shfl_sync(~0u, od, (tid & 3) + 8);
            auto narrow = [&](const uint4 (&a)[5], uint32_t o) { mma(y[2], a[4], pick(o, selC), pick(o, selD)); };
            auto wide = [&](const uint4 (&a)[5], uint32_t o) {
                const uint32_t b0 = pick(o, selA), b1 = pick(o, selB), b2 = pick(o, selA | 0x2222), b3 = pick(o, selB | 0x2222);
                mma(y[0], a[0], b0, b1); mma(y[1], a[1], b0, b1); mma(y[3 * layer], a[2], b2, b3); mma(y[3 * layer + 1], a[3], b2, b3);
            };
            if constexpr (layer == 0) {
                narrow(v, o0); wide(v, o0);
                mbar_wait(SM_CBAR + 48 + (warp >> 2) * 8, 0);
                load_u(u, warp * WOU, SM_RING + 8 * WOU);
                __syncwarp();
                if (mlp && elect() && atoms_inc(SM_CNT + 44, 7) == 7) { mbar_expect(SM_CBAR + 120, 20480); tma3(SM_W2, tmk + TM_W2, 0, hu, SM_CBAR + 120, POL_FIRST); }
                __syncwarp();
                narrow(u, o1); wide(u, o1);
                red_addr(L);
                mbar_wait(SM_CBAR + 64 + (warp >> 2) * 8, 0);
                load_u(z, warp * WOU, SM_RING + 16 * WOU);
                narrow(z, o2); wide(z, o2);
            } else {
                narrow(z, o2); wide(z, o2); narrow(v, o0); narrow(u, o1); wide(v, o0); wide(u, o1);
#pragma unroll
                for (int k = 0; k < 4; k++) { y[0][k] += y[3][k]; y[1][k] += y[4][k]; }
            }
#pragma unroll
            for (int k = 0; k < 4; k++) y[2][k] += shx(y[2][k], 18);
            sts128f_if(!(tid & 18), ya, YP + 512, y[2][0], y[2][1], y[2][2], y[2][3]);
            sts128f_if(!(tid & 2), ya, YP, y[0][0], y[0][1], y[0][2], y[0][3]);
            sts128f_if(!(tid & 2), ya, YP + 256, y[1][0], y[1][1], y[1][2], y[1][3]);
            __syncthreads();
            if (warp < 5) {
                const float s = sum8(tid * 4, YP, 768);
                asm volatile("red.relaxed.gpu.global.add.u64 [%0], %1;" :: "l"(ra), "l"(fx_pack(s)) : "memory");
            }
            cq = clk();
            if (layer == 0) refresh_late();
        }
        if (layer == 1 && !mlp) return;
        if (warp < 5) {
            if (layer == 0) { mlp_prep(L); if (mlp) mbar_wait(SM_CBAR + 80 + warp * 8, 0); }
            load_w1();
            if (layer == 1) { load_w2(); b2v = lds64(ksw + (c4 & 31) * 8, SM_KS + 11264); }
            {
                u64 w[4];
                while (clk() - cq < (layer || mlp ? AR1D : AR1DN));
                fx_poll(ap, w);
                xp = make_uint2(pack_bf(bf_lo(xp.x) + fx_val(w[0]) * inv1, bf_hi(xp.x) + fx_val(w[1]) * inv1),
                                pack_bf(bf_lo(xp.y) + fx_val(w[2]) * inv1, bf_hi(xp.y) + fx_val(w[3]) * inv1));
            }
            {
                const bool ev = layer || !(tid & 4), od = layer || (tid & 4);
                const uint32_t e0 = ev ? xp.x : ONES, e1 = ev ? xp.y : ONES, o0 = od ? xp.x : ONES, o1 = od ? xp.y : ONES;
                float d[8][4];
#pragma unroll
                for (int j = 0; j < 8; j++) { zero4(d[j]); mma(d[j], wf[j], (j & 1) ? o0 : e0, (j & 1) ? o1 : e1); }
                float lo = d[0][0] + d[1][1], hi = d[0][2] + d[1][3];
#pragma unroll
                for (int m = 1; m < 4; m++)
                    asm("{\n.reg .pred p;\nsetp.eq.u32 p, %6, %7;\n@p add.f32 %0, %2, %3;\n@p add.f32 %1, %4, %5;\n}" : "+f"(lo), "+f"(hi)
                        : "f"(d[2 * m][0]), "f"(d[2 * m + 1][1]), "f"(d[2 * m][2]), "f"(d[2 * m + 1][3]), "r"(tid & 3), "r"(m));
                float dd = ((tid & 1) ? hi : lo) + shx((tid & 1) ? lo : hi, 1);
                dd += shx(dd, 2);
                ln_part();
                if (layer == 0) {
                    const float cl = ((d[0][1] + d[1][0]) + (d[2][1] + d[3][0])) + ((d[4][1] + d[5][0]) + (d[6][1] + d[7][0]));
                    const float ch = ((d[0][3] + d[1][2]) + (d[2][3] + d[3][2])) + ((d[4][3] + d[5][2]) + (d[6][3] + d[7][2]));
                    sts32_if(!(tid & 2), hpa, SM_C1, __float_as_uint((tid & 1) ? ch : cl));
                }
                sts32_if(!(tid & 2), hpa, SM_QU, __float_as_uint(dd));
            }
            const float b1v = ldsf(ha, SM_B1);
            float csum = layer ? ldsf(ha, SM_B1 + 64) : 0.f;
            bar_sync(1, layer ? 160 : 192);
            float mean, rstd, msq;
            ln_final(mean, rstd, msq);
            float hp[5];
#pragma unroll
            for (int w = 0; w < 5; w++) hp[w] = ldsf(ha, SM_QU + w * 64);
            if constexpr (layer == 0) {
                float c[5];
#pragma unroll
                for (int w = 0; w < 5; w++) c[w] = ldsf(ha, SM_C1 + w * 64);
                csum = ((c[0] + c[1]) + (c[2] + c[3])) + c[4];
                load_w2();
            }
            float hv = ((((hp[0] + hp[1]) + (hp[2] + hp[3])) + hp[4]) - mean * csum) * rstd + b1v;
            hv = hv * rcp(1.f + ex2(hv * (-2.302208198f - 0.1029432397f * hv * hv)));
            const uint32_t hd = pack_bf(hv, hv);
            float ym[4][4];
            const uint32_t hh[4] = {__shfl_sync(~0u, hd, tid & 3), __shfl_sync(~0u, hd, (tid & 3) + 4), __shfl_sync(~0u, hd, (tid & 3) + 8), __shfl_sync(~0u, hd, (tid & 3) + 12)};
#pragma unroll
            for (int i = 0; i < 4; i++) {
                const uint32_t b0 = pick(hh[i], selA), b1 = pick(hh[i], selB);
                if (i < 2) { zero4(ym[2 * i]); zero4(ym[2 * i + 1]); }
                mma(ym[2 * (i & 1)], w2r[2 * i], b0, b1); mma(ym[2 * (i & 1) + 1], w2r[2 * i + 1], b0, b1);
            }
            const float sc2 = __uint_as_float((uint32_t)(127 + 16 - max(((int)(__float_as_uint(msq) >> 23) - 127) >> 1, -100)) << 23);
            float y[4];
            uint32_t yb[4];
#pragma unroll
            for (int k = 0; k < 4; k++) { y[k] = ((tid & 2) ? ym[1][k] : ym[0][k]) + ((tid & 2) ? ym[3][k] : ym[2][k]); yb[k] = __float_as_uint(fmaf(y[k], sc2, FX2_MAGIC)); }
            const uint32_t big = !mlp ? 0 : (((yb[0] ^ 0x4b400000u) | (yb[1] ^ 0x4b400000u)) | ((yb[2] ^ 0x4b400000u) | (yb[3] ^ 0x4b400000u))) & FX2_MASK;
            u64 w[2], old[2];
#pragma unroll
            for (int k = 0; k < 2; k++) {
                w[k] = mk64(big ? 0 : yb[2 * k] * 512 + 0x80000001u, big ? 0 : yb[2 * k + 1] * 16 + 0x4c000000u);
                if (layer == 0) { if (mlp) asm volatile("red.relaxed.gpu.global.add.u64 [%0], %1;" :: "l"(ap2 + k * 40 * ACC_PITCH), "l"(w[k]) : "memory"); }
                else asm volatile("atom.relaxed.gpu.global.add.u64 %0, [%1], %2;" : "=l"(old[k]) : "l"(ap2 + k * 40 * ACC_PITCH), "l"(w[k]) : "memory");
            }
            const uint32_t c0 = clk();
            if (__any_sync(~0u, big)) {
                if (big) {
#pragma unroll
                    for (int k = 0; k < 4; k++)
                        asm volatile("red.relaxed.gpu.global.add.u64 [%0], %1;" :: "l"(ap2 + (k >> 1) * 40 * ACC_PITCH + 64 + (k & 1) * 32), "l"(fx_pack(y[k] * fx_scale(msq))) : "memory");
                    fence_gpu();
#pragma unroll
                    for (int k = 0; k < 2; k++) {
                        asm volatile("red.relaxed.gpu.global.and.b64 [%0], %1;" :: "l"(ap2 + k * 40 * ACC_PITCH), "l"(~256ull) : "memory");
                        w[k] = FX2_NONE;
                        asm volatile("atom.relaxed.gpu.global.add.u64 %0, [%1], %2;" : "=l"(old[k]) : "l"(ap2 + k * 40 * ACC_PITCH), "l"(FX2_NONE) : "memory");
                    }
                }
                __syncwarp();
            }
            if (layer == 0) { refresh(); load_b2(); park(); stsf(ha, SM_B1 + 64, csum); }
            stsf(0, SM_FXS, msq);
            const float inv32 = fx_inv(sc2) * 0.03125f;
            float xb[4] = {bf_lo(xp.x) + bf_lo(b2v.x) - 24.f * inv32, bf_hi(xp.x) + bf_hi(b2v.x), bf_lo(xp.y) + bf_lo(b2v.y) - 24.f * inv32, bf_hi(xp.y) + bf_hi(b2v.y)};
            auto add_wide = [&]() {
                fence_gpu();
                const float inv = fx_inv(fx_scale(ldsf(0, SM_FXS)));
#pragma unroll
                for (int k = 0; k < 4; k++) xb[k] += fx_val(ld_rlx(ap2 + (k >> 1) * 40 * ACC_PITCH + 64 + (k & 1) * 32)) * inv;
            };
            auto sum2 = [&](int k) {
                return pack_bf(xb[2 * k] + (float)(int)__funnelshift_r(lo32(w[k]), hi32(w[k]), 4) * inv32, xb[2 * k + 1] + (float)hi32(w[k]) * (inv32 + inv32));
            };
            if constexpr (layer == 1) {
#pragma unroll
                for (int k = 0; k < 4; k++) xb[k] = pinf(xb[k]);
                mbar_wait(SM_BAR + 3 * 64 + 56, 0);
#pragma unroll
                for (int k = 0; k < 2; k++) {
                    w[k] += old[k];
                    asm volatile("{\n.reg .pred p;\nsetp.eq.u32 p, %2, 0;\n@p st.global.u32 [%0], %1;\n}" :: "l"(op + k), "r"(sum2(k)), "r"(~lo32(w[k]) & 0x180) : "memory");
                }
                if (((lo32(w[0]) & ~(lo32(w[0]) >> 1)) | (lo32(w[1]) & ~(lo32(w[1]) >> 1))) & 128) {
                    add_wide();
                    if (w[0] & 128) op[0] = sum2(0);
                    if (w[1] & 128) op[1] = sum2(1);
                }
            } else {
                load_wq();
                __syncwarp();
                if (elect()) mbar_arrive(SM_BAR + 56);
#pragma unroll
                for (int k = 0; k < 4; k++) xb[k] = pinf(xb[k]);
                while (clk() - c0 < AR2D);
                uint32_t want = 0x180;
#pragma unroll 1
                for (int it = 0; it < SPIN; it++) {
                    if (it && !__any_sync(~0u, ~(lo32(w[0]) & lo32(w[1])) & 128)) { add_wide(); want = 128; }
                    w[0] = ld_rlx(ap2); w[1] = ld_rlx(ap2 + 40 * ACC_PITCH);
                    if (!__any_sync(~0u, ~(lo32(w[0]) & lo32(w[1])) & want)) break;
                }
                xp = make_uint2(sum2(0), sum2(1));
            }
        } else if constexpr (layer == 1) {
            if (warp == 7) {
                const uint32_t c1 = clk();
                while (clk() - c1 < KAD) tick(z[0]);
                if (zero) sts32(0, SM_JUNK, z[0].x);
            }
        } else {
            const uint32_t c0 = clk();
            load_wq();
            __syncwarp();
            if (elect()) mbar_arrive(SM_BAR + 56);
            if (warp == 5) {
                if (mlp) mbar_wait(SM_CBAR + 120, 0);
                asm volatile("bar.arrive 1, 192;" ::: "memory");
            }
            while (clk() - c0 < S6D + (warp - 5) * S6G) tick(wqh[0]);
            issue2(IC<0>{}, wq0[0].x | wq0[1].x | wq0[2].x | wq0[3].x | wq0[4].x | wq0[5].x);
            if (elect()) mbar_expect(warp == 5 ? SM_BAR + 4 * 64 : SM_CBAR - 32 + warp * 8, warp == 5 ? SUB : HT);
#pragma unroll 1
            for (int it = 0; it < SPIN; it++) { if (mbar_test(SM_BAR + 56, 0)) break; tick(wqh[0]); }
            const uint32_t c1 = clk();
            park();
            while (clk() - c1 < I0D) tick(wqh[0]);
            issue_help();
        }
    };

#pragma unroll 1
    for (uint32_t late = zero;; late = zero + 1) {
        if (late) {
            tail(IC<0>{});

            q_stage(IC<1>{});
            {
                const u64* qp = &g_ll[cta & ~3][tid];
                u64 w[4] = {0, 0, 0, 0};
                if (warp < 6) { w[0] = ld_rlx(qp); w[1] = ld_rlx(qp + 256); w[2] = ld_rlx(qp + 512); w[3] = ld_rlx(qp + 768); }
                mbar_wait(SM_BAR + 3 * 64 + 56, 0);
                const uint32_t ksl = ksw + lane * 16, qa = pin(q_addr()), qb0 = pin(lane < 8 ? lane * 48 : SM_ZQ - SM_VEC);
                uint32_t ks[96], qf[12];
                float mean, rstd, msq;
                ln_final(mean, rstd, msq);
                const float qc = pinf(-mean * rstd * ldsf(tid * 4, SM_CS));
#pragma unroll
                for (int k = 0; k < 6; k++) lds128(ks + 4 * k, ksl, SM_KS + k * 512);
                stsf(0, SM_FXS, fx_scale(msq));
                if (warp < 6) {
                    ll_gather4(qp, ep8() + 5, w);
                    const float q = ((hif(w[0]) + hif(w[1])) + (hif(w[2]) + hif(w[3]))) * rstd + qc;
                    const uint32_t qq = bf2_mul(pack_bf(q, q), 0x3f807180u);
                    sts16(qa, SM_VEC, qq); sts16(qa, SM_QU, qq >> 16);
                    sts32_if(!(fabsf(q) < 1048576.f), 0, SM_BIG, 1);
                    __syncwarp();
                    if (elect()) mbar_arrive(SM_QBAR);
                } else {
                    uint4 c = make_uint4(ks[0], ks[1], ks[2], ks[3]);
                    if (cta == 0 && tid == 255) g_epoch = (ep8() >> 3) + 1;
#pragma unroll 1
                    for (int it = 0; it < SPIN; it++) { if (mbar_test(SM_QBAR, 1)) break; tick(c); }
                    ks[0] = c.x; ks[1] = c.y; ks[2] = c.z; ks[3] = c.w;
                }
                issue2(IC<3>{}, ks[0] | ks[4] | ks[8] | ks[12] | ks[16] | ks[20]);
                mbar_wait(SM_QBAR, 1);
                auto load_q = [&](int u, int k) { lds128(qf + 4 * k, u == 0 ? qb0 : (tid & 24) == 8 * u ? (tid & 7) * 48 : SM_ZQ - SM_VEC, SM_VEC + k * 16); };
                load_q(0, 1); load_q(0, 2); load_q(0, 0);
                float D[4][4];
                uint4 vb[NPK + 2][6], v2[6];
                uint32_t xn = 0;
                const uint32_t t1 = __shfl_sync(~0u, lds32(0, SM_T0), 0);
                auto step = [&](auto Q) {
                    constexpr int st = Q.value, p = cord(st), s = PL.slot[p], n = PL.ld[st];
                    if constexpr (n > 0) {
                        if constexpr (st >= NPK) {
                            const uint32_t due = t1 + (P2A + n * P2B);
#pragma unroll 1
                            for (int it = 0; it < 4096; it++) if ((int)(gtime() - due) >= 0) break;
                        }
                        const uint4 (&u)[6] = vb[st - 1 < NPK ? st - 1 : NPK + ((st - 1) & 1)];
                        issue2(IC<n>{}, st > PVNOW ? 0 : u[0].x | u[1].x | u[2].x | u[3].x | u[4].x | u[5].x);
                    }
                    if constexpr (st == 14) {
#pragma unroll 1
                        for (int it = 0; it < 4096; it++) if ((int)(gtime() - t1) >= P2W) break;
                        issue2(IC<16>{}, 0);
                    }
                    if (p == 1) mbar_wait(SM_CBAR + (warp >> 2) * 8, 1);
                    else if (p == 0) mbar_wait(warp < 4 ? SM_CBAR + 24 : barw, warp < 4);
                    else mbar_wait(barw + s * 8, IC<PL.par[p]>::value);
                    load_v(vb[st < NPK ? st : NPK + (st & 1)], slot_u(s), slot_o(s));
                };
                static_for<0, 96>([&](auto I) {
                    constexpr int F = I.value, n = F / 6, i = n ? F % 6 : (F + 2) % 6;
                    const uint32_t* c = n == 0 ? (i < 2 ? ks + 3 * i : kc + 174 + 3 * i) : n < 6 ? ks + 18 * n - 12 + 3 * i : kc + 18 * (n - 6) + 3 * i;
                    const uint32_t hx = c[2] & 0x78787878u, ha = hx * (zero - 1) + c[2], hb = __funnelshift_r(hx, hx, 4);
                    if (F < 24 && F % 6 == 0) zero4(D[n]);
                    mma(D[n & 3], __byte_perm(c[0], ha, 0x5140), __byte_perm(c[0], ha, 0x7362), __byte_perm(c[1], hb, 0x5140), __byte_perm(c[1], hb, 0x7362), qf[2 * i], qf[2 * i + 1]);
                    if constexpr ((n & 3) == 3 && n < 15 && (i & 1)) load_q((n + 1) >> 2, i >> 1);
                    static_for<6, 24>([&](auto U) {
                        if constexpr (((U.value - 5) * 4 + 2) / 3 - 1 == F) {
                            lds128(ks + 4 * U.value, ksl, SM_KS + U.value * 512);
                            if constexpr (U.value % 6 == 5) { const uint32_t* k = ks + 4 * U.value - 17; issue2(IC<3 + U.value / 6>{}, k[0] | k[4] | k[8] | k[12] | k[16] | k[20]); }
                        }
                    });
                    if constexpr (F == 94) {
                        if (warp < 4) { mbar_wait(SM_CBAR + 16, 1); load_v(v2, wqw, slot_o(2)); }
                        else {
                            const char* p = reinterpret_cast<const char*>(P.v) + (size_t)(roww + vunit(2) * 256) * (DH * 2) + t * 768 + g * 16;
#pragma unroll
                            for (int k = 0; k < 6; k++)
                                asm volatile("ld.global.nc.v4.u32 {%0,%1,%2,%3}, [%4];" : "=r"(v2[k].x), "=r"(v2[k].y), "=r"(v2[k].z), "=r"(v2[k].w) : "l"(p + k * 128));
                        }
                        const uint2 x = lds64(0, SM_XN);
                        xn = x.y ? XCAP + 1 : x.x;
                        sts128(prow + lane * 16, SM_PART + 256, 0, 0, 0, 0);
                        __syncwarp();
#pragma unroll 1
                        for (uint32_t idx = lane; idx < (xn > XCAP ? 0 : xn); idx += 32) {
                            const uint32_t m = lds32(idx * 4, SM_XM);
                            if ((m >> 21) == warp) {
                                const uint4 r = lds128(idx * 16, SM_XR);
                                const uint32_t qo = ((m >> 16) & 3) * 48 + (m & 255);
                                const uint2 a = lds64(qo, SM_QU), b = lds64(qo, SM_QU + 192);
                                const float s = ((bf_lo(r.x) * bf_lo(a.x) + bf_hi(r.x) * bf_hi(a.x)) + (bf_lo(r.y) * bf_lo(b.x) + bf_hi(r.y) * bf_hi(b.x))) +
                                                ((bf_lo(r.z) * bf_lo(a.y) + bf_hi(r.z) * bf_hi(a.y)) + (bf_lo(r.w) * bf_lo(b.y) + bf_hi(r.w) * bf_hi(b.y)));
                                asm volatile("red.relaxed.cta.shared.add.f32 [%0], %1;" :: "r"(SM_PART + 256 + prow + ((m >> 18) & 7) * 64 + ((m >> 8) & 15) * 4), "f"(s) : "memory");
                            }
                        }
                        __syncwarp();
                    }
                    if constexpr (F == PK0 - 2) { refresh(); lds128(kc + 8, prow + lane * 16, SM_PART + 256); }
                    static_for<0, NPK>([&](auto Q) { if constexpr (F == (Q.value ? PK1 + (Q.value - 1) * PKD : PK0)) step(Q); });
                });
                float S[4];
                {
                    const uint32_t shp = lds32(tid * 4, SM_SH);
                    const uint4 cr = lds128(prow + lane * 16, SM_PART + 256);
                    const uint32_t c[4] = {cr.x, cr.y, cr.z, cr.w};
#pragma unroll
                    for (int j = 0; j < 4; j++) S[j] = (D[j][0] + D[j][3]) * __uint_as_float((((shp >> (8 * j)) & 255) + 27) << 23) + __uint_as_float(c[j]);
                }
                if (xn > XCAP) {
#pragma unroll
                    for (int k = 0; k < 3; k++) lds128(qf + 4 * k, (lane & 7) * 48, SM_QU + k * 16);
                    const char* kp = reinterpret_cast<const char*>(P.k) + (size_t)(roww + g) * (DH * 2) + t * 32;
#pragma unroll 1
                    for (int e = 6; e < 22; e++, kp += 256 * DH * 2) {
                        uint4 v[6];
#pragma unroll
                        for (int i = 0; i < 6; i++) v[i] = ldg128(kp + (i >> 1) * 128 + (i & 1) * 16);
                        const float s = score6(v, qf);
                        if (t == ((e >> 2) & 3)) { S[0] = S[1]; S[1] = S[2]; S[2] = S[3]; S[3] = s; }
                    }
                    if (t == 1) { const float a = S[0], b = S[1]; S[0] = S[2]; S[1] = S[3]; S[2] = a; S[3] = b; }
                }
                softmax(IC<1>{}, S);
                auto p_of = [&](int st) { return lds32(ad(t * 4, prow), SM_PART + 256 + ((vunit(cord(st)) + 6) & 15) * 16); };
                auto pv_at = [&](auto Q) { constexpr int st = Q.value; pv(vb[st < NPK ? st : NPK + (st & 1)], p_of(st)); };
                static_for<NPK, 15>([&](auto Q) {
                    constexpr int st = Q.value;
                    if constexpr (st == HWAT) head_look();
                    if constexpr (st == HWC) head_weight(IC<1>{});
                    if constexpr (st == PREP1) { tail_prep1(IC<1>{}); tail_prep2(IC<1>{}); red_addr(IC<1>{}); load_u(z, warp * WOU, SM_RING + 16 * WOU); }
                    if constexpr (st == PREP2) mlp_prep(IC<1>{});
                    uint32_t pp;
                    if constexpr (st >= PVNOW) pp = pin(p_of(st));
                    step(Q);
                    if constexpr (st - NPK < NPK) pv_at(IC<st - NPK>{});
                    if constexpr (st > NPK && st <= PVNOW) pv_at(IC<st - 1>{});
                    if constexpr (st == PV2) pv(v2, lds32(ad(t * 4, prow), SM_PART + 256 + ((vunit(2) + 6) & 15) * 16));
                    if constexpr (st >= PVNOW) pv(vb[NPK + (st & 1)], pp);
                });
            }
            tail(IC<1>{});
            if (!zero) return;
        }
        tid = threadIdx.x;
        derive();
        xp = make_uint2(0, 0);
        if (tid < 160) xp = *reinterpret_cast<const uint2*>(P.x + 4 * c4);
        else if (tid == 192) xp.x = *(volatile unsigned*)&g_epoch;
        else if (tid >= 224 && tid < 240 && mlp) xp.x = reinterpret_cast<const unsigned short*>(P.b1)[hu + lane];
        __syncwarp();
        if (elect()) {
#pragma unroll
            for (int i = 0; i < 7; i++) mbar_init(barw + i * 8, 1);
            if (warp < 4) mbar_arrive(barw);
            mbar_init(SM_CBAR + warp * 8, 1); mbar_init(SM_CBAR + 64 + warp * 8, 1);
            if (warp == 0) { mbar_init(SM_QBAR, 6); mbar_init(SM_BAR + 56, 8); }
            asm volatile("fence.mbarrier_init.release.cluster;" ::: "memory");
            sts64(warp * 8, SM_CNT, 0, 0);
            sts64(warp * 8, SM_ZQ, 0, 0);
        }
#pragma unroll
        for (int i = 12; i < 192; i++) asm volatile("mov.b32 %0, 0;" : "=r"(kc[i]));
        __syncwarp();
        if (warp < 3) { wait_due(warp, 0); if (elect()) issue_kv(warp, warp + 1, warp); }
        else mbar_wait(barw + 56, 0);
        if (tid == 192) sts32(0, SM_EPOCH, xp.x * 8);
        if (tid >= 224 && tid < 240) sts32(lane * 4, SM_B1, xp.x << 16);
        __syncthreads();
        if ((warp == 3 || warp == 4) && elect()) issue_kv(warp, warp == 4 ? 0 : 4, warp);

        load_wq();
        q_stage(IC<0>{});
        {
            int it = (warp >> 2) + 5, slot = (warp >> 2) + 1, bar = warp >> 2, par = 0;
            auto refill = [&](bool kv) {
                uint32_t old;
                asm volatile("{\n.reg .pred p;\nelect.sync _|p, 0xffffffff;\nmov.u32 %0, 0;\n@p atom.relaxed.cta.shared.inc.u32 %0, [%1], 3;\n}" : "=r"(old) : "r"(SM_CNT + slot * 8) : "memory");
                if (__any_sync(~0u, old == 3)) {
                    if (!kv && it >= 64) {
#pragma unroll 1
                        for (int k = 0; k < SPIN; k++) {
                            int f; asm volatile("ld.volatile.shared.u32 %0, [%1];" : "=r"(f) : "r"(SM_CNT + 4) : "memory");
                            if (f >= slot) break;
                        }
                        sts32(0, SM_CNT + 4, slot + 1);
                        if (elect()) issue_wo(slot);
                    } else {
                        wait_due(it, 0);
                        if (elect()) issue_kv(it, slot, bar < 5 ? bar + 5 : bar - 5);
                    }
                    __syncwarp();
                }
            };
            auto advance = [&]() { it += 2; slot += 2; if (slot >= 5) slot -= 5; bar += 2; if (bar >= 10) { bar -= 10; par ^= 1; } };
            {
                uint32_t offK[3], qf[12];
#pragma unroll
                for (int j = 0; j < 3; j++) offK[j] = pin(((tid >> 5) & 3) * SUB + 3 * g * 128 + (((2 * t) ^ ((3 * g + j) & 7)) << 4));
#pragma unroll
                for (int i = 0; i < 12; i++) qf[i] = kc[i] = 0;
                const uint32_t ksl = pin(ksw + lane * 16), sca = pin(prow + g * 64);
                int n0 = 0;
#pragma unroll 1
                for (int e = 0; e < 16; e++) {
                    mbar_wait(SM_CBAR + bar * 8, par);
                    uint4 v[6];
#pragma unroll
                    for (int i = 0; i < 6; i++) v[i] = lds128(ad(offK[i >> 1] ^ ((i & 1) * 16), slot * HT), SM_RING + (i >> 1) * 128);
                    refill(true);
                    advance();
                    if ((0xc20 | ((2 << NP) - 1)) >> e & 1) {
                        refresh();
                        static_for<0, NP>([&](auto E) {
                            if (e == E.value) {
#pragma unroll
                                for (int i = 0; i < 6; i++) {
                                    uint32_t* k = kc + 90 + 24 * E.value + 4 * i;
                                    asm volatile("mov.b32 %0, %4; mov.b32 %1, %5; mov.b32 %2, %6; mov.b32 %3, %7;" : "=r"(k[0]), "=r"(k[1]), "=r"(k[2]), "=r"(k[3]) : "r"(v[i].x), "r"(v[i].y), "r"(v[i].z), "r"(v[i].w));
                                }
                                if (E.value == NP - 2 && warp < 6) {
#pragma unroll
                                    for (int i = 0; i < 2; i++)
                                        asm volatile("cp.async.cg.shared.global [%0], [%1], 16;" :: "r"(ksl + SM_KS + 10240 + i * 512),
                                                     "l"(&g_ll[(cta & ~3) + 2 * i + (lane >> 4)][warp * 32 + (lane & 15) * 2]) : "memory");
                                }
                                if (E.value == NP - 1 && warp < 6) {
                                    asm volatile("cp.async.wait_all;" ::: "memory");
                                    __syncwarp();
                                    const uint32_t a = ksw + lane * 8;
                                    u64 w[4] = {lds_u64(a, SM_KS + 10240), lds_u64(a, SM_KS + 10496), lds_u64(a, SM_KS + 10752), lds_u64(a, SM_KS + 11008)};
                                    ll_gather4(&g_ll[cta & ~3][tid], ep8() + 1, w);
                                    const float cs = (lof(w[0] & ~255ull) + lof(w[1] & ~255ull)) + (lof(w[2] & ~255ull) + lof(w[3] & ~255ull));
                                    float q = (hif(w[0]) + hif(w[1])) + (hif(w[2]) + hif(w[3]));
                                    stsf(tid * 4, SM_CS, cs);
                                    float mean, rstd, msq;
                                    ln_final(mean, rstd, msq);
                                    stsf(0, SM_FXS, fx_scale(msq));
                                    q = (q - mean * cs) * rstd;
                                    sts16(q_addr(), SM_QU, pack_bf(q, q));
                                    __syncwarp();
                                    if (elect()) mbar_arrive(SM_QBAR);
#pragma unroll
                                    for (int i = 0; i < 12; i++) asm volatile("mov.b32 %0, 0;" : "=r"(kc[i]));
                                }
                            }
                        });
                        if (e == NP) {
                            mbar_wait(SM_QBAR, 0);
#pragma unroll
                            for (int k = 0; k < 3; k++) lds128(qf + 4 * k, (lane & 7) * 48, SM_QU + k * 16);
                            static_for<0, NP>([&](auto E) {
                                uint4 r[6];
#pragma unroll
                                for (int i = 0; i < 6; i++) { const uint32_t* k = kc + 90 + 24 * E.value + 4 * i; r[i] = make_uint4(k[0], k[1], k[2], k[3]); }
                                stsf(sca, SM_PART + 256 + (E.value + 6) * 4, score6(r, qf));
                            });
#pragma unroll
                            for (int i = 0; i < 24; i++) asm volatile("mov.b32 %0, 0;" : "=r"(kc[i]));
                        } else if (e == 5) {
#pragma unroll
                            for (int k = 0; k < 22; k++) lds128(kc + 4 * k, ksl, SM_KS + k * 512);
                            lds64(kc + 88, ksl, SM_KS + 22 * 512);
                            n0 = 0;
                        } else if (e == 10) {
#pragma unroll
                            for (int k = 0; k < 22; k++)
                                asm volatile("ld.shared.v4.b32 {%0,%1,%2,%3}, [%4];" : "=r"(kc[90 + 4 * k]), "=r"(kc[91 + 4 * k]), "=r"(kc[92 + 4 * k]), "=r"(kc[93 + 4 * k]) : "r"(ad(ksl, SM_KS + k * 512)) : "memory");
                            asm volatile("ld.shared.v2.b32 {%0,%1}, [%2];" : "=r"(kc[178]), "=r"(kc[179]) : "r"(ad(ksl, SM_KS + 22 * 512)) : "memory");
                            n0 = 0;
                        } else if (e == 11) {
                            lds64(kc + 180, ksl, SM_KS + 520); lds128(kc + 182, ksl, SM_KS + 1024); lds128(kc + 186, ksl, SM_KS + 1536); lds64(kc + 190, ksl, SM_KS + 2048);
                            n0 = 3;
                        }
                    }
                    const int n = (e + 6) & 15;
                    stsf(ad(sca, n * 4), SM_PART + 256, score6(v, qf));
                    uint32_t m = bf2_amax(bf2_amax(v[0].x, v[0].y), bf2_amax(v[0].z, v[0].w)), mn = bf2_amin(bf2_amin(v[0].x, v[0].y), bf2_amin(v[0].z, v[0].w));
#pragma unroll
                    for (int i = 1; i < 6; i++) m = bf2_amax(m, bf2_amax(bf2_amax(v[i].x, v[i].y), bf2_amax(v[i].z, v[i].w)));
                    m = max(m & 0x7fff, (m >> 16) & 0x7fff);
                    m = max(m, __shfl_xor_sync(~0u, m, 1)); m = max(m, __shfl_xor_sync(~0u, m, 2));
#pragma unroll
                    for (int i = 1; i < 6; i++) mn = bf2_amin(mn, bf2_amin(bf2_amin(v[i].x, v[i].y), bf2_amin(v[i].z, v[i].w)));
                    mn = min(mn & 0x7fff, (mn >> 16) & 0x7fff);
                    const int sh = min(max((int)(m >> 7) - 15, 0), 126);
                    asm volatile("st.shared.u8 [%0], %1;" :: "r"(ad(ad((tid >> 2) * 16, n), SM_SH)), "r"(sh) : "memory");
                    const uint32_t dn = (127 - sh) * 0x00800080u;
                    if (__any_sync(~0u, (int)(mn >> 7) <= sh || m >= (142 << 7))) {
                        if (m >= (142 << 7)) sts32(0, SM_BIG, 1);
                        const uint32_t up = (127 + 256 + sh) * 0x00800080u;
#pragma unroll
                        for (int i = 0; i < 6; i++) {
                            const uint32_t r0 = bf2_fma(bf2_mul(v[i].x, dn), up, v[i].x), r1 = bf2_fma(bf2_mul(v[i].y, dn), up, v[i].y);
                            const uint32_t r2 = bf2_fma(bf2_mul(v[i].z, dn), up, v[i].z), r3 = bf2_fma(bf2_mul(v[i].w, dn), up, v[i].w);
                            asm volatile("{\n.reg .pred p;\n.reg .u32 x, a;\nsetp.ne.u32 p, %0, 0;\nmov.u32 x, %7;\n@p atom.relaxed.cta.shared.inc.u32 x, [%6], 0x7fffffff;\n"
                                         "setp.lt.u32 p, x, %7;\nmad.lo.u32 a, x, 16, %8;\n@p st.shared.v4.u32 [a], {%1,%2,%3,%4};\n"
                                         "mad.lo.u32 a, x, 4, %9;\n@p st.shared.u32 [a], %5;\n}"
                                         :: "r"(r0 | r1 | r2 | r3), "r"(r0), "r"(r1), "r"(r2), "r"(r3), "r"(tid << 16 | n << 8 | i * 8), "r"(SM_XN), "n"(XCAP), "n"(SM_XR), "n"(SM_XM) : "memory");
                        }
                    }
                    const uint32_t ae = (n0 >> 1) * 512 + (n0 & 1) * 8, ao = ((n0 + 1) >> 1) * 512 + (~n0 & 1) * 8;
                    uint32_t o[18];
#pragma unroll
                    for (int i = 0; i < 6; i++) {
                        const uint32_t y0 = bf2_mulv(v[i].x, dn), y1 = bf2_mulv(v[i].y, dn), y2 = bf2_mulv(v[i].z, dn), y3 = bf2_mulv(v[i].w, dn);
                        o[3 * i] = __byte_perm(y0, y1, 0x6420); o[3 * i + 1] = __byte_perm(y2, y3, 0x6420);
                        const uint32_t hb = __byte_perm(y2, y3, 0x7531);
                        o[3 * i + 2] = __byte_perm(y0, y1, 0x7531) | __funnelshift_l(hb, hb, 4);
                        if (i & 1) {
#pragma unroll
                            for (int k = 3 * (i >> 1); k < 3 * (i >> 1) + 3; k++) sts64(ad(ksl, (k & 1) ? ao : ae), SM_KS + (k >> 1) * 512, o[2 * k], o[2 * k + 1]);
                        }
                    }
                    n0 += 9;
                }
                fence_async();
            }
            refresh();
            {
                const uint4 sc = lds128(prow + lane * 16, SM_PART + 256);
                const float S[4] = {__uint_as_float(sc.x), __uint_as_float(sc.y), __uint_as_float(sc.z), __uint_as_float(sc.w)};
                softmax(IC<0>{}, S);
            }
            fw = 0.f;
#pragma unroll 1
            for (int e = 0; e < 16; e++) {
                if ((1 << (PUBAT - 3) | 1 << PUBAT | 1 << ZCHK) >> e & 1) {
                    if (e == PUBAT - 3) head_look();
                    else if (e == PUBAT) {
                        head_weight(IC<0>{});
                        if (tid < 196) st_rlx(&g_ll[cta][tid + (tid >> 6 == 3) * 8], 0ull);
                    } else if (warp == 7) {
                        if ((bx & 15) == 0 && elect()) bulk_pf(P.b2, D_MODEL * 2, POL_NORMAL);
#pragma unroll 1
                        for (int k = 0; k < SPIN; k++) {
                            uint32_t v; asm volatile("ld.acquire.gpu.global.u32 %0, [%1];" : "=r"(v) : "l"(&g_zflag) : "memory");
                            if (__all_sync(~0u, v * 8 == ep8() + 8)) break;
                        }
                    }
                    __syncwarp();
                }
                const uint32_t pp = lds32(ad(t * 4, prow + ((e + 6) & 15) * 16), SM_PART + 256);
                mbar_wait(SM_CBAR + bar * 8, par);
                uint4 v[6];
                load_v(v, (warp & 3) * SUB + slot * HT, SM_RING);
                if (e < 15) refill(false);
                advance();
                pv(v, pp);
            }
        }
        tail_prep1(IC<0>{});
        __syncwarp();
    }
}

typedef CUresult (*EncodeFn)(CUtensorMap*, CUtensorMapDataType, cuuint32_t, void*, const cuuint64_t*, const cuuint64_t*, const cuuint32_t*,
                             const cuuint32_t*, CUtensorMapInterleave, CUtensorMapSwizzle, CUtensorMapL2promotion, CUtensorMapFloatOOBfill);

}

extern "C" void kernel_launch(void* const* d_in, const int* in_sizes, int n_in, void* d_out, int out_size) {
    (void)in_sizes; (void)n_in; (void)out_size;
    static EncodeFn enc = nullptr;
    if (!enc) {
        void* fn = nullptr;
        cudaDriverEntryPointQueryResult qr;
        cudaGetDriverEntryPoint("cuTensorMapEncodeTiled", &fn, cudaEnableDefault, &qr);
        enc = (EncodeFn)fn;
        cudaFuncSetAttribute(fused_kernel, cudaFuncAttributeMaxDynamicSharedMemorySize, SM_TOTAL);
    }
    Params P;
    const cuuint32_t ones[3] = {1, 1, 1};
    for (int m = TM_K; m <= TM_V8; m++) {
        const cuuint64_t dim[3] = {64, 3, (cuuint64_t)NHEAD * SK}, str[2] = {128, DH * 2};
        const cuuint32_t box[3] = {m == TM_VP ? 8u : 64u, 3, m == TM_V8 ? 8u : 32u};
        enc(&P.tm[m], CU_TENSOR_MAP_DATA_TYPE_BFLOAT16, 3, d_in[m == TM_K ? 1 : 2], dim, str, box, ones, CU_TENSOR_MAP_INTERLEAVE_NONE,
            m == TM_VP ? CU_TENSOR_MAP_SWIZZLE_NONE : CU_TENSOR_MAP_SWIZZLE_128B, CU_TENSOR_MAP_L2_PROMOTION_NONE, CU_TENSOR_MAP_FLOAT_OOB_FILL_NONE);
    }
    {
        const cuuint64_t dim[3] = {64, NHEAD * 3, D_MODEL}, str[2] = {128, NHEAD * DH * 2};
        const cuuint32_t box[3] = {64, 3, 32};
        enc(&P.tm[TM_WQ], CU_TENSOR_MAP_DATA_TYPE_BFLOAT16, 3, d_in[3], dim, str, box, ones, CU_TENSOR_MAP_INTERLEAVE_NONE,
            CU_TENSOR_MAP_SWIZZLE_128B, CU_TENSOR_MAP_L2_PROMOTION_NONE, CU_TENSOR_MAP_FLOAT_OOB_FILL_NONE);
    }
    {
        const cuuint64_t dim[2] = {DFF, D_MODEL}, str[1] = {DFF * 2};
        const cuuint32_t box[2] = {16, 128};
        enc(&P.tm[TM_W1], CU_TENSOR_MAP_DATA_TYPE_BFLOAT16, 2, d_in[6], dim, str, box, ones, CU_TENSOR_MAP_INTERLEAVE_NONE,
            CU_TENSOR_MAP_SWIZZLE_32B, CU_TENSOR_MAP_L2_PROMOTION_L2_128B, CU_TENSOR_MAP_FLOAT_OOB_FILL_NONE);
    }
    {
        const cuuint64_t dim[3] = {32, 20, NHEAD * DH}, str[2] = {64, D_MODEL * 2};
        const cuuint32_t box[3] = {32, 5, 16};
        enc(&P.tm[TM_WO], CU_TENSOR_MAP_DATA_TYPE_BFLOAT16, 3, d_in[4], dim, str, box, ones, CU_TENSOR_MAP_INTERLEAVE_NONE,
            CU_TENSOR_MAP_SWIZZLE_64B, CU_TENSOR_MAP_L2_PROMOTION_L2_128B, CU_TENSOR_MAP_FLOAT_OOB_FILL_NONE);
    }
    {
        const cuuint64_t dim[4] = {32, 20, 24, NHEAD * 8}, str[3] = {64, D_MODEL * 2, 24 * D_MODEL * 2};
        const cuuint32_t box[4] = {32, 5, 8, 4}, ones4[4] = {1, 1, 1, 1};
        enc(&P.tm[TM_WO4], CU_TENSOR_MAP_DATA_TYPE_BFLOAT16, 4, d_in[4], dim, str, box, ones4, CU_TENSOR_MAP_INTERLEAVE_NONE,
            CU_TENSOR_MAP_SWIZZLE_64B, CU_TENSOR_MAP_L2_PROMOTION_L2_128B, CU_TENSOR_MAP_FLOAT_OOB_FILL_NONE);
        const cuuint32_t thin[4] = {8, 5, 8, 4};
        enc(&P.tm[TM_WOP], CU_TENSOR_MAP_DATA_TYPE_BFLOAT16, 4, d_in[4], dim, str, thin, ones4, CU_TENSOR_MAP_INTERLEAVE_NONE,
            CU_TENSOR_MAP_SWIZZLE_NONE, CU_TENSOR_MAP_L2_PROMOTION_NONE, CU_TENSOR_MAP_FLOAT_OOB_FILL_NONE);
    }
    {
        const cuuint64_t dim[3] = {64, 10, DFF}, str[2] = {128, D_MODEL * 2};
        const cuuint32_t box[3] = {64, 10, 16};
        enc(&P.tm[TM_W2], CU_TENSOR_MAP_DATA_TYPE_BFLOAT16, 3, d_in[8], dim, str, box, ones, CU_TENSOR_MAP_INTERLEAVE_NONE,
            CU_TENSOR_MAP_SWIZZLE_128B, CU_TENSOR_MAP_L2_PROMOTION_NONE, CU_TENSOR_MAP_FLOAT_OOB_FILL_NONE);
    }
    P.x = (const __nv_bfloat16*)d_in[0];
    P.k = (const __nv_bfloat16*)d_in[1];
    P.v = (const __nv_bfloat16*)d_in[2];
    P.b1 = (const __nv_bfloat16*)d_in[7];
    P.b2 = (const __nv_bfloat16*)d_in[9];
    P.out = (__nv_bfloat16*)d_out;
    fused_kernel<<<NCTA + 1, NTHR, SM_TOTAL, cudaStreamPerThread>>>(P);
}
```
